```python
import torch

def _softmax(x, axis=-1):
    return torch.softmax(x, dim=axis)
def _gelu(x):
    return torch.nn.functional.gelu(x, approximate="tanh")
def _silu(x):
    return torch.nn.functional.silu(x)
def _sigmoid(x):
    return torch.sigmoid(x)
def _layernorm(x, axis=-1, eps=1e-5):
    m = x.mean(dim=axis, keepdim=True)
    v = x.var(dim=axis, keepdim=True, unbiased=False)
    return (x - m) / torch.sqrt(v + eps)
def _scatter_add(tgt, idx, src, axis=0):
    return tgt.clone().index_add_(axis, idx, src)
def _segment_sum(src, seg, n):
    out = torch.zeros((n,) + src.shape[1:], dtype=src.dtype)
    return out.index_add_(0, seg, src)
def _pad(x, pw):
    flat = tuple(v for pair in reversed(pw) for v in pair)
    return torch.nn.functional.pad(x, flat)

kernel_name = 'concat_heads__linear_attn_block__ssm_conv_h3__prompt'

def setup_inputs():

    _w = (lambda a: (lambda t: t.to(torch.bfloat16) if t.is_floating_point() else t)(torch.as_tensor(a)))
    def _A_setup():
        B, S, D = 1, 2048, 1024
        return {
            "x": _w((lambda *s: torch.randn(*s, dtype=torch.bfloat16) * 0.05)(B, S, D)),
            "wqkv": _w((lambda *s: torch.randn(*s, dtype=torch.bfloat16) * 1.6)(D, 3 * D)),
            "wo": _w((lambda *s: torch.randn(*s, dtype=torch.bfloat16) * 0.1)(D, D)),
        }
    _A_in = _A_setup()

    def _B_setup():
        B, S, D = 1, 2048, 1024
        ks = 4
        return {
            "q": _w((lambda *s: torch.randn(*s, dtype=torch.bfloat16) * 0.05)(B, S, D)),
            "k": _w((lambda *s: torch.randn(*s, dtype=torch.bfloat16) * 0.8)(B, S, D)),
            "v": _w((lambda *s: torch.randn(*s, dtype=torch.bfloat16) * 0.4)(B, S, D)),
            "shift_k": _w((lambda *s: torch.randn(*s, dtype=torch.bfloat16) * 0.8)(D, ks) * 0.5),
            "ssm_k": _w((lambda *s: torch.randn(*s, dtype=torch.bfloat16) * 3.2)(D, S) * (1.0 / S ** 0.5)),
            "ssm_D": _w((lambda *s: torch.randn(*s, dtype=torch.bfloat16) * 0.8)(D)),
        }
    _B_in = _B_setup()

    return {
        "A_x": _A_in["x"],
        "A_wqkv": _A_in["wqkv"],
        "A_wo": _A_in["wo"],
        "B_q": _B_in["q"],
        "B_k": _B_in["k"],
        "B_v": _B_in["v"],
        "B_shift_k": _B_in["shift_k"],
        "B_ssm_k": _B_in["ssm_k"],
        "B_ssm_D": _B_in["ssm_D"],
    }

def reference(A_x, A_wqkv, A_wo, B_q, B_k, B_v, B_shift_k, B_ssm_k, B_ssm_D):
    def _A_ref(x, wqkv, wo):
        B, S, D = x.shape
        H = 32; Dh = D // H
        qkv = (lambda x, *d: x.permute(*d))((x @ wqkv).reshape(B, S, 3, H, Dh), 2, 0, 3, 1, 4)
        q, k, v = qkv[0], qkv[1], qkv[2]
        phi = lambda t: torch.where(t > 0, t + 1, torch.exp(t)) + 1e-6
        pq, pk = phi(q), phi(k)
        kv = torch.einsum("bhsd,bhse->bhde", pk, v)
        z = torch.einsum("bhsd->bhd", pk)
        num = torch.einsum("bhqd,bhde->bhqe", pq, kv)
        den = torch.einsum("bhqd,bhd->bhq", pq, z)[..., None] + 1e-6
        o = num / den
        return (lambda x, *d: x.permute(*d))(o, 0, 2, 1, 3).reshape(B, S, D) @ wo

    def _B_ref(q, k, v, shift_k, ssm_k, ssm_D):
        B, S, D = q.shape
        ks = shift_k.shape[-1]
        k_pad = _pad(k, ((0, 0), (ks - 1, 0), (0, 0)))
        k_shift = torch.zeros_like(k)
        for t in range(ks):
            k_shift = k_shift + k_pad[:, t:t + S, :] * shift_k[:, ks - 1 - t][None, None, :]
        kv = k_shift * v
        L = 2 * S
        kv_pad = _pad(kv, ((0, 0), (0, S), (0, 0)))
        kf_pad = _pad(ssm_k, ((0, 0), (0, S)))
        kv_f = (lambda x, axes=(-2,-1): torch.fft.rfft2(x.float(), dim=axes))(kv_pad[:, None, :, :], axes=(1, 2))
        kf_f = (lambda x, axes=(-2,-1): torch.fft.rfft2(x.float(), dim=axes))(kf_pad[:, None, :], axes=(1, 2))
        kf_f = (lambda x, *d: x.permute(*d))(kf_f, 1, 2, 0)
        y_f = kv_f * kf_f[None, :, :, :]
        y = (lambda x, s, axes=(-2,-1): torch.fft.irfft2(x, s=s, dim=axes).to(torch.bfloat16))(y_f, (1, L), axes=(1, 2))[:, 0, :S, :]
        y = y + kv * ssm_D[None, None, :]
        return q * y

    a = _A_ref(A_x, A_wqkv, A_wo)
    b = _B_ref(B_q, B_k, B_v, B_shift_k, B_ssm_k, B_ssm_D)
    return torch.concatenate([a, b], axis=-1)
```

```cpp
#include <cuda.h>
#include <cuda_runtime.h>
#include <cuda_bf16.h>
#include <stdint.h>

#define DEVI __device__ __forceinline__
#define INL __attribute__((always_inline))

namespace {

DEVI void mma_kt_init(float* d, uint32_t da, uint32_t db) {
  asm volatile("{\n.reg .b64 a, b;\nmov.b64 a, {%64, 0x40000040};\nmov.b64 b, {%65, 0x40000040};\nwgmma.mma_async.sync.aligned.m64n128k16.f32.bf16.bf16 {%0, %1, %2, %3, %4, %5, %6, %7, %8, %9, %10, %11, %12, %13, %14, %15, %16, %17, %18, %19, %20, %21, %22, %23, %24, %25, %26, %27, %28, %29, %30, %31, %32, %33, %34, %35, %36, %37, %38, %39, %40, %41, %42, %43, %44, %45, %46, %47, %48, %49, %50, %51, %52, %53, %54, %55, %56, %57, %58, %59, %60, %61, %62, %63}, a, b, 0, 1, 1, 1, 0;\n}\n"
    : "=f"(d[0]), "=f"(d[1]), "=f"(d[2]), "=f"(d[3]), "=f"(d[4]), "=f"(d[5]), "=f"(d[6]), "=f"(d[7]), "=f"(d[8]), "=f"(d[9]), "=f"(d[10]), "=f"(d[11]), "=f"(d[12]), "=f"(d[13]), "=f"(d[14]), "=f"(d[15]), "=f"(d[16]), "=f"(d[17]), "=f"(d[18]), "=f"(d[19]), "=f"(d[20]), "=f"(d[21]), "=f"(d[22]), "=f"(d[23]), "=f"(d[24]), "=f"(d[25]), "=f"(d[26]), "=f"(d[27]), "=f"(d[28]), "=f"(d[29]), "=f"(d[30]), "=f"(d[31]), "=f"(d[32]), "=f"(d[33]), "=f"(d[34]), "=f"(d[35]), "=f"(d[36]), "=f"(d[37]), "=f"(d[38]), "=f"(d[39]), "=f"(d[40]), "=f"(d[41]), "=f"(d[42]), "=f"(d[43]), "=f"(d[44]), "=f"(d[45]), "=f"(d[46]), "=f"(d[47]), "=f"(d[48]), "=f"(d[49]), "=f"(d[50]), "=f"(d[51]), "=f"(d[52]), "=f"(d[53]), "=f"(d[54]), "=f"(d[55]), "=f"(d[56]), "=f"(d[57]), "=f"(d[58]), "=f"(d[59]), "=f"(d[60]), "=f"(d[61]), "=f"(d[62]), "=f"(d[63])
    : "r"(da), "r"(db));
}
DEVI void mma_kt(float* d, uint32_t da, uint32_t db) {
  asm volatile("{\n.reg .b64 a, b;\nmov.b64 a, {%64, 0x40000040};\nmov.b64 b, {%65, 0x40000040};\nwgmma.mma_async.sync.aligned.m64n128k16.f32.bf16.bf16 {%0, %1, %2, %3, %4, %5, %6, %7, %8, %9, %10, %11, %12, %13, %14, %15, %16, %17, %18, %19, %20, %21, %22, %23, %24, %25, %26, %27, %28, %29, %30, %31, %32, %33, %34, %35, %36, %37, %38, %39, %40, %41, %42, %43, %44, %45, %46, %47, %48, %49, %50, %51, %52, %53, %54, %55, %56, %57, %58, %59, %60, %61, %62, %63}, a, b, 1, 1, 1, 1, 0;\n}\n"
    : "+f"(d[0]), "+f"(d[1]), "+f"(d[2]), "+f"(d[3]), "+f"(d[4]), "+f"(d[5]), "+f"(d[6]), "+f"(d[7]), "+f"(d[8]), "+f"(d[9]), "+f"(d[10]), "+f"(d[11]), "+f"(d[12]), "+f"(d[13]), "+f"(d[14]), "+f"(d[15]), "+f"(d[16]), "+f"(d[17]), "+f"(d[18]), "+f"(d[19]), "+f"(d[20]), "+f"(d[21]), "+f"(d[22]), "+f"(d[23]), "+f"(d[24]), "+f"(d[25]), "+f"(d[26]), "+f"(d[27]), "+f"(d[28]), "+f"(d[29]), "+f"(d[30]), "+f"(d[31]), "+f"(d[32]), "+f"(d[33]), "+f"(d[34]), "+f"(d[35]), "+f"(d[36]), "+f"(d[37]), "+f"(d[38]), "+f"(d[39]), "+f"(d[40]), "+f"(d[41]), "+f"(d[42]), "+f"(d[43]), "+f"(d[44]), "+f"(d[45]), "+f"(d[46]), "+f"(d[47]), "+f"(d[48]), "+f"(d[49]), "+f"(d[50]), "+f"(d[51]), "+f"(d[52]), "+f"(d[53]), "+f"(d[54]), "+f"(d[55]), "+f"(d[56]), "+f"(d[57]), "+f"(d[58]), "+f"(d[59]), "+f"(d[60]), "+f"(d[61]), "+f"(d[62]), "+f"(d[63])
    : "r"(da), "r"(db));
}
DEVI void mma_n128_init(float* d, uint32_t da, uint32_t db) {
  asm volatile("{\n.reg .b64 a, b;\nmov.b64 a, {%64, 0x40000040};\nmov.b64 b, {%65, 0x40000040};\nwgmma.mma_async.sync.aligned.m64n128k16.f32.bf16.bf16 {%0, %1, %2, %3, %4, %5, %6, %7, %8, %9, %10, %11, %12, %13, %14, %15, %16, %17, %18, %19, %20, %21, %22, %23, %24, %25, %26, %27, %28, %29, %30, %31, %32, %33, %34, %35, %36, %37, %38, %39, %40, %41, %42, %43, %44, %45, %46, %47, %48, %49, %50, %51, %52, %53, %54, %55, %56, %57, %58, %59, %60, %61, %62, %63}, a, b, 0, 1, 1, 0, 1;\n}\n"
    : "=f"(d[0]), "=f"(d[1]), "=f"(d[2]), "=f"(d[3]), "=f"(d[4]), "=f"(d[5]), "=f"(d[6]), "=f"(d[7]), "=f"(d[8]), "=f"(d[9]), "=f"(d[10]), "=f"(d[11]), "=f"(d[12]), "=f"(d[13]), "=f"(d[14]), "=f"(d[15]), "=f"(d[16]), "=f"(d[17]), "=f"(d[18]), "=f"(d[19]), "=f"(d[20]), "=f"(d[21]), "=f"(d[22]), "=f"(d[23]), "=f"(d[24]), "=f"(d[25]), "=f"(d[26]), "=f"(d[27]), "=f"(d[28]), "=f"(d[29]), "=f"(d[30]), "=f"(d[31]), "=f"(d[32]), "=f"(d[33]), "=f"(d[34]), "=f"(d[35]), "=f"(d[36]), "=f"(d[37]), "=f"(d[38]), "=f"(d[39]), "=f"(d[40]), "=f"(d[41]), "=f"(d[42]), "=f"(d[43]), "=f"(d[44]), "=f"(d[45]), "=f"(d[46]), "=f"(d[47]), "=f"(d[48]), "=f"(d[49]), "=f"(d[50]), "=f"(d[51]), "=f"(d[52]), "=f"(d[53]), "=f"(d[54]), "=f"(d[55]), "=f"(d[56]), "=f"(d[57]), "=f"(d[58]), "=f"(d[59]), "=f"(d[60]), "=f"(d[61]), "=f"(d[62]), "=f"(d[63])
    : "r"(da), "r"(db));
}
DEVI void mma_n128(float* d, uint32_t da, uint32_t db) {
  asm volatile("{\n.reg .b64 a, b;\nmov.b64 a, {%64, 0x40000040};\nmov.b64 b, {%65, 0x40000040};\nwgmma.mma_async.sync.aligned.m64n128k16.f32.bf16.bf16 {%0, %1, %2, %3, %4, %5, %6, %7, %8, %9, %10, %11, %12, %13, %14, %15, %16, %17, %18, %19, %20, %21, %22, %23, %24, %25, %26, %27, %28, %29, %30, %31, %32, %33, %34, %35, %36, %37, %38, %39, %40, %41, %42, %43, %44, %45, %46, %47, %48, %49, %50, %51, %52, %53, %54, %55, %56, %57, %58, %59, %60, %61, %62, %63}, a, b, 1, 1, 1, 0, 1;\n}\n"
    : "+f"(d[0]), "+f"(d[1]), "+f"(d[2]), "+f"(d[3]), "+f"(d[4]), "+f"(d[5]), "+f"(d[6]), "+f"(d[7]), "+f"(d[8]), "+f"(d[9]), "+f"(d[10]), "+f"(d[11]), "+f"(d[12]), "+f"(d[13]), "+f"(d[14]), "+f"(d[15]), "+f"(d[16]), "+f"(d[17]), "+f"(d[18]), "+f"(d[19]), "+f"(d[20]), "+f"(d[21]), "+f"(d[22]), "+f"(d[23]), "+f"(d[24]), "+f"(d[25]), "+f"(d[26]), "+f"(d[27]), "+f"(d[28]), "+f"(d[29]), "+f"(d[30]), "+f"(d[31]), "+f"(d[32]), "+f"(d[33]), "+f"(d[34]), "+f"(d[35]), "+f"(d[36]), "+f"(d[37]), "+f"(d[38]), "+f"(d[39]), "+f"(d[40]), "+f"(d[41]), "+f"(d[42]), "+f"(d[43]), "+f"(d[44]), "+f"(d[45]), "+f"(d[46]), "+f"(d[47]), "+f"(d[48]), "+f"(d[49]), "+f"(d[50]), "+f"(d[51]), "+f"(d[52]), "+f"(d[53]), "+f"(d[54]), "+f"(d[55]), "+f"(d[56]), "+f"(d[57]), "+f"(d[58]), "+f"(d[59]), "+f"(d[60]), "+f"(d[61]), "+f"(d[62]), "+f"(d[63])
    : "r"(da), "r"(db));
}
DEVI void mma_n64_init(float* d, uint32_t da, uint32_t db) {
  asm volatile("{\n.reg .b64 a, b;\nmov.b64 a, {%32, 0x40000040};\nmov.b64 b, {%33, 0x40000040};\nwgmma.mma_async.sync.aligned.m64n64k16.f32.bf16.bf16 {%0, %1, %2, %3, %4, %5, %6, %7, %8, %9, %10, %11, %12, %13, %14, %15, %16, %17, %18, %19, %20, %21, %22, %23, %24, %25, %26, %27, %28, %29, %30, %31}, a, b, 0, 1, 1, 0, 1;\n}\n"
    : "=f"(d[0]), "=f"(d[1]), "=f"(d[2]), "=f"(d[3]), "=f"(d[4]), "=f"(d[5]), "=f"(d[6]), "=f"(d[7]), "=f"(d[8]), "=f"(d[9]), "=f"(d[10]), "=f"(d[11]), "=f"(d[12]), "=f"(d[13]), "=f"(d[14]), "=f"(d[15]), "=f"(d[16]), "=f"(d[17]), "=f"(d[18]), "=f"(d[19]), "=f"(d[20]), "=f"(d[21]), "=f"(d[22]), "=f"(d[23]), "=f"(d[24]), "=f"(d[25]), "=f"(d[26]), "=f"(d[27]), "=f"(d[28]), "=f"(d[29]), "=f"(d[30]), "=f"(d[31])
    : "r"(da), "r"(db));
}
DEVI void mma_n64(float* d, uint32_t da, uint32_t db) {
  asm volatile("{\n.reg .b64 a, b;\nmov.b64 a, {%32, 0x40000040};\nmov.b64 b, {%33, 0x40000040};\nwgmma.mma_async.sync.aligned.m64n64k16.f32.bf16.bf16 {%0, %1, %2, %3, %4, %5, %6, %7, %8, %9, %10, %11, %12, %13, %14, %15, %16, %17, %18, %19, %20, %21, %22, %23, %24, %25, %26, %27, %28, %29, %30, %31}, a, b, 1, 1, 1, 0, 1;\n}\n"
    : "+f"(d[0]), "+f"(d[1]), "+f"(d[2]), "+f"(d[3]), "+f"(d[4]), "+f"(d[5]), "+f"(d[6]), "+f"(d[7]), "+f"(d[8]), "+f"(d[9]), "+f"(d[10]), "+f"(d[11]), "+f"(d[12]), "+f"(d[13]), "+f"(d[14]), "+f"(d[15]), "+f"(d[16]), "+f"(d[17]), "+f"(d[18]), "+f"(d[19]), "+f"(d[20]), "+f"(d[21]), "+f"(d[22]), "+f"(d[23]), "+f"(d[24]), "+f"(d[25]), "+f"(d[26]), "+f"(d[27]), "+f"(d[28]), "+f"(d[29]), "+f"(d[30]), "+f"(d[31])
    : "r"(da), "r"(db));
}
DEVI void mma_kv_init(float* d, const uint32_t* a, uint32_t db) {
  asm volatile("{\n.reg .b64 b;\nmov.b64 b, {%40, 0x40000040};\nwgmma.mma_async.sync.aligned.m64n72k16.f32.bf16.bf16 {%0, %1, %2, %3, %4, %5, %6, %7, %8, %9, %10, %11, %12, %13, %14, %15, %16, %17, %18, %19, %20, %21, %22, %23, %24, %25, %26, %27, %28, %29, %30, %31, %32, %33, %34, %35}, {%36,%37,%38,%39}, b, 0, 1, 1, 1;\n}\n"
    : "=f"(d[0]), "=f"(d[1]), "=f"(d[2]), "=f"(d[3]), "=f"(d[4]), "=f"(d[5]), "=f"(d[6]), "=f"(d[7]), "=f"(d[8]), "=f"(d[9]), "=f"(d[10]), "=f"(d[11]), "=f"(d[12]), "=f"(d[13]), "=f"(d[14]), "=f"(d[15]), "=f"(d[16]), "=f"(d[17]), "=f"(d[18]), "=f"(d[19]), "=f"(d[20]), "=f"(d[21]), "=f"(d[22]), "=f"(d[23]), "=f"(d[24]), "=f"(d[25]), "=f"(d[26]), "=f"(d[27]), "=f"(d[28]), "=f"(d[29]), "=f"(d[30]), "=f"(d[31]), "=f"(d[32]), "=f"(d[33]), "=f"(d[34]), "=f"(d[35])
    : "r"(a[0]), "r"(a[1]), "r"(a[2]), "r"(a[3]), "r"(db));
}
DEVI void mma_kv(float* d, const uint32_t* a, uint32_t db) {
  asm volatile("{\n.reg .b64 b;\nmov.b64 b, {%40, 0x40000040};\nwgmma.mma_async.sync.aligned.m64n72k16.f32.bf16.bf16 {%0, %1, %2, %3, %4, %5, %6, %7, %8, %9, %10, %11, %12, %13, %14, %15, %16, %17, %18, %19, %20, %21, %22, %23, %24, %25, %26, %27, %28, %29, %30, %31, %32, %33, %34, %35}, {%36,%37,%38,%39}, b, 1, 1, 1, 1;\n}\n"
    : "+f"(d[0]), "+f"(d[1]), "+f"(d[2]), "+f"(d[3]), "+f"(d[4]), "+f"(d[5]), "+f"(d[6]), "+f"(d[7]), "+f"(d[8]), "+f"(d[9]), "+f"(d[10]), "+f"(d[11]), "+f"(d[12]), "+f"(d[13]), "+f"(d[14]), "+f"(d[15]), "+f"(d[16]), "+f"(d[17]), "+f"(d[18]), "+f"(d[19]), "+f"(d[20]), "+f"(d[21]), "+f"(d[22]), "+f"(d[23]), "+f"(d[24]), "+f"(d[25]), "+f"(d[26]), "+f"(d[27]), "+f"(d[28]), "+f"(d[29]), "+f"(d[30]), "+f"(d[31]), "+f"(d[32]), "+f"(d[33]), "+f"(d[34]), "+f"(d[35])
    : "r"(a[0]), "r"(a[1]), "r"(a[2]), "r"(a[3]), "r"(db));
}
DEVI void mma_o_init(float* d, const uint32_t* a, uint32_t db) {
  asm volatile("{\n.reg .b64 b;\nmov.b64 b, {%24, 0x20};\nwgmma.mma_async.sync.aligned.m64n40k16.f32.bf16.bf16 {%0, %1, %2, %3, %4, %5, %6, %7, %8, %9, %10, %11, %12, %13, %14, %15, %16, %17, %18, %19}, {%20,%21,%22,%23}, b, 0, 1, 1, 1;\n}\n"
    : "=f"(d[0]), "=f"(d[1]), "=f"(d[2]), "=f"(d[3]), "=f"(d[4]), "=f"(d[5]), "=f"(d[6]), "=f"(d[7]), "=f"(d[8]), "=f"(d[9]), "=f"(d[10]), "=f"(d[11]), "=f"(d[12]), "=f"(d[13]), "=f"(d[14]), "=f"(d[15]), "=f"(d[16]), "=f"(d[17]), "=f"(d[18]), "=f"(d[19])
    : "r"(a[0]), "r"(a[1]), "r"(a[2]), "r"(a[3]), "r"(db));
}
DEVI void mma_o(float* d, const uint32_t* a, uint32_t db) {
  asm volatile("{\n.reg .b64 b;\nmov.b64 b, {%24, 0x20};\nwgmma.mma_async.sync.aligned.m64n40k16.f32.bf16.bf16 {%0, %1, %2, %3, %4, %5, %6, %7, %8, %9, %10, %11, %12, %13, %14, %15, %16, %17, %18, %19}, {%20,%21,%22,%23}, b, 1, 1, 1, 1;\n}\n"
    : "+f"(d[0]), "+f"(d[1]), "+f"(d[2]), "+f"(d[3]), "+f"(d[4]), "+f"(d[5]), "+f"(d[6]), "+f"(d[7]), "+f"(d[8]), "+f"(d[9]), "+f"(d[10]), "+f"(d[11]), "+f"(d[12]), "+f"(d[13]), "+f"(d[14]), "+f"(d[15]), "+f"(d[16]), "+f"(d[17]), "+f"(d[18]), "+f"(d[19])
    : "r"(a[0]), "r"(a[1]), "r"(a[2]), "r"(a[3]), "r"(db));
}
DEVI void mma_s1_init(uint32_t* d, const uint32_t* a, uint32_t db) {
  asm volatile("{\n.reg .b64 b;\nmov.b64 b, {%36, 0x20};\nwgmma.mma_async.sync.aligned.m64n128k16.f16.f16.f16 {%0, %1, %2, %3, %4, %5, %6, %7, %8, %9, %10, %11, %12, %13, %14, %15, %16, %17, %18, %19, %20, %21, %22, %23, %24, %25, %26, %27, %28, %29, %30, %31}, {%32,%33,%34,%35}, b, 0, 1, 1, 1;\n}\n"
    : "=r"(d[0]), "=r"(d[1]), "=r"(d[2]), "=r"(d[3]), "=r"(d[4]), "=r"(d[5]), "=r"(d[6]), "=r"(d[7]), "=r"(d[8]), "=r"(d[9]), "=r"(d[10]), "=r"(d[11]), "=r"(d[12]), "=r"(d[13]), "=r"(d[14]), "=r"(d[15]), "=r"(d[16]), "=r"(d[17]), "=r"(d[18]), "=r"(d[19]), "=r"(d[20]), "=r"(d[21]), "=r"(d[22]), "=r"(d[23]), "=r"(d[24]), "=r"(d[25]), "=r"(d[26]), "=r"(d[27]), "=r"(d[28]), "=r"(d[29]), "=r"(d[30]), "=r"(d[31])
    : "r"(a[0]), "r"(a[1]), "r"(a[2]), "r"(a[3]), "r"(db));
}
DEVI void mma_s1(uint32_t* d, const uint32_t* a, uint32_t db) {
  asm volatile("{\n.reg .b64 b;\nmov.b64 b, {%36, 0x20};\nwgmma.mma_async.sync.aligned.m64n128k16.f16.f16.f16 {%0, %1, %2, %3, %4, %5, %6, %7, %8, %9, %10, %11, %12, %13, %14, %15, %16, %17, %18, %19, %20, %21, %22, %23, %24, %25, %26, %27, %28, %29, %30, %31}, {%32,%33,%34,%35}, b, 1, 1, 1, 1;\n}\n"
    : "+r"(d[0]), "+r"(d[1]), "+r"(d[2]), "+r"(d[3]), "+r"(d[4]), "+r"(d[5]), "+r"(d[6]), "+r"(d[7]), "+r"(d[8]), "+r"(d[9]), "+r"(d[10]), "+r"(d[11]), "+r"(d[12]), "+r"(d[13]), "+r"(d[14]), "+r"(d[15]), "+r"(d[16]), "+r"(d[17]), "+r"(d[18]), "+r"(d[19]), "+r"(d[20]), "+r"(d[21]), "+r"(d[22]), "+r"(d[23]), "+r"(d[24]), "+r"(d[25]), "+r"(d[26]), "+r"(d[27]), "+r"(d[28]), "+r"(d[29]), "+r"(d[30]), "+r"(d[31])
    : "r"(a[0]), "r"(a[1]), "r"(a[2]), "r"(a[3]), "r"(db));
}
DEVI void mma_s2_init(uint32_t* d, const uint32_t* a, uint32_t db) {
  asm volatile("{\n.reg .b64 b;\nmov.b64 b, {%12, 0x10};\nwgmma.mma_async.sync.aligned.m64n32k16.f16.f16.f16 {%0, %1, %2, %3, %4, %5, %6, %7}, {%8,%9,%10,%11}, b, 0, 1, 1, 0;\n}\n"
    : "=r"(d[0]), "=r"(d[1]), "=r"(d[2]), "=r"(d[3]), "=r"(d[4]), "=r"(d[5]), "=r"(d[6]), "=r"(d[7])
    : "r"(a[0]), "r"(a[1]), "r"(a[2]), "r"(a[3]), "r"(db));
}
DEVI void mma_s2(uint32_t* d, const uint32_t* a, uint32_t db) {
  asm volatile("{\n.reg .b64 b;\nmov.b64 b, {%12, 0x10};\nwgmma.mma_async.sync.aligned.m64n32k16.f16.f16.f16 {%0, %1, %2, %3, %4, %5, %6, %7}, {%8,%9,%10,%11}, b, 1, 1, 1, 0;\n}\n"
    : "+r"(d[0]), "+r"(d[1]), "+r"(d[2]), "+r"(d[3]), "+r"(d[4]), "+r"(d[5]), "+r"(d[6]), "+r"(d[7])
    : "r"(a[0]), "r"(a[1]), "r"(a[2]), "r"(a[3]), "r"(db));
}
DEVI void mma_s2_neg(uint32_t* d, const uint32_t* a, uint32_t db) {
  asm volatile("{\n.reg .b64 b;\nmov.b64 b, {%12, 0x10};\nwgmma.mma_async.sync.aligned.m64n32k16.f16.f16.f16 {%0, %1, %2, %3, %4, %5, %6, %7}, {%8,%9,%10,%11}, b, 1, -1, 1, 0;\n}\n"
    : "+r"(d[0]), "+r"(d[1]), "+r"(d[2]), "+r"(d[3]), "+r"(d[4]), "+r"(d[5]), "+r"(d[6]), "+r"(d[7])
    : "r"(a[0]), "r"(a[1]), "r"(a[2]), "r"(a[3]), "r"(db));
}
DEVI void mma_i2_init(float* d, const uint32_t* a, uint32_t db, uint32_t meta) {
  asm volatile("{\n.reg .b64 b;\nmov.b64 b, {%68, 0x80};\nwgmma.mma_async.sp.sync.aligned.m64n128k32.f32.f16.f16 {%0, %1, %2, %3, %4, %5, %6, %7, %8, %9, %10, %11, %12, %13, %14, %15, %16, %17, %18, %19, %20, %21, %22, %23, %24, %25, %26, %27, %28, %29, %30, %31, %32, %33, %34, %35, %36, %37, %38, %39, %40, %41, %42, %43, %44, %45, %46, %47, %48, %49, %50, %51, %52, %53, %54, %55, %56, %57, %58, %59, %60, %61, %62, %63}, {%64,%65,%66,%67}, b, %69, 0, 0, 1, 1, 1;\n}\n"
    : "=f"(d[0]), "=f"(d[1]), "=f"(d[2]), "=f"(d[3]), "=f"(d[4]), "=f"(d[5]), "=f"(d[6]), "=f"(d[7]), "=f"(d[8]), "=f"(d[9]), "=f"(d[10]), "=f"(d[11]), "=f"(d[12]), "=f"(d[13]), "=f"(d[14]), "=f"(d[15]), "=f"(d[16]), "=f"(d[17]), "=f"(d[18]), "=f"(d[19]), "=f"(d[20]), "=f"(d[21]), "=f"(d[22]), "=f"(d[23]), "=f"(d[24]), "=f"(d[25]), "=f"(d[26]), "=f"(d[27]), "=f"(d[28]), "=f"(d[29]), "=f"(d[30]), "=f"(d[31]), "=f"(d[32]), "=f"(d[33]), "=f"(d[34]), "=f"(d[35]), "=f"(d[36]), "=f"(d[37]), "=f"(d[38]), "=f"(d[39]), "=f"(d[40]), "=f"(d[41]), "=f"(d[42]), "=f"(d[43]), "=f"(d[44]), "=f"(d[45]), "=f"(d[46]), "=f"(d[47]), "=f"(d[48]), "=f"(d[49]), "=f"(d[50]), "=f"(d[51]), "=f"(d[52]), "=f"(d[53]), "=f"(d[54]), "=f"(d[55]), "=f"(d[56]), "=f"(d[57]), "=f"(d[58]), "=f"(d[59]), "=f"(d[60]), "=f"(d[61]), "=f"(d[62]), "=f"(d[63])
    : "r"(a[0]), "r"(a[1]), "r"(a[2]), "r"(a[3]), "r"(db), "r"(meta));
}
DEVI void mma_i2(float* d, const uint32_t* a, uint32_t db, uint32_t meta) {
  asm volatile("{\n.reg .b64 b;\nmov.b64 b, {%68, 0x80};\nwgmma.mma_async.sp.sync.aligned.m64n128k32.f32.f16.f16 {%0, %1, %2, %3, %4, %5, %6, %7, %8, %9, %10, %11, %12, %13, %14, %15, %16, %17, %18, %19, %20, %21, %22, %23, %24, %25, %26, %27, %28, %29, %30, %31, %32, %33, %34, %35, %36, %37, %38, %39, %40, %41, %42, %43, %44, %45, %46, %47, %48, %49, %50, %51, %52, %53, %54, %55, %56, %57, %58, %59, %60, %61, %62, %63}, {%64,%65,%66,%67}, b, %69, 0, 1, 1, 1, 1;\n}\n"
    : "+f"(d[0]), "+f"(d[1]), "+f"(d[2]), "+f"(d[3]), "+f"(d[4]), "+f"(d[5]), "+f"(d[6]), "+f"(d[7]), "+f"(d[8]), "+f"(d[9]), "+f"(d[10]), "+f"(d[11]), "+f"(d[12]), "+f"(d[13]), "+f"(d[14]), "+f"(d[15]), "+f"(d[16]), "+f"(d[17]), "+f"(d[18]), "+f"(d[19]), "+f"(d[20]), "+f"(d[21]), "+f"(d[22]), "+f"(d[23]), "+f"(d[24]), "+f"(d[25]), "+f"(d[26]), "+f"(d[27]), "+f"(d[28]), "+f"(d[29]), "+f"(d[30]), "+f"(d[31]), "+f"(d[32]), "+f"(d[33]), "+f"(d[34]), "+f"(d[35]), "+f"(d[36]), "+f"(d[37]), "+f"(d[38]), "+f"(d[39]), "+f"(d[40]), "+f"(d[41]), "+f"(d[42]), "+f"(d[43]), "+f"(d[44]), "+f"(d[45]), "+f"(d[46]), "+f"(d[47]), "+f"(d[48]), "+f"(d[49]), "+f"(d[50]), "+f"(d[51]), "+f"(d[52]), "+f"(d[53]), "+f"(d[54]), "+f"(d[55]), "+f"(d[56]), "+f"(d[57]), "+f"(d[58]), "+f"(d[59]), "+f"(d[60]), "+f"(d[61]), "+f"(d[62]), "+f"(d[63])
    : "r"(a[0]), "r"(a[1]), "r"(a[2]), "r"(a[3]), "r"(db), "r"(meta));
}
__device__ const __align__(128) uint32_t d_tab[2944] = {
  0x3bf63c00,0x2e460000,0x391339a8,0x3a2f39a8,0x3ba83bd9,0x34a5323e,0x378b3872,0x3b0e3aa7,0x3b0e3b64,0x378b361f,0x34a5361f,0x3ba83b64,
  0x3a2f3aa7,0x39133872,0x2e46323e,0x3bf63bd9,0x3b0e3c00,0x378b0000,0xb4a5b9a8,0xbba8b9a8,0x2e463872,0x3bf63aa7,0x3913323e,0xba2fbbd9,
  0xba2fb61f,0x39133b64,0x3bf63b64,0x2e46b61f,0xbba8bbd9,0xb4a5323e,0x378b3aa7,0x3b0e3872,0x39133c00,0x3a2f0000,0xae4639a8,0x3bf639a8,
  0xbb0eb23e,0x378b3bd9,0xbba8baa7,0xb4a53872,0xb4a5bb64,0xbba8b61f,0x378bb61f,0xbb0ebb64,0x3bf63872,0xae46baa7,0x3a2f3bd9,0x3913b23e,
  0x34a53c00,0x3ba80000,0x378bb9a8,0xbb0eb9a8,0xba2fbaa7,0xb9133872,0x2e463bd9,0x3bf6323e,0x3bf6361f,0x2e46bb64,0xb913bb64,0xba2f361f,
  0xbb0e323e,0x378b3bd9,0x3ba83872,0x34a5baa7,0xae463c00,0x3bf60000,0xba2f39a8,0x391339a8,0x34a5bbd9,0xbba8b23e,0x3b0eb872,0xb78bbaa7,
  0xb78b3b64,0x3b0e361f,0xbba8361f,0x34a53b64,0x3913baa7,0xba2fb872,0x3bf6b23e,0xae46bbd9,0xb78b3c00,0x3b0e0000,0x3ba8b9a8,0xb4a5b9a8,
  0x3bf6b872,0xae46baa7,0xba2fb23e,0xb9133bd9,0xb913b61f,0xba2f3b64,0xae463b64,0x3bf6b61f,0xb4a53bd9,0x3ba8b23e,0x3b0ebaa7,0xb78bb872,
  0xba2f3c00,0x39130000,0xbbf639a8,0xae4639a8,0x378b323e,0x3b0ebbd9,0xb4a53aa7,0x3ba8b872,0x3ba8bb64,0xb4a5b61f,0x3b0eb61f,0x378bbb64,
  0xae46b872,0xbbf63aa7,0x3913bbd9,0xba2f323e,0xbba83c00,0x34a50000,0x3b0eb9a8,0x378bb9a8,0xb9133aa7,0x3a2fb872,0x3bf6bbd9,0xae46b23e,
  0xae46361f,0x3bf6bb64,0x3a2fbb64,0xb913361f,0x378bb23e,0x3b0ebbd9,0x34a5b872,0xbba83aa7,0xbbf63c00,0xae460000,0xb91339a8,0xba2f39a8,
  0xbba83bd9,0xb4a5323e,0xb78b3872,0xbb0e3aa7,0xbb0e3b64,0xb78b361f,0xb4a5361f,0xbba83b64,0xba2f3aa7,0xb9133872,0xae46323e,0xbbf63bd9,
  0xbb0e3c00,0xb78b0000,0x34a5b9a8,0x3ba8b9a8,0xae463872,0xbbf63aa7,0xb913323e,0x3a2fbbd9,0x3a2fb61f,0xb9133b64,0xbbf63b64,0xae46b61f,
  0x3ba8bbd9,0x34a5323e,0xb78b3aa7,0xbb0e3872,0xb9133c00,0xba2f0000,0x2e4639a8,0xbbf639a8,0x3b0eb23e,0xb78b3bd9,0x3ba8baa7,0x34a53872,
  0x34a5bb64,0x3ba8b61f,0xb78bb61f,0x3b0ebb64,0xbbf63872,0x2e46baa7,0xba2f3bd9,0xb913b23e,0xb4a53c00,0xbba80000,0xb78bb9a8,0x3b0eb9a8,
  0x3a2fbaa7,0x39133872,0xae463bd9,0xbbf6323e,0xbbf6361f,0xae46bb64,0x3913bb64,0x3a2f361f,0x3b0e323e,0xb78b3bd9,0xbba83872,0xb4a5baa7,
  0x2e463c00,0xbbf60000,0x3a2f39a8,0xb91339a8,0xb4a5bbd9,0x3ba8b23e,0xbb0eb872,0x378bbaa7,0x378b3b64,0xbb0e361f,0x3ba8361f,0xb4a53b64,
  0xb913baa7,0x3a2fb872,0xbbf6b23e,0x2e46bbd9,0x378b3c00,0xbb0e0000,0xbba8b9a8,0x34a5b9a8,0xbbf6b872,0x2e46baa7,0x3a2fb23e,0x39133bd9,
  0x3913b61f,0x3a2f3b64,0x2e463b64,0xbbf6b61f,0x34a53bd9,0xbba8b23e,0xbb0ebaa7,0x378bb872,0x3a2f3c00,0xb9130000,0x3bf639a8,0x2e4639a8,
  0xb78b323e,0xbb0ebbd9,0x34a53aa7,0xbba8b872,0xbba8bb64,0x34a5b61f,0xbb0eb61f,0xb78bbb64,0x2e46b872,0x3bf63aa7,0xb913bbd9,0x3a2f323e,
  0x3ba83c00,0xb4a50000,0xbb0eb9a8,0xb78bb9a8,0x39133aa7,0xba2fb872,0xbbf6bbd9,0x2e46b23e,0x2e46361f,0xbbf6bb64,0xba2fbb64,0x3913361f,
  0xb78bb23e,0xbb0ebbd9,0xb4a5b872,0x3ba83aa7,0x3bf63c00,0x2e460000,0x391339a8,0x3a2f39a8,0x3ba83bd9,0x34a5323e,0x378b3872,0x3b0e3aa7,
  0x3b0e3b64,0x378b361f,0x34a5361f,0x3ba83b64,0x3a2f3aa7,0x39133872,0x2e46323e,0x3bf63bd9,0x3b0e3c00,0x378b0000,0xb4a5b9a8,0xbba8b9a8,
  0x2e463872,0x3bf63aa7,0x3913323e,0xba2fbbd9,0xba2fb61f,0x39133b64,0x3bf63b64,0x2e46b61f,0xbba8bbd9,0xb4a5323e,0x378b3aa7,0x3b0e3872,
  0x39133c00,0x3a2f0000,0xae4639a8,0x3bf639a8,0xbb0eb23e,0x378b3bd9,0xbba8baa7,0xb4a53872,0xb4a5bb64,0xbba8b61f,0x378bb61f,0xbb0ebb64,
  0x3bf63872,0xae46baa7,0x3a2f3bd9,0x3913b23e,0x34a53c00,0x3ba80000,0x378bb9a8,0xbb0eb9a8,0xba2fbaa7,0xb9133872,0x2e463bd9,0x3bf6323e,
  0x3bf6361f,0x2e46bb64,0xb913bb64,0xba2f361f,0xbb0e323e,0x378b3bd9,0x3ba83872,0x34a5baa7,0xae463c00,0x3bf60000,0xba2f39a8,0x391339a8,
  0x34a5bbd9,0xbba8b23e,0x3b0eb872,0xb78bbaa7,0xb78b3b64,0x3b0e361f,0xbba8361f,0x34a53b64,0x3913baa7,0xba2fb872,0x3bf6b23e,0xae46bbd9,
  0xb78b3c00,0x3b0e0000,0x3ba8b9a8,0xb4a5b9a8,0x3bf6b872,0xae46baa7,0xba2fb23e,0xb9133bd9,0xb913b61f,0xba2f3b64,0xae463b64,0x3bf6b61f,
  0xb4a53bd9,0x3ba8b23e,0x3b0ebaa7,0xb78bb872,0xba2f3c00,0x39130000,0xbbf639a8,0xae4639a8,0x378b323e,0x3b0ebbd9,0xb4a53aa7,0x3ba8b872,
  0x3ba8bb64,0xb4a5b61f,0x3b0eb61f,0x378bbb64,0xae46b872,0xbbf63aa7,0x3913bbd9,0xba2f323e,0xbba83c00,0x34a50000,0x3b0eb9a8,0x378bb9a8,
  0xb9133aa7,0x3a2fb872,0x3bf6bbd9,0xae46b23e,0xae46361f,0x3bf6bb64,0x3a2fbb64,0xb913361f,0x378bb23e,0x3b0ebbd9,0x34a5b872,0xbba83aa7,
  0xbbf63c00,0xae460000,0xb91339a8,0xba2f39a8,0xbba83bd9,0xb4a5323e,0xb78b3872,0xbb0e3aa7,0xbb0e3b64,0xb78b361f,0xb4a5361f,0xbba83b64,
  0xba2f3aa7,0xb9133872,0xae46323e,0xbbf63bd9,0xbb0e3c00,0xb78b0000,0x34a5b9a8,0x3ba8b9a8,0xae463872,0xbbf63aa7,0xb913323e,0x3a2fbbd9,
  0x3a2fb61f,0xb9133b64,0xbbf63b64,0xae46b61f,0x3ba8bbd9,0x34a5323e,0xb78b3aa7,0xbb0e3872,0xb9133c00,0xba2f0000,0x2e4639a8,0xbbf639a8,
  0x3b0eb23e,0xb78b3bd9,0x3ba8baa7,0x34a53872,0x34a5bb64,0x3ba8b61f,0xb78bb61f,0x3b0ebb64,0xbbf63872,0x2e46baa7,0xba2f3bd9,0xb913b23e,
  0xb4a53c00,0xbba80000,0xb78bb9a8,0x3b0eb9a8,0x3a2fbaa7,0x39133872,0xae463bd9,0xbbf6323e,0xbbf6361f,0xae46bb64,0x3913bb64,0x3a2f361f,
  0x3b0e323e,0xb78b3bd9,0xbba83872,0xb4a5baa7,0x2e463c00,0xbbf60000,0x3a2f39a8,0xb91339a8,0xb4a5bbd9,0x3ba8b23e,0xbb0eb872,0x378bbaa7,
  0x378b3b64,0xbb0e361f,0x3ba8361f,0xb4a53b64,0xb913baa7,0x3a2fb872,0xbbf6b23e,0x2e46bbd9,0x378b3c00,0xbb0e0000,0xbba8b9a8,0x34a5b9a8,
  0xbbf6b872,0x2e46baa7,0x3a2fb23e,0x39133bd9,0x3913b61f,0x3a2f3b64,0x2e463b64,0xbbf6b61f,0x34a53bd9,0xbba8b23e,0xbb0ebaa7,0x378bb872,
  0x3a2f3c00,0xb9130000,0x3bf639a8,0x2e4639a8,0xb78b323e,0xbb0ebbd9,0x34a53aa7,0xbba8b872,0xbba8bb64,0x34a5b61f,0xbb0eb61f,0xb78bbb64,
  0x2e46b872,0x3bf63aa7,0xb913bbd9,0x3a2f323e,0x3ba83c00,0xb4a50000,0xbb0eb9a8,0xb78bb9a8,0x39133aa7,0xba2fb872,0xbbf6bbd9,0x2e46b23e,
  0x2e46361f,0xbbf6bb64,0xba2fbb64,0x3913361f,0xb78bb23e,0xbb0ebbd9,0xb4a5b872,0x3ba83aa7,0x3bea3bfe,0x30b22a48,0x38c4395f,0x3a6d39ed,
  0x3b883bc3,0x356433c6,0x36d7381d,0x3b3b3add,0x3add3b3b,0x381d36d7,0x33c63564,0x3bc33b88,0x39ed3a6d,0x395f38c4,0x2a4830b2,0x3bfe3bea,
  0x39ed3bc3,0x395f33c6,0xaa48b81d,0xbbfebadd,0xb0b23564,0x3bea3b88,0x3a6d36d7,0xb8c4bb3b,0xbb3bb8c4,0x36d73a6d,0x3b883bea,0x3564b0b2,
  0xbaddbbfe,0xb81daa48,0x33c6395f,0x3bc339ed,0x33c63b3b,0x3bc336d7,0xb81d3564,0x3add3b88,0xbbfeb8c4,0x2a483a6d,0xb9edbbea,0xb95f30b2,
  0x30b2b95f,0xbbeab9ed,0x3a6d2a48,0xb8c4bbfe,0x3b883add,0x3564b81d,0x36d73bc3,0x3b3b33c6,0xb5643a6d,0x3b8838c4,0x3b3bb0b2,0xb6d7bbea,
  0xb3c6bbfe,0xbbc3aa48,0xb81d395f,0x3add39ed,0x39ed3add,0x395fb81d,0xaa48bbc3,0xbbfeb3c6,0xbbeab6d7,0xb0b23b3b,0x38c43b88,0x3a6db564,
  0xba6d395f,0x38c439ed,0xbbeaaa48,0xb0b23bfe,0x3b3bb81d,0xb6d7badd,0x3b8833c6,0x3564bbc3,0xbbc33564,0x33c63b88,0xbaddb6d7,0xb81d3b3b,
  0x3bfeb0b2,0xaa48bbea,0x39ed38c4,0x395fba6d,0xbbfe381d,0x2a483add,0x39ed33c6,0x395fbbc3,0x38c436d7,0x3a6dbb3b,0x30b2bb88,0xbbea3564,
  0x3564bbea,0xbb8830b2,0xbb3b3a6d,0x36d738c4,0xbbc3395f,0x33c639ed,0x3add2a48,0x381dbbfe,0xbadd3564,0xb81d3b88,0xb3c6b6d7,0xbbc33b3b,
  0xb95f3bea,0x39edb0b2,0xbbfe3a6d,0x2a4838c4,0x38c42a48,0x3a6dbbfe,0xb0b239ed,0x3beab95f,0x3b3bbbc3,0xb6d7b3c6,0x3b88b81d,0x3564badd,
  0xb6d730b2,0xbb3b3bea,0xb56438c4,0x3b88ba6d,0xbadd395f,0xb81d39ed,0x33c62a48,0x3bc3bbfe,0xbbfe3bc3,0x2a4833c6,0x39edb81d,0x395fbadd,
  0xba6d3b88,0x38c4b564,0x3beabb3b,0x30b2b6d7,0x30b2aa48,0xbbea3bfe,0x3a6db9ed,0xb8c4395f,0x3564b3c6,0xbb883bc3,0x3b3bbadd,0xb6d7381d,
  0x381db6d7,0xbadd3b3b,0x3bc3bb88,0xb3c63564,0x395fb8c4,0xb9ed3a6d,0x3bfebbea,0xaa4830b2,0x395fb3c6,0xb9ed3bc3,0xbbfe3add,0x2a48b81d,
  0x3beabb88,0x30b23564,0xb8c43b3b,0xba6d36d7,0x36d7ba6d,0x3b3bb8c4,0x356430b2,0xbb883bea,0xb81d2a48,0x3addbbfe,0x3bc3b9ed,0xb3c6395f,
  0x3bc3b6d7,0xb3c63b3b,0x3addbb88,0x381d3564,0x2a48ba6d,0x3bfeb8c4,0xb95fb0b2,0x39edbbea,0xbbea39ed,0xb0b2b95f,0xb8c43bfe,0xba6d2a48,
  0x3564381d,0xbb883add,0x3b3bb3c6,0xb6d73bc3,0x3b88b8c4,0x35643a6d,0xb6d73bea,0xbb3bb0b2,0xbbc32a48,0x33c6bbfe,0x3addb9ed,0x381d395f,
  0x395f381d,0xb9ed3add,0xbbfe33c6,0x2a48bbc3,0xb0b2bb3b,0x3beab6d7,0x3a6d3564,0xb8c43b88,0x38c4b9ed,0x3a6d395f,0xb0b2bbfe,0x3beaaa48,
  0xb6d73add,0xbb3bb81d,0x35643bc3,0xbb8833c6,0x33c6bb88,0x3bc33564,0xb81dbb3b,0x3addb6d7,0xaa483bea,0xbbfeb0b2,0x395f3a6d,0xb9ed38c4,
  0x2a48badd,0x3bfe381d,0x395f3bc3,0xb9ed33c6,0x3a6d3b3b,0xb8c436d7,0xbbeab564,0xb0b2bb88,0xbb88b0b2,0xb564bbea,0x36d7b8c4,0x3b3b3a6d,
  0x33c6b9ed,0x3bc3395f,0x381d3bfe,0xbadd2a48,0xb81dbb88,0x3add3564,0xbbc3bb3b,0x33c6b6d7,0x39ed30b2,0x395f3bea,0x2a48b8c4,0x3bfe3a6d,
  0x3a6d3bfe,0xb8c42a48,0x3bea395f,0x30b239ed,0xb6d733c6,0xbb3bbbc3,0x35643add,0xbb88b81d,0xbb3bbbea,0x36d730b2,0x3b883a6d,0x356438c4,
  0xb81db9ed,0x3add395f,0x3bc33bfe,0xb3c62a48,0x2a48b3c6,0x3bfe3bc3,0x395f3add,0xb9edb81d,0x38c43564,0x3a6d3b88,0x30b236d7,0xbbeabb3b,
  0xbbeabbfe,0xb0b2aa48,0xb8c4b95f,0xba6db9ed,0xbb88bbc3,0xb564b3c6,0xb6d7b81d,0xbb3bbadd,0xbaddbb3b,0xb81db6d7,0xb3c6b564,0xbbc3bb88,
  0xb9edba6d,0xb95fb8c4,0xaa48b0b2,0xbbfebbea,0xb9edbbc3,0xb95fb3c6,0x2a48381d,0x3bfe3add,0x30b2b564,0xbbeabb88,0xba6db6d7,0x38c43b3b,
  0x3b3b38c4,0xb6d7ba6d,0xbb88bbea,0xb56430b2,0x3add3bfe,0x381d2a48,0xb3c6b95f,0xbbc3b9ed,0xb3c6bb3b,0xbbc3b6d7,0x381db564,0xbaddbb88,
  0x3bfe38c4,0xaa48ba6d,0x39ed3bea,0x395fb0b2,0xb0b2395f,0x3bea39ed,0xba6daa48,0x38c43bfe,0xbb88badd,0xb564381d,0xb6d7bbc3,0xbb3bb3c6,
  0x3564ba6d,0xbb88b8c4,0xbb3b30b2,0x36d73bea,0x33c63bfe,0x3bc32a48,0x381db95f,0xbaddb9ed,0xb9edbadd,0xb95f381d,0x2a483bc3,0x3bfe33c6,
  0x3bea36d7,0x30b2bb3b,0xb8c4bb88,0xba6d3564,0x3a6db95f,0xb8c4b9ed,0x3bea2a48,0x30b2bbfe,0xbb3b381d,0x36d73add,0xbb88b3c6,0xb5643bc3,
  0x3bc3b564,0xb3c6bb88,0x3add36d7,0x381dbb3b,0xbbfe30b2,0x2a483bea,0xb9edb8c4,0xb95f3a6d,0x3bfeb81d,0xaa48badd,0xb9edb3c6,0xb95f3bc3,
  0xb8c4b6d7,0xba6d3b3b,0xb0b23b88,0x3beab564,0xb5643bea,0x3b88b0b2,0x3b3bba6d,0xb6d7b8c4,0x3bc3b95f,0xb3c6b9ed,0xbaddaa48,0xb81d3bfe,
  0x3addb564,0x381dbb88,0x33c636d7,0x3bc3bb3b,0x395fbbea,0xb9ed30b2,0x3bfeba6d,0xaa48b8c4,0xb8c4aa48,0xba6d3bfe,0x30b2b9ed,0xbbea395f,
  0xbb3b3bc3,0x36d733c6,0xbb88381d,0xb5643add,0x36d7b0b2,0x3b3bbbea,0x3564b8c4,0xbb883a6d,0x3addb95f,0x381db9ed,0xb3c6aa48,0xbbc33bfe,
  0x3bfebbc3,0xaa48b3c6,0xb9ed381d,0xb95f3add,0x3a6dbb88,0xb8c43564,0xbbea3b3b,0xb0b236d7,0xb0b22a48,0x3beabbfe,0xba6d39ed,0x38c4b95f,
  0xb56433c6,0x3b88bbc3,0xbb3b3add,0x36d7b81d,0xb81d36d7,0x3addbb3b,0xbbc33b88,0x33c6b564,0xb95f38c4,0x39edba6d,0xbbfe3bea,0x2a48b0b2,
  0xb95f33c6,0x39edbbc3,0x3bfebadd,0xaa48381d,0xbbea3b88,0xb0b2b564,0x38c4bb3b,0x3a6db6d7,0xb6d73a6d,0xbb3b38c4,0xb564b0b2,0x3b88bbea,
  0x381daa48,0xbadd3bfe,0xbbc339ed,0x33c6b95f,0xbbc336d7,0x33c6bb3b,0xbadd3b88,0xb81db564,0xaa483a6d,0xbbfe38c4,0x395f30b2,0xb9ed3bea,
  0x3beab9ed,0x30b2395f,0x38c4bbfe,0x3a6daa48,0xb564b81d,0x3b88badd,0xbb3b33c6,0x36d7bbc3,0xbb8838c4,0xb564ba6d,0x36d7bbea,0x3b3b30b2,
  0x3bc3aa48,0xb3c63bfe,0xbadd39ed,0xb81db95f,0xb95fb81d,0x39edbadd,0x3bfeb3c6,0xaa483bc3,0x30b23b3b,0xbbea36d7,0xba6db564,0x38c4bb88,
  0xb8c439ed,0xba6db95f,0x30b23bfe,0xbbea2a48,0x36d7badd,0x3b3b381d,0xb564bbc3,0x3b88b3c6,0xb3c63b88,0xbbc3b564,0x381d3b3b,0xbadd36d7,
  0x2a48bbea,0x3bfe30b2,0xb95fba6d,0x39edb8c4,0xaa483add,0xbbfeb81d,0xb95fbbc3,0x39edb3c6,0xba6dbb3b,0x38c4b6d7,0x3bea3564,0x30b23b88,
  0x3b8830b2,0x35643bea,0xb6d738c4,0xbb3bba6d,0xb3c639ed,0xbbc3b95f,0xb81dbbfe,0x3addaa48,0x381d3b88,0xbaddb564,0x3bc33b3b,0xb3c636d7,
  0xb9edb0b2,0xb95fbbea,0xaa4838c4,0xbbfeba6d,0xba6dbbfe,0x38c4aa48,0xbbeab95f,0xb0b2b9ed,0x36d7b3c6,0x3b3b3bc3,0xb564badd,0x3b88381d,
  0x3b3b3bea,0xb6d7b0b2,0xbb88ba6d,0xb564b8c4,0x381d39ed,0xbaddb95f,0xbbc3bbfe,0x33c6aa48,0xaa4833c6,0xbbfebbc3,0xb95fbadd,0x39ed381d,
  0xb8c4b564,0xba6dbb88,0xb0b2b6d7,0x3bea3b3b,0x3c003c00,0x1a480000,0x3bff3bff,0x27112648,0x3c003c00,0x20b61e48,0x3bff3bff,0x285227da,
  0x3c003c00,0x23db2248,0x3bfe3bff,0x291b28b6,0x3c003c00,0x257f24b6,0x3bfe3bfe,0x29e3297f,0x3c003c00,0x23db0000,0x3bed3bf1,0x30672fd6,
  0x3bfe3bff,0x29e327da,0x3be33be8,0x316030e4,0x3bfa3bfc,0x2ce72bd9,0x3bd73bdd,0x325731db,0x3bf43bf7,0x2edc2de2,0x3bca3bd1,0x334c32d2,
  0x3bff3c00,0x27110000,0x3bc13bce,0x33df3303,0x3bf93bfd,0x2d4c2b11,0x3ba23bb2,0x34c9345d,0x3bed3bf4,0x30672f0e,0x3b7d3b91,0x359f3534,
  0x3bda3be4,0x32263147,0x3b533b69,0x36703608,0x3bfe3c00,0x291b0000,0x3b7d3b99,0x359f3505,0x3bf13bf9,0x2fa42d1a,0x3b3e3b5f,0x36cc3637,
  0x3bd73be6,0x32573115,0x3af33b1a,0x37ee375e,0x3bb13bc6,0x34693396,0x3a9c3ac9,0x3881383d,0x3bfd3c00,0x2aac0000,0x3b223b50,0x373d367c,
  0x3be73bf5,0x30fd2eaa,0x3ab83af0,0x385837f9,0x3bbb3bd4,0x342032a1,0x3a3b3a7c,0x390538b0,0x3b793b9d,0x35b634ed,0x39ad39f6,0x39a43956,
  0x3bfc3c00,0x2c1f0000,0x3ab13af6,0x386237e3,0x3bda3bef,0x3226301d,0x3a133a65,0x393538ce,0x3b973bbc,0x35113414,0x395b39ba,0x39f23996,
  0x3b333b69,0x36f93608,0x388c38f6,0x3a953a47,0x3bfa3c00,0x2ce70000,0x3a2b3a8a,0x3918389b,0x3bca3be8,0x334c30e4,0x395139c3,0x39fa398d,
  0x3b6b3ba0,0x35fd34d5,0x385838d8,0x3ab83a5e,0x3ae03b2b,0x3817371b,0x368737a1,0x3b4e3b08,0x3bf83c00,0x2db00000,0x39923a0f,0x39be393a,
  0x3bb73be0,0x343831aa,0x38773909,0x3aa33a37,0x3b393b80,0x36e33593,0x367037b7,0x3b533b02,0x3a7f3ae3,0x38ab3812,0x337d351d,0x3bc73b95,
  0x3bf63c00,0x2e780000,0x38e73984,0x3a5239cb,0x3ba23bd6,0x34c9326f,0x3710383d,0x3b2e3ac9,0x3aff3b5a,0x37c2364e,0x34083593,0x3bbe3b80,
  0x3a133a92,0x39353891,0x2aac30e4,0x3bfd3be8,0x3bf33c00,0x2f400000,0x382d38ec,0x3ad33a4f,0x3b8a3bcb,0x35583334,0x351136c1,0x3b973b41,
  0x3abf3b30,0x384d3705,0x2e1432a1,0x3bf73bd4,0x399b3a37,0x39b53909,0xb036a4b6,0x3bee3c00,0x3bf03c00,0x30040000,0x36cc3848,0x3b3e3ac2,
  0x3b703bc0,0x35e533f7,0x31f434ed,0x3bdc3b9d,0x3a783b02,0x38b537b7,0xac1f2bd9,0x3bfc3bfc,0x391839d4,0x3a2b397b,0xb4f9b20d,0x3b9b3bdb,
  0x3bed3c00,0x30670000,0x35293732,0x3b933b25,0x3b533bb2,0x3670345d,0x2aac320d,0x3bfd3bdb,0x3a2b3ad0,0x39183832,0xb31bad7e,0x3bcd3bf8,
  0x388c3969,0x3a9539e5,0xb7acb5ab,0x3b053b7b,0x3be93c00,0x30cb0000,0x32ea35c2,0x3bd03b77,0x3b333ba4,0x36f934bd,0xad4c2c51,0x3bf93bfb,
  0x39d83a99,0x39763887,0xb5fdb365,0x3b6b3bc9,0x37ee38f6,0x3af33a47,0xb90eb812,0x3a333ae3,0x3be53c00,0x312e0000,0x2edc3444,0x3bf43bb6,
  0x3b113b95,0x3780351d,0xb2eaab11,0x3bd03bfd,0x39803a5e,0x39d038d8,0xb822b5f1,0x3ad93b6e,0x36b5387c,0x3b433aa0,0xba1bb930,0x392b3a17,
  0x3be13c00,0x31910000,0x9a483179,0x3c003be2,0x3aed3b84,0x3802357c,0xb587b1aa,0x3b823be0,0x39223a1f,0x3a233927,0xb92bb807,0x3a1b3ae9,
  0x357037f9,0x3b863af0,0xbaf3ba27,0x37ee391d,0x3bdc3c00,0x31f40000,0xaf402cb5,0x3bf33bfa,0x3ac63b72,0x384235da,0xb780b4bd,0x3b113ba4,
  0x38bf39dc,0x3a713972,0xba13b900,0x39353a3f,0x342036ee,0x3bbb3b36,0xbb8fbaf0,0x354037f9,0x3bd73c00,0x32570000,0xb31ba648,0x3bcd3bff,
  0x3a9c3b5f,0x38813637,0xb8abb693,0x3a7f3b4b,0x38583996,0x3ab839ba,0xbad3b9dc,0x382d3972,0x319135da,0x3be13b72,0xbbe9bb84,0x30cb357c,
  0x3bd23c00,0x32b90000,0xb540afd6,0x3b8f3bf1,0x3a713b4b,0x38bf3693,0xb980b828,0x39d03ad6,0x37d8394d,0x3af939fe,0xbb67ba99,0x36143887,
  0x2db034bd,0x3bf83ba4,0xbbffbbe0,0xa85231aa,0x3bcd3c00,0x331b0000,0xb6e3b303,0x3b393bce,0x3a433b36,0x38fb36ee,0xba3bb8f6,0x39053a47,
  0x36f93900,0x3b333a3f,0xbbcabb30,0x334c3705,0x1a483334,0x3c003bcb,0xbbd0bc00,0xb2ea1e48,0x3bc73c00,0x337d0000,0xb838b505,0x3acc3b99,
  0x3a133b20,0x39353748,0xbad9b9b1,0x3822399f,0x361438b0,0x3b673a7c,0xbbfbbba0,0x2c8334d5,0xad4c30e4,0x3bf93be8,0xbb5dbbe4,0xb642b147,
  0x3bc13c00,0x33df0000,0xb8f1b67c,0x3a4b3b50,0x39e13b08,0x396d37a1,0xbb58ba56,0x365938e2,0x3529385d,0x3b933ab5,0xbbf8bbe6,0xadb03115,
  0xb1602d1a,0x3be33bf9,0xbaaabb8c,0xb86db54c,0x3bbb3c00,0x34200000,0xb99bb7e3,0x39b53af6,0x39ad3af0,0x39a437f9,0xbbb4bae3,0x34513812,
  0x34383807,0x3bb73ae9,0xbbc1bc00,0xb3df2248,0xb4081e48,0x3bbe3c00,0xb9bebafc,0xb992b7cd,0x3bb43c00,0x34510000,0xba33b89b,0x390e3a8a,
  0x39763ad6,0x39d83828,0xbbedbb55,0x30673665,0x3288375e,0x3bd53b1a,0xbb58bbed,0xb659b04e,0xb558ac51,0x3b8a3bfb,0xb8a0ba37,0xba87b909,
  0x3bad3c00,0x34810000,0xbab8b93a,0x38583a0f,0x393e3abc,0x3a0b3852,0xbc00bbab,0x1a48348d,0x309936aa,0x3beb3b46,0xbabfbbaf,0xb84db475,
  0xb69eb080,0x3b493bec,0xb6b5b943,0xbb43ba07,0x3ba63c00,0x34b10000,0xbb28b9cb,0x37263984,0x39053aa0,0x3a3b387c,0xbbeebbe4,0xb0363147,
  0x2d4c35f1,0x3bf93b6e,0xb9fabb46,0xb951b6aa,0xb7d8b2d2,0x3af93bd1,0xb3dfb828,0xbbc1bad6,0x3b9e3c00,0x34e10000,0xbb82ba4f,0x358738ec,
  0x38c93a83,0x3a6938a6,0xbbb7bbfe,0xb438297f,0x257f3534,0x3c003b91,0xb90ebab5,0xba33b85d,0xb881b48d,0x3a9c3bab,0xac1fb5da,0xbbfcbb72,
  0x3b973c00,0x35110000,0xbbc4bac2,0x33ae3848,0x388c3a65,0x3a9538ce,0xbb5dbbf9,0xb642ad1a,0xa91b3475,0x3bfe3baf,0xb802b9fe,0xbaedb94d,
  0xb90eb5ab,0x3a333b7b,0x2fa4b26f,0xbbf1bbd6,0x3b8f3c00,0x35400000,0xbbeebb25,0x30363732,0x384d3a47,0x3abf38f6,0xbae0bbd6,0xb817b26f,
  0xae783365,0x3bf63bc9,0xb5b6b927,0xbb79ba1f,0xb992b6c1,0x39be3b41,0x34c9a7da,0xbba2bbff,0x3b863c00,0x35700000,0xbc00bb77,0x257f35c2,
  0x380d3a27,0x3ae6391d,0xba43bb95,0xb8fbb51d,0xb12e31db,0x3be53bdd,0xb288b832,0xbbd5bad0,0xba0bb7cd,0x393e3afc,0x37803080,0xbb11bbec,
  0x3b7d3c00,0x359f0000,0xbbf8bbb6,0xadb03444,0x37963a07,0x3b0b3943,0xb989bb36,0xb9c7b6ee,0xb31b304e,0x3bcd3bed,0xa9e3b64e,0xbbfebb5a,
  0xba78b867,0x38b53aae,0x38fb34ed,0xba43bb9d,0x3b743c00,0x35ce0000,0xbbd7bbe2,0xb2573179,0x371039e5,0x3b2e3969,0xb8b5babc,0xba78b852,
  0xb4812d7e,0x3bad3bf8,0x2f40b414,0xbbf3bbbc,0xbad9b8e2,0x38223a56,0x3a0b3775,0xb93ebb14,0x3b6b3c00,0x35fd0000,0xbb9ebbfa,0xb4e12cb5,
  0x368739c3,0x3b4e398d,0xb796ba27,0xbb0bb91d,0xb57028b6,0x3b863bff,0x3451af0e,0xbbb4bbf4,0xbb2eb956,0x371039f6,0x3ae638e2,0xb80dba56,
  0x80003c00,0x80003c00,0x80003c00,0x80003c00,0x80003c00,0x80003c00,0x80003c00,0x80003c00,0x80003c00,0x80003c00,0x80003c00,0x80003c00,
  0x80003c00,0x80003c00,0x80003c00,0x80003c00,0xaa483bfe,0xb9ed395f,0xbbfeaa48,0xb95fb9ed,0xb3c63bc3,0xbadd381d,0xbbc3b3c6,0xb81dbadd,
  0xb6d73b3b,0xbb883564,0xbb3bb6d7,0xb564bb88,0xb8c43a6d,0xbbea30b2,0xba6db8c4,0xb0b2bbea,0xae463bf6,0xbbf6ae46,0x2e46bbf6,0x3bf62e46,
  0xb78b3b0e,0xbb0eb78b,0x378bbb0e,0x3b0e378b,0xba2f3913,0xb913ba2f,0x3a2fb913,0x39133a2f,0xbba834a5,0xb4a5bba8,0x3ba8b4a5,0x34a53ba8,
  0xb0b23bea,0xb8c4ba6d,0x3bea30b2,0xba6d38c4,0xb95f39ed,0xaa48bbfe,0x39ed395f,0xbbfe2a48,0xbbc333c6,0x381dbadd,0x33c63bc3,0xbaddb81d,
  0xbb88b564,0x3b3bb6d7,0xb5643b88,0xb6d7bb3b,0xb23e3bd9,0x323ebbd9,0xb23e3bd9,0x323ebbd9,0xbaa73872,0x3aa7b872,0xbaa73872,0x3aa7b872,
  0xbbd9b23e,0x3bd9323e,0xbbd9b23e,0x3bd9323e,0xb872baa7,0x38723aa7,0xb872baa7,0x38723aa7,0xb3c63bc3,0x3addb81d,0xbbc3b3c6,0x381d3add,
  0xbb883564,0x3b3b36d7,0xb564bb88,0xb6d73b3b,0xba6db8c4,0x30b23bea,0x38c4ba6d,0xbbea30b2,0x2a48bbfe,0xb9ed395f,0x3bfe2a48,0xb95fb9ed,
  0xb4a53ba8,0x3ba834a5,0x34a5bba8,0xbba8b4a5,0xbbf62e46,0x2e463bf6,0x3bf6ae46,0xae46bbf6,0xb78bbb0e,0xbb0e378b,0x378b3b0e,0x3b0eb78b,
  0x3913ba2f,0xba2fb913,0xb9133a2f,0x3a2f3913,0xb5643b88,0x36d73b3b,0x3b883564,0x3b3bb6d7,0xbbeab0b2,0xba6d38c4,0xb0b23bea,0x38c43a6d,
  0xaa48bbfe,0xb9edb95f,0xbbfe2a48,0xb95f39ed,0x3bc3b3c6,0x381dbadd,0xb3c6bbc3,0xbaddb81d,0xb61f3b64,0xb61f3b64,0xb61f3b64,0xb61f3b64,
  0xbb64b61f,0xbb64b61f,0xbb64b61f,0xbb64b61f,0x361fbb64,0x361fbb64,0x361fbb64,0x361fbb64,0x3b64361f,0x3b64361f,0x3b64361f,0x3b64361f,
  0xb6d73b3b,0xbb883564,0xbb3bb6d7,0xb564bb88,0xba6db8c4,0xb0b2bbea,0x38c4ba6d,0x3beab0b2,0x39edb95f,0x3bfe2a48,0x395f39ed,0xaa483bfe,
  0x381d3add,0xb3c63bc3,0xbadd381d,0xbbc3b3c6,0xb78b3b0e,0xbb0eb78b,0x378bbb0e,0x3b0e378b,0xb913ba2f,0x3a2fb913,0x39133a2f,0xba2f3913,
  0x3ba8b4a5,0x34a53ba8,0xbba834a5,0xb4a5bba8,0xae463bf6,0xbbf6ae46,0x2e46bbf6,0x3bf62e46,0xb81d3add,0xb3c6bbc3,0x3add381d,0xbbc333c6,
  0xb6d7bb3b,0x3b883564,0xbb3b36d7,0x3564bb88,0x3bea30b2,0xba6d38c4,0x30b2bbea,0x38c43a6d,0xb95f39ed,0xaa48bbfe,0x39ed395f,0xbbfe2a48,
  0xb8723aa7,0x3872baa7,0xb8723aa7,0x3872baa7,0xb23ebbd9,0x323e3bd9,0xb23ebbd9,0x323e3bd9,0x3aa73872,0xbaa7b872,0x3aa73872,0xbaa7b872,
  0xbbd9323e,0x3bd9b23e,0xbbd9323e,0x3bd9b23e,0xb8c43a6d,0x3beab0b2,0xba6db8c4,0x30b23bea,0x2a48bbfe,0xb9ed395f,0x3bfe2a48,0xb95fb9ed,
  0x381d3add,0x33c6bbc3,0xbadd381d,0x3bc333c6,0xbb3bb6d7,0x35643b88,0x36d7bb3b,0xbb883564,0xb9133a2f,0x3a2f3913,0x3913ba2f,0xba2fb913,
  0x34a5bba8,0xbba8b4a5,0xb4a53ba8,0x3ba834a5,0x2e463bf6,0x3bf6ae46,0xae46bbf6,0xbbf62e46,0xb78bbb0e,0xbb0e378b,0x378b3b0e,0x3b0eb78b,
  0xb95f39ed,0x2a483bfe,0x39ed395f,0x3bfeaa48,0x381dbadd,0xb3c6bbc3,0xbaddb81d,0xbbc333c6,0xb5643b88,0x36d73b3b,0x3b883564,0x3b3bb6d7,
  0x30b2bbea,0xb8c4ba6d,0xbbeab0b2,0xba6d38c4,0xb9a839a8,0xb9a839a8,0xb9a839a8,0xb9a839a8,0x39a8b9a8,0x39a8b9a8,0x39a8b9a8,0x39a8b9a8,
  0xb9a839a8,0xb9a839a8,0xb9a839a8,0xb9a839a8,0x39a8b9a8,0x39a8b9a8,0x39a8b9a8,0x39a8b9a8,0xb9ed395f,0xbbfeaa48,0xb95fb9ed,0x2a48bbfe,
  0x3addb81d,0x3bc333c6,0x381d3add,0xb3c63bc3,0xbb883564,0xbb3bb6d7,0xb564bb88,0x36d7bb3b,0x3beab0b2,0x3a6d38c4,0x30b23bea,0xb8c43a6d,
  0xba2f3913,0xb913ba2f,0x3a2fb913,0x39133a2f,0x3ba8b4a5,0x34a53ba8,0xbba834a5,0xb4a5bba8,0xbbf6ae46,0x2e46bbf6,0x3bf62e46,0xae463bf6,
  0x3b0e378b,0xb78b3b0e,0xbb0eb78b,0x378bbb0e,0xba6d38c4,0x30b2bbea,0x38c43a6d,0xbbeab0b2,0x3bfeaa48,0xb95f39ed,0xaa48bbfe,0x39ed395f,
  0xbaddb81d,0x3bc3b3c6,0xb81d3add,0xb3c6bbc3,0x36d73b3b,0xbb88b564,0x3b3bb6d7,0xb5643b88,0xbaa73872,0x3aa7b872,0xbaa73872,0x3aa7b872,
  0x3bd9323e,0xbbd9b23e,0x3bd9323e,0xbbd9b23e,0xb872baa7,0x38723aa7,0xb872baa7,0x38723aa7,0xb23e3bd9,0x323ebbd9,0xb23e3bd9,0x323ebbd9,
  0xbadd381d,0x3bc333c6,0xb81dbadd,0xb3c63bc3,0x3b3b36d7,0xb564bb88,0xb6d73b3b,0x3b88b564,0xb0b2bbea,0xb8c43a6d,0x3beab0b2,0xba6db8c4,
  0xb9ed395f,0x3bfe2a48,0xb95fb9ed,0xaa483bfe,0xbb0e378b,0x378b3b0e,0x3b0eb78b,0xb78bbb0e,0x3a2f3913,0x3913ba2f,0xba2fb913,0xb9133a2f,
  0x34a5bba8,0xbba8b4a5,0xb4a53ba8,0x3ba834a5,0xbbf62e46,0x2e463bf6,0x3bf6ae46,0xae46bbf6,0xbb3b36d7,0xb5643b88,0x36d73b3b,0x3b883564,
  0x38c43a6d,0x3bea30b2,0x3a6db8c4,0x30b2bbea,0x395fb9ed,0xaa48bbfe,0xb9edb95f,0xbbfe2a48,0xbaddb81d,0xbbc333c6,0xb81d3add,0x33c63bc3,
  0xbb64361f,0xbb64361f,0xbb64361f,0xbb64361f,0x361f3b64,0x361f3b64,0x361f3b64,0x361f3b64,0x3b64b61f,0x3b64b61f,0x3b64b61f,0x3b64b61f,
  0xb61fbb64,0xb61fbb64,0xb61fbb64,0xb61fbb64,0xbb883564,0xbb3bb6d7,0xb564bb88,0x36d7bb3b,0x30b23bea,0xb8c43a6d,0xbbea30b2,0xba6db8c4,
  0x3bfe2a48,0x395f39ed,0xaa483bfe,0xb9ed395f,0x33c6bbc3,0x3addb81d,0x3bc333c6,0x381d3add,0xbba834a5,0xb4a5bba8,0x3ba8b4a5,0x34a53ba8,
  0xae463bf6,0xbbf6ae46,0x2e46bbf6,0x3bf62e46,0x3b0e378b,0xb78b3b0e,0xbb0eb78b,0x378bbb0e,0x3a2fb913,0x39133a2f,0xba2f3913,0xb913ba2f,
  0xbbc333c6,0x381dbadd,0x33c63bc3,0xbaddb81d,0xb5643b88,0xb6d7bb3b,0x3b883564,0xbb3b36d7,0x38c43a6d,0xbbeab0b2,0x3a6db8c4,0xb0b23bea,
  0x3bfeaa48,0xb95f39ed,0xaa48bbfe,0x39ed395f,0xbbd9323e,0x3bd9b23e,0xbbd9323e,0x3bd9b23e,0xb8723aa7,0x3872baa7,0xb8723aa7,0x3872baa7,
  0x323e3bd9,0xb23ebbd9,0x323e3bd9,0xb23ebbd9,0x3aa73872,0xbaa7b872,0x3aa73872,0xbaa7b872,0xbbea30b2,0x3a6d38c4,0xb0b2bbea,0xb8c43a6d,
  0xb9ed395f,0x3bfe2a48,0xb95fb9ed,0xaa483bfe,0xb3c63bc3,0x3addb81d,0xbbc3b3c6,0x381d3add,0x35643b88,0x36d7bb3b,0xbb883564,0x3b3b36d7,
  0xbbf62e46,0x2e463bf6,0x3bf6ae46,0xae46bbf6,0xbb0e378b,0x378b3b0e,0x3b0eb78b,0xb78bbb0e,0xb9133a2f,0x3a2f3913,0x3913ba2f,0xba2fb913,
  0xb4a53ba8,0x3ba834a5,0x34a5bba8,0xbba8b4a5,0xbbfe2a48,0xb95f39ed,0x2a483bfe,0x39ed395f,0xbbc333c6,0xb81d3add,0x33c63bc3,0x3add381d,
  0xbb3b36d7,0xb5643b88,0x36d73b3b,0x3b883564,0xba6d38c4,0xb0b23bea,0x38c43a6d,0x3bea30b2,0x80003c00,0x80003c00,0x80003c00,0x80003c00,
  0x80003c00,0x80003c00,0x80003c00,0x80003c00,0x80003c00,0x80003c00,0x80003c00,0x80003c00,0x80003c00,0x80003c00,0x80003c00,0x80003c00,
  0x2a48bbfe,0x39edb95f,0x3bfe2a48,0x395f39ed,0x33c6bbc3,0x3addb81d,0x3bc333c6,0x381d3add,0x36d7bb3b,0x3b88b564,0x3b3b36d7,0x35643b88,
  0x38c4ba6d,0x3beab0b2,0x3a6d38c4,0x30b23bea,0xae463bf6,0xbbf6ae46,0x2e46bbf6,0x3bf62e46,0xb78b3b0e,0xbb0eb78b,0x378bbb0e,0x3b0e378b,
  0xba2f3913,0xb913ba2f,0x3a2fb913,0x39133a2f,0xbba834a5,0xb4a5bba8,0x3ba8b4a5,0x34a53ba8,0x30b2bbea,0x38c43a6d,0xbbeab0b2,0x3a6db8c4,
  0x395fb9ed,0x2a483bfe,0xb9edb95f,0x3bfeaa48,0x3bc3b3c6,0xb81d3add,0xb3c6bbc3,0x3add381d,0x3b883564,0xbb3b36d7,0x3564bb88,0x36d73b3b,
  0xb23e3bd9,0x323ebbd9,0xb23e3bd9,0x323ebbd9,0xbaa73872,0x3aa7b872,0xbaa73872,0x3aa7b872,0xbbd9b23e,0x3bd9323e,0xbbd9b23e,0x3bd9323e,
  0xb872baa7,0x38723aa7,0xb872baa7,0x38723aa7,0x33c6bbc3,0xbadd381d,0x3bc333c6,0xb81dbadd,0x3b88b564,0xbb3bb6d7,0x35643b88,0x36d7bb3b,
  0x3a6d38c4,0xb0b2bbea,0xb8c43a6d,0x3beab0b2,0xaa483bfe,0x39edb95f,0xbbfeaa48,0x395f39ed,0xb4a53ba8,0x3ba834a5,0x34a5bba8,0xbba8b4a5,
  0xbbf62e46,0x2e463bf6,0x3bf6ae46,0xae46bbf6,0xb78bbb0e,0xbb0e378b,0x378b3b0e,0x3b0eb78b,0x3913ba2f,0xba2fb913,0xb9133a2f,0x3a2f3913,
  0x3564bb88,0xb6d7bb3b,0xbb88b564,0xbb3b36d7,0x3bea30b2,0x3a6db8c4,0x30b2bbea,0xb8c4ba6d,0x2a483bfe,0x39ed395f,0x3bfeaa48,0x395fb9ed,
  0xbbc333c6,0xb81d3add,0x33c63bc3,0x3add381d,0xb61f3b64,0xb61f3b64,0xb61f3b64,0xb61f3b64,0xbb64b61f,0xbb64b61f,0xbb64b61f,0xbb64b61f,
  0x361fbb64,0x361fbb64,0x361fbb64,0x361fbb64,0x3b64361f,0x3b64361f,0x3b64361f,0x3b64361f,0x36d7bb3b,0x3b88b564,0x3b3b36d7,0x35643b88,
  0x3a6d38c4,0x30b23bea,0xb8c43a6d,0xbbea30b2,0xb9ed395f,0xbbfeaa48,0xb95fb9ed,0x2a48bbfe,0xb81dbadd,0x33c6bbc3,0x3addb81d,0x3bc333c6,
  0xb78b3b0e,0xbb0eb78b,0x378bbb0e,0x3b0e378b,0xb913ba2f,0x3a2fb913,0x39133a2f,0xba2f3913,0x3ba8b4a5,0x34a53ba8,0xbba834a5,0xb4a5bba8,
  0xae463bf6,0xbbf6ae46,0x2e46bbf6,0x3bf62e46,0x381dbadd,0x33c63bc3,0xbaddb81d,0x3bc3b3c6,0x36d73b3b,0xbb88b564,0x3b3bb6d7,0xb5643b88,
  0xbbeab0b2,0x3a6db8c4,0xb0b23bea,0xb8c4ba6d,0x395fb9ed,0x2a483bfe,0xb9edb95f,0x3bfeaa48,0xb8723aa7,0x3872baa7,0xb8723aa7,0x3872baa7,
  0xb23ebbd9,0x323e3bd9,0xb23ebbd9,0x323e3bd9,0x3aa73872,0xbaa7b872,0x3aa73872,0xbaa7b872,0xbbd9323e,0x3bd9b23e,0xbbd9323e,0x3bd9b23e,
  0x38c4ba6d,0xbbea30b2,0x3a6d38c4,0xb0b2bbea,0xaa483bfe,0x39edb95f,0xbbfeaa48,0x395f39ed,0xb81dbadd,0xb3c63bc3,0x3addb81d,0xbbc3b3c6,
  0x3b3b36d7,0xb564bb88,0xb6d73b3b,0x3b88b564,0xb9133a2f,0x3a2f3913,0x3913ba2f,0xba2fb913,0x34a5bba8,0xbba8b4a5,0xb4a53ba8,0x3ba834a5,
  0x2e463bf6,0x3bf6ae46,0xae46bbf6,0xbbf62e46,0xb78bbb0e,0xbb0e378b,0x378b3b0e,0x3b0eb78b,0x395fb9ed,0xaa48bbfe,0xb9edb95f,0xbbfe2a48,
  0xb81d3add,0x33c63bc3,0x3add381d,0x3bc3b3c6,0x3564bb88,0xb6d7bb3b,0xbb88b564,0xbb3b36d7,0xb0b23bea,0x38c43a6d,0x3bea30b2,0x3a6db8c4,
  0xb9a839a8,0xb9a839a8,0xb9a839a8,0xb9a839a8,0x39a8b9a8,0x39a8b9a8,0x39a8b9a8,0x39a8b9a8,0xb9a839a8,0xb9a839a8,0xb9a839a8,0xb9a839a8,
  0x39a8b9a8,0x39a8b9a8,0x39a8b9a8,0x39a8b9a8,0x39edb95f,0x3bfe2a48,0x395f39ed,0xaa483bfe,0xbadd381d,0xbbc3b3c6,0xb81dbadd,0x33c6bbc3,
  0x3b88b564,0x3b3b36d7,0x35643b88,0xb6d73b3b,0xbbea30b2,0xba6db8c4,0xb0b2bbea,0x38c4ba6d,0xba2f3913,0xb913ba2f,0x3a2fb913,0x39133a2f,
  0x3ba8b4a5,0x34a53ba8,0xbba834a5,0xb4a5bba8,0xbbf6ae46,0x2e46bbf6,0x3bf62e46,0xae463bf6,0x3b0e378b,0xb78b3b0e,0xbb0eb78b,0x378bbb0e,
  0x3a6db8c4,0xb0b23bea,0xb8c4ba6d,0x3bea30b2,0xbbfe2a48,0x395fb9ed,0x2a483bfe,0xb9edb95f,0x3add381d,0xbbc333c6,0x381dbadd,0x33c63bc3,
  0xb6d7bb3b,0x3b883564,0xbb3b36d7,0x3564bb88,0xbaa73872,0x3aa7b872,0xbaa73872,0x3aa7b872,0x3bd9323e,0xbbd9b23e,0x3bd9323e,0xbbd9b23e,
  0xb872baa7,0x38723aa7,0xb872baa7,0x38723aa7,0xb23e3bd9,0x323ebbd9,0xb23e3bd9,0x323ebbd9,0x3addb81d,0xbbc3b3c6,0x381d3add,0x33c6bbc3,
  0xbb3bb6d7,0x35643b88,0x36d7bb3b,0xbb883564,0x30b23bea,0x38c4ba6d,0xbbea30b2,0x3a6d38c4,0x39edb95f,0xbbfeaa48,0x395f39ed,0x2a48bbfe,
  0xbb0e378b,0x378b3b0e,0x3b0eb78b,0xb78bbb0e,0x3a2f3913,0x3913ba2f,0xba2fb913,0xb9133a2f,0x34a5bba8,0xbba8b4a5,0xb4a53ba8,0x3ba834a5,
  0xbbf62e46,0x2e463bf6,0x3bf6ae46,0xae46bbf6,0x3b3bb6d7,0x3564bb88,0xb6d7bb3b,0xbb88b564,0xb8c4ba6d,0xbbeab0b2,0xba6d38c4,0xb0b23bea,
  0xb95f39ed,0x2a483bfe,0x39ed395f,0x3bfeaa48,0x3add381d,0x3bc3b3c6,0x381dbadd,0xb3c6bbc3,0xbb64361f,0xbb64361f,0xbb64361f,0xbb64361f,
  0x361f3b64,0x361f3b64,0x361f3b64,0x361f3b64,0x3b64b61f,0x3b64b61f,0x3b64b61f,0x3b64b61f,0xb61fbb64,0xb61fbb64,0xb61fbb64,0xb61fbb64,
  0x3b88b564,0x3b3b36d7,0x35643b88,0xb6d73b3b,0xb0b2bbea,0x38c4ba6d,0x3beab0b2,0x3a6d38c4,0xbbfeaa48,0xb95fb9ed,0x2a48bbfe,0x39edb95f,
  0xb3c63bc3,0xbadd381d,0xbbc3b3c6,0xb81dbadd,0xbba834a5,0xb4a5bba8,0x3ba8b4a5,0x34a53ba8,0xae463bf6,0xbbf6ae46,0x2e46bbf6,0x3bf62e46,
  0x3b0e378b,0xb78b3b0e,0xbb0eb78b,0x378bbb0e,0x3a2fb913,0x39133a2f,0xba2f3913,0xb913ba2f,0x3bc3b3c6,0xb81d3add,0xb3c6bbc3,0x3add381d,
  0x3564bb88,0x36d73b3b,0xbb88b564,0x3b3bb6d7,0xb8c4ba6d,0x3bea30b2,0xba6d38c4,0x30b2bbea,0xbbfe2a48,0x395fb9ed,0x2a483bfe,0xb9edb95f,
  0xbbd9323e,0x3bd9b23e,0xbbd9323e,0x3bd9b23e,0xb8723aa7,0x3872baa7,0xb8723aa7,0x3872baa7,0x323e3bd9,0xb23ebbd9,0x323e3bd9,0xb23ebbd9,
  0x3aa73872,0xbaa7b872,0x3aa73872,0xbaa7b872,0x3beab0b2,0xba6db8c4,0x30b23bea,0x38c4ba6d,0x39edb95f,0xbbfeaa48,0x395f39ed,0x2a48bbfe,
  0x33c6bbc3,0xbadd381d,0x3bc333c6,0xb81dbadd,0xb564bb88,0xb6d73b3b,0x3b88b564,0xbb3bb6d7,0xbbf62e46,0x2e463bf6,0x3bf6ae46,0xae46bbf6,
  0xbb0e378b,0x378b3b0e,0x3b0eb78b,0xb78bbb0e,0xb9133a2f,0x3a2f3913,0x3913ba2f,0xba2fb913,0xb4a53ba8,0x3ba834a5,0x34a5bba8,0xbba8b4a5,
  0x3bfeaa48,0x395fb9ed,0xaa48bbfe,0xb9edb95f,0x3bc3b3c6,0x381dbadd,0xb3c6bbc3,0xbaddb81d,0x3b3bb6d7,0x3564bb88,0xb6d7bb3b,0xbb88b564,
  0x3a6db8c4,0x30b2bbea,0xb8c4ba6d,0xbbeab0b2,0x00000000,0x00000000,0x00000000,0x00000000,0xaa1f0000,0xaf64ada8,0xaf64b000,0xaa1fada8,
  0xada80000,0xada8b000,0x2da88000,0x2da83000,0xaf640000,0x2a1fada8,0x2a1f3000,0xaf64ada8,0xb0000000,0x30008000,0xb0000000,0x30008000,
  0xaf640000,0x2a1f2da8,0x2a1fb000,0xaf642da8,0xada80000,0xada83000,0x2da88000,0x2da8b000,0xaa1f0000,0xaf642da8,0xaf643000,0xaa1f2da8,
  0x00000000,0x00000000,0x00000000,0x00000000,0x2a1f8000,0x2f642da8,0x2f643000,0x2a1f2da8,0xada80000,0xada8b000,0x2da88000,0x2da83000,
  0x2f648000,0xaa1f2da8,0xaa1fb000,0x2f642da8,0xb0000000,0x30008000,0xb0000000,0x30008000,0x2f648000,0xaa1fada8,0xaa1f3000,0x2f64ada8,
  0xada80000,0xada83000,0x2da88000,0x2da8b000,0x2a1f8000,0x2f64ada8,0x2f64b000,0x2a1fada8,0x80000000,0x80000000,0x80000000,0x80000000,
  0x2a1f0000,0x2f64ada8,0x2f64b000,0x2a1fada8,0x2da80000,0x2da8b000,0xada88000,0xada83000,0x2f640000,0xaa1fada8,0xaa1f3000,0x2f64ada8,
  0x30000000,0xb0008000,0x30000000,0xb0008000,0x2f640000,0xaa1f2da8,0xaa1fb000,0x2f642da8,0x2da80000,0x2da83000,0xada88000,0xada8b000,
  0x2a1f0000,0x2f642da8,0x2f643000,0x2a1f2da8,0x80000000,0x80000000,0x80000000,0x80000000,0xaa1f8000,0xaf642da8,0xaf643000,0xaa1f2da8,
  0x2da80000,0x2da8b000,0xada88000,0xada83000,0xaf648000,0x2a1f2da8,0x2a1fb000,0xaf642da8,0x30000000,0xb0008000,0x30000000,0xb0008000,
  0xaf648000,0x2a1fada8,0x2a1f3000,0xaf64ada8,0x2da80000,0x2da83000,0xada88000,0xada8b000,0xaa1f8000,0xaf64ada8,0xaf64b000,0xaa1fada8,
  0x30003000,0x30003000,0x30003000,0x30003000,0x2f643000,0x2a1f2da8,0xaa1f0000,0xaf64ada8,0x2da83000,0xada80000,0xada8b000,0x2da88000,
  0x2a1f3000,0xaf64ada8,0x2f648000,0xaa1f2da8,0x00003000,0x8000b000,0x00003000,0x8000b000,0xaa1f3000,0x2f64ada8,0xaf640000,0x2a1f2da8,
  0xada83000,0x2da88000,0x2da8b000,0xada80000,0xaf643000,0xaa1f2da8,0x2a1f8000,0x2f64ada8,0x30003000,0x30003000,0x30003000,0x30003000,
  0xaf64b000,0xaa1fada8,0x2a1f8000,0x2f642da8,0x2da83000,0xada80000,0xada8b000,0x2da88000,0xaa1fb000,0x2f642da8,0xaf640000,0x2a1fada8,
  0x00003000,0x8000b000,0x00003000,0x8000b000,0x2a1fb000,0xaf642da8,0x2f648000,0xaa1fada8,0xada83000,0x2da88000,0x2da8b000,0xada80000,
  0x2f64b000,0x2a1fada8,0xaa1f0000,0xaf642da8,0xb0003000,0xb0003000,0xb0003000,0xb0003000,0xaf643000,0xaa1f2da8,0x2a1f0000,0x2f64ada8,
  0xada83000,0x2da80000,0x2da8b000,0xada88000,0xaa1f3000,0x2f64ada8,0xaf648000,0x2a1f2da8,0x80003000,0x0000b000,0x80003000,0x0000b000,
  0x2a1f3000,0xaf64ada8,0x2f640000,0xaa1f2da8,0x2da83000,0xada88000,0xada8b000,0x2da80000,0x2f643000,0x2a1f2da8,0xaa1f8000,0xaf64ada8,
  0xb0003000,0xb0003000,0xb0003000,0xb0003000,0x2f64b000,0x2a1fada8,0xaa1f8000,0xaf642da8,0xada83000,0x2da80000,0x2da8b000,0xada88000,
  0x2a1fb000,0xaf642da8,0x2f640000,0xaa1fada8,0x80003000,0x0000b000,0x80003000,0x0000b000,0xaa1fb000,0x2f642da8,0xaf648000,0x2a1fada8,
  0x2da83000,0xada88000,0xada8b000,0x2da80000,0xaf64b000,0xaa1fada8,0x2a1f0000,0x2f642da8,0x80008000,0x80008000,0x80008000,0x80008000,
  0x2a1f8000,0x2f642da8,0x2f643000,0x2a1f2da8,0x2da88000,0x2da83000,0xada80000,0xada8b000,0x2f648000,0xaa1f2da8,0xaa1fb000,0x2f642da8,
  0x30008000,0xb0000000,0x30008000,0xb0000000,0x2f648000,0xaa1fada8,0xaa1f3000,0x2f64ada8,0x2da88000,0x2da8b000,0xada80000,0xada83000,
  0x2a1f8000,0x2f64ada8,0x2f64b000,0x2a1fada8,0x80008000,0x80008000,0x80008000,0x80008000,0xaa1f0000,0xaf64ada8,0xaf64b000,0xaa1fada8,
  0x2da88000,0x2da83000,0xada80000,0xada8b000,0xaf640000,0x2a1fada8,0x2a1f3000,0xaf64ada8,0x30008000,0xb0000000,0x30008000,0xb0000000,
  0xaf640000,0x2a1f2da8,0x2a1fb000,0xaf642da8,0x2da88000,0x2da8b000,0xada80000,0xada83000,0xaa1f0000,0xaf642da8,0xaf643000,0xaa1f2da8,
  0x00008000,0x00008000,0x00008000,0x00008000,0xaa1f8000,0xaf642da8,0xaf643000,0xaa1f2da8,0xada88000,0xada83000,0x2da80000,0x2da8b000,
  0xaf648000,0x2a1f2da8,0x2a1fb000,0xaf642da8,0xb0008000,0x30000000,0xb0008000,0x30000000,0xaf648000,0x2a1fada8,0x2a1f3000,0xaf64ada8,
  0xada88000,0xada8b000,0x2da80000,0x2da83000,0xaa1f8000,0xaf64ada8,0xaf64b000,0xaa1fada8,0x00008000,0x00008000,0x00008000,0x00008000,
  0x2a1f0000,0x2f64ada8,0x2f64b000,0x2a1fada8,0xada88000,0xada83000,0x2da80000,0x2da8b000,0x2f640000,0xaa1fada8,0xaa1f3000,0x2f64ada8,
  0xb0008000,0x30000000,0xb0008000,0x30000000,0x2f640000,0xaa1f2da8,0xaa1fb000,0x2f642da8,0xada88000,0xada8b000,0x2da80000,0x2da83000,
  0x2a1f0000,0x2f642da8,0x2f643000,0x2a1f2da8,
};

template <int V> struct IntC { static constexpr int value = V; };
constexpr int kThreads = 384;
constexpr int kCtas = 128;

#define CREGS 232
#define AREGS 40
#define EARLY 2
#define PREP0 1200
#define PREPGAP 600
#define PF0 12000
#define PFGAP 400
#define CSEQ 0
#define OSEQ 1
#define H0 17
#define HS 1
#define HCV 28
#define UCV 24
#define PROMK 0
#define PROMX 0
#define XPF 0
#define MAPV 1
#define PREW 1
#define UPRE 0
#define XEARLY 0
#define RPF 0
#define RPF0 2
#define RPFM 3
#define UNUM 7
#define UDEN 3
#define U0 4
#define ULAT 3
#define WQPF 28
#define KVPF 0
#define EXP 0
#define PREPCP 1
#define QGAP 100
#define POSTTMA 1
#define POSTGAP 400

constexpr int NS1 = 6;
__host__ __device__ constexpr int slot1(int it) { return (it + 4) % NS1; }
__host__ __device__ constexpr uint32_t w1_off(int s) { return (1 + s + (s >> 1)) * 16384; }
__host__ __device__ constexpr uint32_t x1_off(int it) { return ((it >> 1) & 3) * 49152; }
constexpr uint32_t ST2 = 32768;
constexpr uint32_t R_KV = 2 * ST2;
constexpr uint32_t RA = 131072;
constexpr uint32_t RB = 163840;
constexpr uint32_t RU = 196608;
constexpr uint32_t Y_OWN = 16384, Y_IN = 24576;
constexpr uint32_t SM_ONES = 229376;
constexpr uint32_t SM_F2 = SM_ONES + 128;
constexpr uint32_t SM_BAR = 231424;
constexpr uint32_t SM_SCALE = SM_BAR + 496;
constexpr uint32_t SM_MAX = SM_BAR + 512;
constexpr uint32_t SM_TOTAL = 232448;
constexpr uint32_t SM_BASE = 1024;
constexpr uint32_t KV_HEAD = 2560;

enum Bar { B_F1 = 0, B_E1 = 6, B_F2 = 12, B_E2 = 16, B_F2M = 20, B_MAX = 21, B_VST = 22, B_ZERO = 23, B_U = 24, B_KVP = 25, B_KV = 26, B_OW = 27,
           B_OFREE = 29, B_S1 = 31, B_Y = 32, B_KVI = 33, B_I2 = 34, B_ZST = 36, B_KVL = 37, B_Q = 45, B_RDY = 46, B_COUNT = 60 };

struct Params {
  CUtensorMap w1, x, k, v, w2, wo, o, outa, q, outb;
  const __nv_bfloat16* shift_k;
  const __nv_bfloat16* ssm_k;
  const __nv_bfloat16* ssm_d;
  const __nv_bfloat16* q_ptr;
  const __nv_bfloat16* x_ptr;
  const __nv_bfloat16* k_ptr;
  const __nv_bfloat16* v_ptr;
  const __nv_bfloat16* w_ptr;
  const __nv_bfloat16* wo_ptr;
  uint8_t* out;
};

constexpr int KV_WORDS = 4096 + 128;
__device__ __align__(128) float g_kv[8][KV_WORDS];
__device__ unsigned g_kvflag[8 * 32], g_zflag[8 * 32];
__device__ __align__(128) unsigned g_oflag[16 * 32];
__device__ unsigned g_epoch[kCtas];
__device__ __align__(128) __nv_bfloat16 g_o[2048 * 1024];

#define TSTAMP(cond, i) do { } while (0)
#define GSTAMP(cond, i) do { } while (0)
#define KSTAMP(n) do { } while (0)
#define QSTAMP(n) do { } while (0)

constexpr int kSpinLimit = 1 << 17;

DEVI void mbar_init(uint32_t a, uint32_t c) { asm volatile("mbarrier.init.shared::cta.b64 [%0], %1;" :: "r"(a), "r"(c) : "memory"); }
DEVI void mbar_expect(uint32_t a, uint32_t b) { asm volatile("mbarrier.arrive.expect_tx.shared::cta.b64 _, [%0], %1;" :: "r"(a), "r"(b) : "memory"); }
DEVI void mbar_arrive(uint32_t a) { asm volatile("mbarrier.arrive.shared::cta.b64 _, [%0];" :: "r"(a) : "memory"); }
DEVI void mbar_arrive_if(uint32_t a, bool pred) {
  asm volatile("{\n.reg .pred p;\nsetp.ne.b32 p, %1, 0;\n@p mbarrier.arrive.shared::cta.b64 _, [%0];\n}" :: "r"(a), "r"((int)pred) : "memory");
}
DEVI void mbar_wait(uint32_t a, uint32_t parity) {
  asm volatile("{\n.reg .pred p;\n.reg .u32 n;\nmov.u32 n, 0;\nW_LOOP:\n"
               "mbarrier.try_wait.parity.shared::cta.b64 p, [%0], %1;\n@p bra W_DONE;\n"
               "add.u32 n, n, 1;\nsetp.lt.u32 p, n, %2;\n@p bra W_LOOP;\nW_DONE:\n}"
               :: "r"(a), "r"(parity), "n"(kSpinLimit) : "memory");
}
DEVI void mbar_wait_cl(uint32_t a, uint32_t parity) {
  asm volatile("{\n.reg .pred p;\n.reg .u32 n;\nmov.u32 n, 0;\nW_LOOP:\n"
               "mbarrier.try_wait.parity.acquire.cluster.shared::cta.b64 p, [%0], %1;\n@p bra W_DONE;\n"
               "add.u32 n, n, 1;\nsetp.lt.u32 p, n, %2;\n@p bra W_LOOP;\nW_DONE:\n}"
               :: "r"(a), "r"(parity), "n"(kSpinLimit) : "memory");
}
DEVI void mbar_wait_long(uint32_t a, uint32_t parity) {
  asm volatile("{\n.reg .pred p;\n.reg .u32 n;\nmov.u32 n, 0;\nW_LOOP:\n"
               "mbarrier.try_wait.parity.shared::cta.b64 p, [%0], %1, %3;\n@p bra W_DONE;\n"
               "add.u32 n, n, 1;\nsetp.lt.u32 p, n, %2;\n@p bra W_LOOP;\nW_DONE:\n}"
               :: "r"(a), "r"(parity), "n"(kSpinLimit), "r"(4000) : "memory");
}
DEVI void flag_wait(const unsigned* p, unsigned target) {
  int n = 0; unsigned v;
  do {
    asm volatile("ld.acquire.gpu.global.u32 %0, [%1];" : "=r"(v) : "l"(p) : "memory");
  } while ((int)(v - target) < 0 && ++n < kSpinLimit);
}
DEVI unsigned ld_relaxed(const unsigned* p) { unsigned v; asm volatile("ld.relaxed.gpu.global.u32 %0, [%1];" : "=r"(v) : "l"(p) : "memory"); return v; }
DEVI uint32_t clock32() { uint32_t t; asm volatile("mov.u32 %0, %%clock;" : "=r"(t)); return t; }
DEVI void pace(uint32_t t0, uint32_t n) { while (clock32() - t0 < n) __nanosleep(20); }
DEVI bool elect() { uint32_t p; asm volatile("{\n.reg .pred p;\nelect.sync _|p, 0xffffffff;\nselp.u32 %0, 1, 0, p;\n}" : "=r"(p)); return p; }
DEVI void fence_async_smem() { asm volatile("fence.proxy.async.shared::cta;" ::: "memory"); }
DEVI void bar_sync(int id, int n) { asm volatile("bar.sync %0, %1;" :: "r"(id), "r"(n) : "memory"); }
DEVI void cluster_sync() { asm volatile("barrier.cluster.arrive.relaxed.aligned;\nbarrier.cluster.wait.aligned;" ::: "memory"); }
DEVI void wg_fence() { asm volatile("wgmma.fence.sync.aligned;" ::: "memory"); }
DEVI void wg_commit() { asm volatile("wgmma.commit_group.sync.aligned;" ::: "memory"); }
template <int N> DEVI void wg_wait() { asm volatile("wgmma.wait_group.sync.aligned %0;" :: "n"(N) : "memory"); }
template <int N> DEVI void pin(uint32_t* r) {
#pragma unroll
  for (int i = 0; i < N; i++) asm volatile("" : "+r"(r[i]));
}
template <int N> DEVI void pin(float* r) {
#pragma unroll
  for (int i = 0; i < N; i++) asm volatile("" : "+f"(r[i]));
}

DEVI void tma2d(uint32_t dst, const CUtensorMap* m, int c0, int c1, uint32_t bar) {
  asm volatile("cp.async.bulk.tensor.2d.shared::cluster.global.mbarrier::complete_tx::bytes [%0], [%1, {%3, %4}], [%2];"
               :: "r"(dst), "l"(m), "r"(bar), "r"(c0), "r"(c1) : "memory");
}
DEVI void tma2d_mc(uint32_t dst, const CUtensorMap* m, int c0, int c1, uint32_t bar) {
  asm volatile("cp.async.bulk.tensor.2d.shared::cluster.global.mbarrier::complete_tx::bytes.multicast::cluster [%0], [%1, {%3, %4}], [%2], %5;"
               :: "r"(dst), "l"(m), "r"(bar), "r"(c0), "r"(c1), "h"((uint16_t)3) : "memory");
}
DEVI void tma3d(uint32_t dst, const CUtensorMap* m, int c0, int c1, int c2, uint32_t bar) {
  asm volatile("cp.async.bulk.tensor.3d.shared::cluster.global.mbarrier::complete_tx::bytes [%0], [%1, {%3, %4, %5}], [%2];"
               :: "r"(dst), "l"(m), "r"(bar), "r"(c0), "r"(c1), "r"(c2) : "memory");
}
DEVI void tma4d(uint32_t dst, const CUtensorMap* m, int c1, int c2, int c3, uint32_t bar) {
  asm volatile("cp.async.bulk.tensor.4d.shared::cluster.global.mbarrier::complete_tx::bytes [%0], [%1, {%3, %4, %5, %6}], [%2];"
               :: "r"(dst), "l"(m), "r"(bar), "r"(0), "r"(c1), "r"(c2), "r"(c3) : "memory");
}
DEVI void tma5d(uint32_t dst, const CUtensorMap* m, int c0, int c1, int c3, int c4, uint32_t bar) {
  asm volatile("cp.async.bulk.tensor.5d.shared::cluster.global.mbarrier::complete_tx::bytes [%0], [%1, {%3, %4, %5, %6, %7}], [%2];"
               :: "r"(dst), "l"(m), "r"(bar), "r"(c0), "r"(c1), "r"(0), "r"(c3), "r"(c4) : "memory");
}
DEVI void tma2d_store(const CUtensorMap* m, uint32_t src, int c0, int c1) {
  asm volatile("cp.async.bulk.tensor.2d.global.shared::cta.bulk_group [%0, {%2, %3}], [%1];" :: "l"(m), "r"(src), "r"(c0), "r"(c1) : "memory");
}
DEVI void tma2d_store_if(const CUtensorMap* m, uint32_t src, int c0, int c1, bool pred) {
  asm volatile("{\n.reg .pred p, e;\nelect.sync _|e, 0xffffffff;\nsetp.ne.and.b32 p, %4, 0, e;\n@p cp.async.bulk.tensor.2d.global.shared::cta.bulk_group [%0, {%2, %3}], [%1];\n"
               "@p cp.async.bulk.commit_group;\n}" :: "l"(m), "r"(src), "r"(c0), "r"(c1), "r"((int)pred) : "memory");
}
DEVI void tma5d_store(const CUtensorMap* m, uint32_t src, int c0, int c1, int c3, int c4) {
  asm volatile("cp.async.bulk.tensor.5d.global.shared::cta.bulk_group [%0, {%2, %3, %4, %5, %6}], [%1];\ncp.async.bulk.commit_group;"
               :: "l"(m), "r"(src), "r"(c0), "r"(c1), "r"(0), "r"(c3), "r"(c4) : "memory");
}
DEVI uint32_t mapa(uint32_t a, int rank) { uint32_t r; asm("mapa.shared::cluster.u32 %0, %1, %2;" : "=r"(r) : "r"(a), "r"(rank)); return r; }
DEVI void bulk_to_peer(uint32_t dst, uint32_t src, uint32_t bytes, uint32_t bar) {
  asm volatile("cp.async.bulk.shared::cluster.shared::cta.mbarrier::complete_tx::bytes [%0], [%1], %2, [%3];" :: "r"(dst), "r"(src), "r"(bytes), "r"(bar) : "memory");
}
DEVI void st_async4(uint32_t dst, uint32_t a, uint32_t b, uint32_t c, uint32_t d, uint32_t bar) {
  asm volatile("st.async.weak.shared::cluster.mbarrier::complete_tx::bytes.v4.b32 [%0], {%1,%2,%3,%4}, [%5];"
               :: "r"(dst), "r"(a), "r"(b), "r"(c), "r"(d), "r"(bar) : "memory");
}
DEVI void st_either4(bool local, uint32_t dst, uint32_t a, uint32_t b, uint32_t c, uint32_t d, uint32_t bar) {
  asm volatile("{\n.reg .pred p;\nsetp.ne.b32 p, %6, 0;\n@p st.shared.v4.b32 [%0], {%1,%2,%3,%4};\n"
               "@!p st.async.weak.shared::cluster.mbarrier::complete_tx::bytes.v4.b32 [%0], {%1,%2,%3,%4}, [%5];\n}"
               :: "r"(dst), "r"(a), "r"(b), "r"(c), "r"(d), "r"(bar), "r"((int)local) : "memory");
}
DEVI void st_async1_if(uint32_t dst, uint32_t a, uint32_t bar, bool pred) {
  asm volatile("{\n.reg .pred p;\nsetp.ne.b32 p, %3, 0;\n@p st.async.weak.shared::cluster.mbarrier::complete_tx::bytes.b32 [%0], %1, [%2];\n}"
               :: "r"(dst), "r"(a), "r"(bar), "r"((int)pred) : "memory");
}
DEVI void cp16(uint32_t dst, const void* src, uint32_t n = 16) { asm volatile("cp.async.cg.shared.global [%0], [%1], 16, %2;" :: "r"(dst), "l"(src), "r"(n) : "memory"); }
DEVI void cp_commit() { asm volatile("cp.async.commit_group;" ::: "memory"); }
template <int N> DEVI void cp_wait() { asm volatile("cp.async.wait_group %0;" :: "n"(N) : "memory"); }
DEVI void cp_wait_all() { asm volatile("cp.async.wait_all;" ::: "memory"); }
DEVI void pf_line(const void* p) { asm volatile("prefetch.global.L2 [%0];" :: "l"(p) : "memory"); }
DEVI void bulk_commit() { asm volatile("cp.async.bulk.commit_group;" ::: "memory"); }
DEVI void bulk_wait_all() { asm volatile("cp.async.bulk.wait_group 0;" ::: "memory"); }
DEVI void bulk_wait_read() { asm volatile("cp.async.bulk.wait_group.read 0;" ::: "memory"); }
DEVI void prefetch_map(const CUtensorMap* m) { asm volatile("prefetch.tensormap [%0];" :: "l"(m) : "memory"); }

__host__ __device__ constexpr uint32_t dlo(uint32_t off, uint32_t lbo) { return (off >> 4) + ((lbo >> 4) << 16); }
DEVI uint32_t pack_bf16(float lo, float hi) { uint32_t r; asm("cvt.rn.bf16x2.f32 %0, %1, %2;" : "=r"(r) : "f"(hi), "f"(lo)); return r; }
DEVI uint32_t pack_f16(float lo, float hi) { uint32_t r; asm("cvt.rn.f16x2.f32 %0, %1, %2;" : "=r"(r) : "f"(hi), "f"(lo)); return r; }
DEVI void stsm4(uint32_t addr, uint32_t r0, uint32_t r1, uint32_t r2, uint32_t r3) {
  asm volatile("stmatrix.sync.aligned.m8n8.x4.shared.b16 [%0], {%1,%2,%3,%4};" :: "r"(addr), "r"(r0), "r"(r1), "r"(r2), "r"(r3) : "memory");
}
DEVI void sts128(uint32_t addr, uint32_t a, uint32_t b, uint32_t c, uint32_t d) {
  asm volatile("st.shared.v4.b32 [%0], {%1,%2,%3,%4};" :: "r"(addr), "r"(a), "r"(b), "r"(c), "r"(d) : "memory");
}
DEVI void sts32(uint32_t addr, uint32_t v) { asm volatile("st.shared.b32 [%0], %1;" :: "r"(addr), "r"(v) : "memory"); }
DEVI uint32_t lds32(uint32_t a) { uint32_t v; asm volatile("ld.shared.b32 %0, [%1];" : "=r"(v) : "r"(a)); return v; }
DEVI void lds128(uint32_t* v, uint32_t a) {
  asm volatile("ld.shared.v4.b32 {%0,%1,%2,%3}, [%4];" : "=r"(v[0]), "=r"(v[1]), "=r"(v[2]), "=r"(v[3]) : "r"(a));
}
DEVI void ldg128(uint32_t* v, const void* p) {
  asm volatile("ld.global.nc.L1::no_allocate.v4.b32 {%0,%1,%2,%3}, [%4];" : "=r"(v[0]), "=r"(v[1]), "=r"(v[2]), "=r"(v[3]) : "l"(p));
}
DEVI uint32_t ldg32(const void* p) { uint32_t v; asm volatile("ld.global.nc.L1::no_allocate.b32 %0, [%1];" : "=r"(v) : "l"(p)); return v; }
DEVI uint32_t ldg32_if(const void* p, bool pred) {
  uint32_t v; asm volatile("{\n.reg .pred p;\nsetp.ne.b32 p, %2, 0;\nmov.b32 %0, 0;\n@p ld.global.nc.L1::no_allocate.b32 %0, [%1];\n}" : "=r"(v) : "l"(p), "r"((int)pred)); return v;
}
DEVI float phi(float t) {
  float e, s;
  asm("ex2.approx.ftz.f32 %0, %1;" : "=f"(e) : "f"(t * 1.4426950408889634f));
  asm("add.sat.f32 %0, %1, 0f358637BD;" : "=f"(s) : "f"(e));
  return fmaxf(t + 1.000001f, s);
}
DEVI void arrive_both(uint32_t bar, int lane, bool pred = true) {
  asm volatile("{\n.reg .pred p;\n.reg .b32 r;\nsetp.ne.b32 p, %2, 0;\nmapa.shared::cluster.u32 r, %0, %1;\n@p mbarrier.arrive.shared::cluster.b64 _, [r];\n}"
               :: "r"(bar), "r"(lane & 1), "r"((int)(pred && lane < 2)) : "memory");
}
DEVI uint32_t bmul2(uint32_t a, uint32_t b) { uint32_t r; asm("mul.rn.bf16x2 %0, %1, %2;" : "=r"(r) : "r"(a), "r"(b)); return r; }
DEVI uint32_t bfma2(uint32_t a, uint32_t b, uint32_t c) { uint32_t r; asm("fma.rn.bf16x2 %0, %1, %2, %3;" : "=r"(r) : "r"(a), "r"(b), "r"(c)); return r; }
DEVI uint32_t bamax2(uint32_t a, uint32_t b) { uint32_t r; asm("max.NaN.xorsign.abs.bf16x2 %0, %1, %2;" : "=r"(r) : "r"(a), "r"(b)); return r; }
DEVI uint32_t hmul2(uint32_t a, uint32_t b) { uint32_t r; asm("mul.rn.f16x2 %0, %1, %2;" : "=r"(r) : "r"(a), "r"(b)); return r; }
DEVI uint32_t hadd2(uint32_t a, uint32_t b) { uint32_t r; asm("add.rn.f16x2 %0, %1, %2;" : "=r"(r) : "r"(a), "r"(b)); return r; }
DEVI uint32_t hsub2(uint32_t a, uint32_t b) { uint32_t r; asm("sub.rn.f16x2 %0, %1, %2;" : "=r"(r) : "r"(a), "r"(b)); return r; }
DEVI uint32_t hfma2(uint32_t a, uint32_t b, uint32_t c) { uint32_t r; asm("fma.rn.f16x2 %0, %1, %2, %3;" : "=r"(r) : "r"(a), "r"(b), "r"(c)); return r; }
DEVI uint32_t hfnma2(uint32_t a, uint32_t b, uint32_t c) {
  uint32_t r; asm("{\n.reg .b32 n;\nneg.f16x2 n, %1;\nfma.rn.f16x2 %0, n, %2, %3;\n}" : "=r"(r) : "r"(a), "r"(b), "r"(c)); return r;
}
DEVI float bf_lo(uint32_t w) { return __uint_as_float(w << 16); }
DEVI float bf_hi(uint32_t w) { return __uint_as_float(w & 0xffff0000u); }

DEVI uint32_t chan_exponent(const uint32_t* w) {
  uint32_t m[4];
#pragma unroll
  for (int i = 0; i < 4; i++) m[i] = bamax2(w[i], w[i + 4]);
#pragma unroll
  for (int i = 8; i < 32; i++) m[i & 3] = bamax2(m[i & 3], w[i]);
  uint32_t x = bamax2(bamax2(m[0], m[1]), bamax2(m[2], m[3])) & 0x7fff7fffu;
  x = max(x >> 16, x & 0xffffu);
  x = __reduce_max_sync(0xffffffffu, x);
  return min(x >> 7, 251u);
}
DEVI uint32_t to_f16(uint32_t w, uint32_t mul) { const uint32_t y = bmul2(w, mul); return pack_f16(bf_lo(y), bf_hi(y)); }

struct Tile { int j, r; };
DEVI Tile tile_of() {
  int cta; asm volatile("mov.u32 %0, %%ctaid.x;" : "=r"(cta));
  {
    const int cl = cta >> 1, rd = ((cl - 36) * 37) >> 8;
    const int g = cl < 4 ? 0 : cl < 36 ? (cl - 4) & 7 : cl - 35 - 7 * rd, rr = cl < 4 ? 4 + cl : cl < 36 ? (cl - 4) >> 3 : 4 + rd;
    return Tile{(g & 6) | (cta & 1), 2 * rr + (g & 1)};
  }
  const int cl = cta >> 1, rd = ((cl - 36) * 37) >> 8, g2 = cl - 37 - 7 * rd;
  const int g = cl < 4 ? 7 : cl < 36 ? (cl - 5) & 7 : g2 < 0 ? 6 : g2;
  const int rr = cl < 4 ? 4 + cl : cl < 36 ? (cl - 4) >> 3 : 4 + rd;
  return Tile{(g & 6) | (cta & 1), 2 * rr + (g & 1)};
}

__host__ __device__ constexpr int upiece(int it) {
  for (int m = 0; m < 8; m++) if (U0 + m * UNUM / UDEN == it) return m;
  return -1;
}
__host__ __device__ constexpr bool prew(int it) { return it >= 0 && it < 31 && (((PREW & 1) && it >= UCV && it < UCV + 4) || ((PREW & 2) && upiece(it) >= 0)); }
static_assert(HCV >= U0 + 3 * UNUM / UDEN + NS1, "the filters overwrite the first pieces");

DEVI void twiddle(uint32_t& ore, uint32_t& oim, uint32_t re, uint32_t im, uint32_t c, uint32_t s) {
  ore = hfnma2(im, s, hmul2(re, c));
  oim = hfma2(re, s, hmul2(im, c));
}

__global__ void __cluster_dims__(2, 1, 1) __launch_bounds__(kThreads, 1)
fused_kernel(const __grid_constant__ Params P) {
  extern __shared__ __align__(1024) uint8_t smem[];
  const uint32_t sb = (uint32_t)__cvta_generic_to_shared(smem);
  const int tid = threadIdx.x, lane = tid & 31;
  const int warp = tid >> 5, warpu = __shfl_sync(0xffffffffu, tid >> 5, 0);
  const int cta = blockIdx.x, rho = cta & 1, cl = cta >> 1;
  const uint32_t tstart = clock32();
  auto bar = [&](int i) INL { return sb + SM_BAR + 8u * i; };
  auto load1 = [&](int it, int s, int j, int r, bool mc) INL {
    const uint32_t fb = bar(B_F1 + s), xs = sb + x1_off(it);
    mbar_expect(fb, (it & 1) ? 16384 : 32768);
    tma4d(sb + w1_off(s), &P.w1, 32 * it, 2 * j, 1, fb);
    if (XEARLY && mc && it >= 7) {
      if ((it & 1) && it < 31) tma2d_mc(sb + x1_off(it + 1) + rho * 8192, &P.x, 32 * it + 32, 128 * r + 64 * rho, bar(B_F1 + (s + 1 == NS1 ? 0 : s + 1)));
    } else if (!(it & 1)) {
      if (mc) tma2d_mc(xs + rho * 8192, &P.x, 32 * it, 128 * r + 64 * rho, fb);
      else { tma2d(xs, &P.x, 32 * it, 128 * r, fb); tma2d(xs + 8192, &P.x, 32 * it, 128 * r + 64, fb); }
    }
  };
  TSTAMP(tid == 0, 0); GSTAMP(tid == 0, 62);

  if (warpu == 8 && elect()) {
    for (int i = 0; i < NS1; i++) mbar_init(bar(B_F1 + i), 1);
    fence_async_smem();
    const Tile T = tile_of();
    for (int i = 0; i < EARLY; i++) load1(i, slot1(i), T.j, T.r, false);
    asm volatile("fence.mbarrier_init.release.cluster;" ::: "memory");
  }
  if (tid == 288) {
    for (int i = 0; i < NS1; i++) mbar_init(bar(B_E1 + i), 16);

    for (int i = 0; i < 4; i++) { mbar_init(bar(B_F2 + i), 1); mbar_init(bar(B_E2 + i), 16); }
    asm volatile("fence.mbarrier_init.release.cluster;" ::: "memory");
  }
  if (tid == 352) {
    if (sb != SM_BASE + (rho << 24)) __trap();
    for (int i = B_KVL; i < B_COUNT; i++) mbar_init(bar(i), 1);
    mbar_expect(bar(B_Q), 32768);
    asm volatile("fence.mbarrier_init.release.cluster;" ::: "memory");
  }
  if (tid == 320) {
    mbar_init(bar(B_F2M), 3); mbar_init(bar(B_MAX), 1); mbar_init(bar(B_VST), 8); mbar_init(bar(B_ZST), 8);
    mbar_init(bar(B_ZERO), 1); mbar_init(bar(B_U), 1); mbar_init(bar(B_KVP), 8); mbar_init(bar(B_KV), 1);
    for (int i = 0; i < 2; i++) { mbar_init(bar(B_OW + i), 8); mbar_init(bar(B_OFREE + i), 2); }
    mbar_init(bar(B_S1), 8); mbar_init(bar(B_Y), 9); mbar_init(bar(B_KVI), 8); mbar_init(bar(B_I2), 8); mbar_init(bar(B_I2 + 1), 8);
    mbar_expect(bar(B_U), 16384); mbar_expect(bar(B_MAX), 512); mbar_expect(bar(B_Y), 16384);
    asm volatile("fence.mbarrier_init.release.cluster;" ::: "memory");
  }
  __syncwarp();
  cluster_sync();

  if (warpu < 8) {
    asm volatile("setmaxnreg.inc.sync.aligned.u32 %0;" :: "n"(CREGS));
    const int wg = warp >> 2, wq = warp & 3, g = lane >> 2, q = lane & 3;
    constexpr uint32_t sbq = SM_BASE >> 4;
    const uint32_t sb = SM_BASE + (rho << 24);
    auto bar = [&](int i) INL { return sb + SM_BAR + 8u * i; };
    const uint32_t wgu = warpu >> 2;
    const int srow = wg * 64 + wq * 16 + (lane & 15);
    const uint32_t stm = srow * 128 + (((lane >> 4) ^ (srow & 7)) << 4);
    auto stage2 = [&](float* acc, int n, bool first, bool wait = true) INL {
      const int s = n & 3;
      if (wait) mbar_wait(bar(B_F2 + s), (n >> 2) & 1);
      const uint32_t da = sbq + wgu * 512 + s * (ST2 >> 4) + dlo(0, 16), db = sbq + s * (ST2 >> 4) + dlo(16384, 8192);
      wg_fence();
      if (first) mma_n128_init(acc, da, db); else mma_n128(acc, da, db);
#pragma unroll
      for (int kk = 1; kk < 4; kk++) mma_n128(acc, da + 2 * kk, db + kk * (2048 >> 4));
      wg_commit();
    };
    auto release2 = [&](int n) INL { arrive_both(bar(B_E2 + (n & 3)), lane); };
    auto publish = [&](int b) INL { fence_async_smem(); __syncwarp(); mbar_arrive_if(bar(b), lane == 0); };

    float aq[64];
    uint32_t f1[8], tw[4];
    uint32_t su[2][32], sh[2][32];
    uint32_t x0[4][8], x1[4][8], p0[2][8], p1[2][8], z0[2][8], z1[2][8];
    auto s1 = [&](uint32_t* d, uint32_t base) INL {
      const uint32_t db = sbq + wgu * 1024 + dlo(base, 128);
      mma_s1_init(d, f1, db);
      mma_s1(d, f1 + 4, db + (256 >> 4));
      wg_commit();
    };
    const uint32_t dre = sbq + dlo(SM_F2 + 512, 128), dim = sbq + dlo(SM_F2, 128);
    auto fwd2 = [&](uint32_t (*x)[8], int c) INL {
      uint32_t a[4][8];
#pragma unroll
      for (int t = 0; t < 4; t++) {
        uint32_t* s = (t < 2 ? sh[c >> 1] : su[c >> 1]) + 16 * (c & 1) + 8 * (t & 1);
        pin<8>(s);
#pragma unroll
        for (int i = 0; i < 4; i++) twiddle(a[t][i], a[t][4 + i], s[4 * (i & 1) + (i & 2)], s[4 * (i & 1) + (i & 2) + 1], tw[i & 2], tw[(i & 2) + 1]);
      }
      wg_fence();
#pragma unroll
      for (int t = 0; t < 4; t++) { mma_s2_init(x[t], a[t], dre); mma_s2(x[t], a[t] + 4, dim); }
      wg_commit();
    };
    auto product = [&](uint32_t (*a)[8], uint32_t (*x)[8], int i) INL {
#pragma unroll
      for (int t = 0; t < 4; t++) { pin<2>(x[t] + i); pin<2>(x[t] + 4 + i); }
      auto hr = [&](int l) INL { return x[l >> 1][i + (l & 1)]; };
      auto hi = [&](int l) INL { return x[l >> 1][4 + i + (l & 1)]; };
      auto ur = [&](int l) INL { return x[2 + (l >> 1)][i + (l & 1)]; };
      auto ui = [&](int l) INL { return x[2 + (l >> 1)][4 + i + (l & 1)]; };
      uint32_t gr[4], gi[4];
      gr[0] = hr(0); gi[0] = hi(0);
#pragma unroll
      for (int l = 1; l < 4; l++) { gr[l] = hadd2(hr(l), hi(l - 1)); gi[l] = hsub2(hi(l), hr(l - 1)); }
#pragma unroll
      for (int p = 0; p < 4; p++) {
        uint32_t re = hfnma2(gi[0], ui(p), hmul2(gr[0], ur(p))), im = hfma2(gi[0], ur(p), hmul2(gr[0], ui(p)));
#pragma unroll
        for (int l = 1; l <= p; l++) {
          re = hfnma2(gi[l], ui(p - l), hfma2(gr[l], ur(p - l), re));
          im = hfma2(gi[l], ur(p - l), hfma2(gr[l], ui(p - l), im));
        }
        a[p >> 1][i + (p & 1)] = re; a[p >> 1][4 + i + (p & 1)] = im;
      }
#pragma unroll
      for (int t = 0; t < 2; t++) { pin<2>(a[t] + i); pin<2>(a[t] + 4 + i); }
    };
    auto inv1 = [&](uint32_t (*z)[8], uint32_t (*a)[8]) INL {
      wg_fence();
#pragma unroll
      for (int t = 0; t < 2; t++) { mma_s2_init(z[t], a[t], dre); mma_s2_neg(z[t], a[t] + 4, dim); }
      wg_commit();
    };
    auto zstore = [&](uint32_t (*z)[8], int c) INL {
      const uint32_t zoff = sb + RB + (q >> 1) * (RU + 16 - RB) + (8 * rho + 4 * wg) * 2048 + (4 * (8 * wq + g) + 2 * (q & 1)) * 16;
#pragma unroll
      for (int t = 0; t < 2; t++) {
        uint32_t a[8];
        pin<8>(z[t]);
#pragma unroll
        for (int i = 0; i < 4; i++) twiddle(a[i], a[4 + i], z[t][i], z[t][4 + i], tw[i & 2], tw[(i & 2) + 1]);
        const uint32_t dst = zoff + t * (16384 - rho * 32768) + c * 2048;
        sts128(dst, a[0], a[1], a[2], a[3]);
        sts128(dst + 16, a[4], a[5], a[6], a[7]);
      }
    };
    float kvr[18];
    {
      float ak[64], av[64];
      auto kstep = [&](int it) INL {
        const int s = slot1(it);
        if (!prew(it - 1)) mbar_wait(bar(B_F1 + s), (it / NS1) & 1);
        TSTAMP(tid == 0 && it == 0, 1);
        const uint32_t dx = sbq + dlo(x1_off(it) + (it & 1) * 64, 16), da = dx + wgu * 512;
        const uint32_t dk = sbq + wgu * 256 + dlo(w1_off(s), 16), dv = sbq + dlo(w1_off(s) + 8192, 4096);
        wg_fence();
        if (it == 0) { mma_kt_init(ak, dk, dx); mma_n128_init(av, da, dv); }
        else { mma_kt(ak, dk, dx); mma_n128(av, da, dv); }
        mma_kt(ak, dk + (2048 >> 4), dx + 2);
        mma_n128(av, da + 2, dv + (2048 >> 4));
        wg_commit();
        wg_wait<1>();
        if (it > 0) arrive_both(bar(B_E1 + (s + NS1 - 1) % NS1), lane);
        if (prew(it)) mbar_wait(bar(B_F1 + slot1(it + 1)), ((it + 1) / NS1) & 1);
        KSTAMP(it);
      };
      uint32_t w[32], kk[35], u[32], sw[4], mx[16], um, umul, ud, hmul, eu;
      unsigned short dskip;
      float tap0;
      const __nv_bfloat16* hp;
      const bool local = (g >> 2) == rho;
      auto calcu = [&](int e0, int e1) INL {
#pragma unroll
        for (int e = e0; e < e1; e++) {
          pin<1>(kk + 3 + e); pin<1>(u + e);
          u[e] = bmul2(bfma2(kk[3 + e], sw[0], bfma2(kk[2 + e], sw[1], bfma2(kk[1 + e], sw[2], bmul2(kk[e], sw[3])))), u[e]);
          um = bamax2(um, u[e]);
          pin<1>(u + e);
        }
        pin<1>(&um);
      };
      ldg128(sw, P.shift_k + (cl * 16 + 2 * g) * 4);
#pragma unroll
      for (int e = 0; e < 3; e++) kk[e] = ldg32(P.k_ptr + (1021 + e) * 1024 + 16 * cl + 2 * g);
      asm volatile("ld.global.nc.b16 %0, [%1];" : "=h"(dskip) : "l"(P.ssm_d + 8 * cta + warp));
      auto side = [&](int it) INL {
        if (it == 1) {
          pin<4>(sw);
          const uint32_t t0 = __byte_perm(sw[0], sw[2], 0x5410), t1 = __byte_perm(sw[0], sw[2], 0x7632), t2 = __byte_perm(sw[1], sw[3], 0x5410);
          sw[3] = __byte_perm(sw[1], sw[3], 0x7632); sw[0] = t0; sw[1] = t1; sw[2] = t2;
          const bool halo = rho && warp + q == 0;
#pragma unroll
          for (int e = 0; e < 3; e++) kk[e] = halo ? kk[e] : 0u;
          tap0 = lane == 0 ? bf_lo(dskip) : 0.f;
          um = 0;
          pin<4>(sw); pin<3>(kk); pin<1>(&tap0);
        }
        if (upiece(it - 1) >= 0) {
          const int m = upiece(it - 1);
          calcu(m == 0 ? 3 : 4 * m, 4 * m + 4);
          if (m == 7) {
            pin<3>(kk);
            calcu(0, 3);
            um = bamax2(um, __shfl_xor_sync(0xffffffffu, um, 1));
            um = bamax2(um, __shfl_xor_sync(0xffffffffu, um, 2));
            st_async1_if(mapa(sb + SM_MAX + g * 64 + (8 * rho + warp) * 4, q & 1), um, mapa(bar(B_MAX), q & 1), q < 2);
          }
        }
        if (upiece(it) >= 0) {
          const int m = upiece(it);
          const uint32_t a = sb + RB + m * 8192 + warp * 128 + q * 32 + g * 4;
          mbar_wait(bar(B_KVL + m), 0);
#pragma unroll
          for (int e = 0; e < 4; e++) { kk[3 + 4 * m + e] = lds32(a + e * 1024); u[4 * m + e] = lds32(a + 4096 + e * 1024); }
          if (m == 7) {
#pragma unroll
            for (int e = 0; e < 3; e++)
              asm volatile("{\n.reg .pred p;\nsetp.ne.b32 p, %2, 0;\n@p ld.shared.b32 %0, [%1];\n}" : "+r"(kk[e]) : "r"(a + (e + 1) * 1024 - 32), "r"(warp + q));
          }
        }
        if (it == UCV - 1 - UPRE) {
          mbar_wait(bar(B_MAX), 0);
          TSTAMP(tid == 0, 5);
#pragma unroll
          for (int i = 0; i < 4; i++) lds128(mx + 4 * i, sb + SM_MAX + g * 64 + i * 16);
        }
        if (it == UCV - UPRE) {
          pin<16>(mx);
#pragma unroll
          for (int i = 4; i < 16; i++) mx[i & 3] = bamax2(mx[i & 3], mx[i]);
          const uint32_t e2 = __vminu2((bamax2(bamax2(mx[0], mx[1]), bamax2(mx[2], mx[3])) >> 7) & 0x00ff00ffu, 0x00fb00fbu);
          umul = (0x00fd00fdu - e2) << 7;
          eu = (__shfl_sync(0xffffffffu, e2, 16 * rho + 4 * (warp >> 1)) >> (16 * (warp & 1))) & 0xffu;
          ud = mapa(sb + RU + (g & 3) * 8192 + (2 * rho + wg) * 1024 + (4 * wq + q) * 16, g >> 2);
        }
        if (it >= UCV && it < UCV + 4) {
          const int i = it - UCV;
          uint32_t* y = u + 8 * i;
          pin<8>(y);
#pragma unroll
          for (int e = 0; e < 8; e++) y[e] = bmul2(y[e], umul);
          const uint32_t dst = ud + (i & 1) * 512 + (i >> 1) * 256, ub = mapa(bar(B_U), rho ^ 1);
          st_either4(local, dst, pack_f16(bf_lo(y[0]), bf_lo(y[1])), pack_f16(bf_lo(y[2]), bf_lo(y[3])), pack_f16(bf_lo(y[4]), bf_lo(y[5])), pack_f16(bf_lo(y[6]), bf_lo(y[7])), ub);
          st_either4(local, dst + 4096, pack_f16(bf_hi(y[0]), bf_hi(y[1])), pack_f16(bf_hi(y[2]), bf_hi(y[3])), pack_f16(bf_hi(y[4]), bf_hi(y[5])), pack_f16(bf_hi(y[6]), bf_hi(y[7])), ub);
        }
        if (it == H0) { hp = P.ssm_k + (size_t)(8 * cta + warp) * 2048 + (4 * (lane & 7) + (lane >> 3)) * 8; asm volatile("" : "+l"(hp)); }
        if (it >= H0 && it < H0 + 8 * HS && (it - H0) % HS == 0) ldg128(w + 4 * ((it - H0) / HS), hp + (it - H0) / HS * 256);
        if (it == HCV - 1) {
          pin<32>(w);
          tap0 += bf_lo(w[0]);
          w[0] = pack_bf16(tap0, bf_hi(w[0]));
          hmul = (252u - chan_exponent(w)) * 0x00800080u;
        }
        if (it == (UCV > HCV - 1 ? UCV : HCV - 1)) {
          const int e = min(max((int)(eu + 128 - (hmul >> 23)), 0), 254);
          asm volatile("st.shared.b16 [%0], %1;" :: "r"(sb + SM_SCALE + 2 * warp), "h"((unsigned short)(e << 7)) : "memory");
        }
        if (it >= HCV && it < HCV + 4) {
          const uint32_t dst = sb + RB + warp * 4096 + (it - HCV) * 1024 + ((lane >> 3) & 1) * 512 + (lane >> 4) * 256 + (lane & 7) * 16;
#pragma unroll
          for (int i = 2 * (it - HCV); i < 2 * (it - HCV) + 2; i++) {
            pin<4>(w + 4 * i);
            const uint32_t w0 = i == 0 ? pack_f16(tap0 * bf_lo(hmul), bf_hi(w[0]) * bf_lo(hmul)) : to_f16(w[4 * i], hmul);
            sts128(dst + (i & 1) * 128, w0, to_f16(w[4 * i + 1], hmul), to_f16(w[4 * i + 2], hmul), to_f16(w[4 * i + 3], hmul));
          }
        }
      };
#pragma unroll
      for (int it = 0; it < 32; it++) { kstep(it); side(it); }
      auto qstep = [&](int n) INL {
        stage2(aq, n, n == 0);
        wg_wait<1>();
        if (n == 0) arrive_both(bar(B_E1 + NS1 - 1), lane); else release2(n - 1);
        QSTAMP(n);
      };
      uint32_t pk[8][4];
      auto phik = [&](int kt) INL {
        pin<8>(ak + 8 * kt);
#pragma unroll
        for (int i = 0; i < 4; i++) pk[kt][i] = pack_bf16(phi(ak[8 * kt + 2 * i]), phi(ak[8 * kt + 2 * i + 1]));
        pin<4>(pk[kt]);
      };
      auto vst = [&](int kt) INL {
        float* a = av + 8 * kt;
        pin<8>(a);
        stsm4(sb + RA + (kt >> 2) * 16384 + (stm ^ ((kt & 3) << 5)), pack_bf16(a[0], a[1]), pack_bf16(a[2], a[3]), pack_bf16(a[4], a[5]), pack_bf16(a[6], a[7]));
      };
      qstep(0);
      TSTAMP(tid == 0, 2);
      phik(0); phik(1);
      mbar_wait(bar(B_E1 + NS1 - 1), 1);
      vst(0); vst(1);
      qstep(1);
      vst(2); vst(3); vst(4); phik(2); phik(3);
      qstep(2);
      vst(5); vst(6); vst(7);
      publish(B_VST);
      phik(4); phik(5);
      qstep(3);
      phik(6); phik(7);
      mbar_wait(bar(B_VST), 0);
      TSTAMP(tid == 0, 3);
      float dkv[36];
      wg_fence();
#pragma unroll
      for (int ks = 0; ks < 8; ks++) {
        const uint32_t db = sbq + wgu * (1024u - (1024u << 16)) + dlo(RA + ks * 2048, SM_ONES - RA - ks * 2048);
        if (ks == 0) mma_kv_init(dkv, pk[ks], db); else mma_kv(dkv, pk[ks], db);
      }
      wg_commit();
      ldg128(f1, d_tab + (tid & 127) * 4); ldg128(f1 + 4, d_tab + 512 + (tid & 127) * 4); ldg128(tw, d_tab + 1024 + (tid & 127) * 4);
      float* gacc = &g_kv[tile_of().j][warp * 512 + lane * 4];
      auto kvred = [&](int b) INL {
        const bool hh = wq >> 1;
        asm volatile("red.relaxed.gpu.global.add.v4.f32 [%0], {%1,%2,%3,%4};" :: "l"(gacc + b * 128), "f"(hh ? dkv[16 + 4 * b] : dkv[4 * b]),
                     "f"(hh ? dkv[17 + 4 * b] : dkv[1 + 4 * b]), "f"(hh ? dkv[18 + 4 * b] : dkv[2 + 4 * b]), "f"(hh ? dkv[19 + 4 * b] : dkv[3 + 4 * b]) : "memory");
      };
      qstep(4);
      mbar_wait(bar(B_ZERO), 0);
      pin<36>(dkv);
      kvred(0); kvred(1);
      qstep(5);
      kvred(2); kvred(3);
      asm volatile("{\n.reg .pred p;\nsetp.eq.s32 p, %3, 0;\n@p red.relaxed.gpu.global.add.v2.f32 [%0], {%1,%2};\n}"
                   :: "l"(gacc + 4096 - warp * 496 - g * 14), "f"(dkv[32]), "f"(dkv[34]), "r"(q) : "memory");
      __syncwarp();
      mbar_arrive_if(bar(B_KVP), lane == 0);
      TSTAMP(tid == 0, 4);
      qstep(6);
      mbar_wait(bar(B_U), 0);
      fence_async_smem();
      wg_fence(); s1(sh[0], RB); s1(su[0], RU);
      qstep(7);
      mbar_wait(bar(B_F2M), 0);
      fwd2(x0, 0);
      qstep(8);
      fwd2(x1, 1);
      qstep(9);
      product(p0, x0, 0);
      qstep(10);
      product(p0, x0, 2);
      qstep(11);
      product(p1, x1, 0);
      qstep(12);
      product(p1, x1, 2);
      qstep(13);
      qstep(14);
      mbar_wait(bar(B_KV), 0);
      TSTAMP(tid == 0, 7);
#pragma unroll
      for (int b = 0; b < 4; b++)
        asm volatile("ld.global.cg.v4.f32 {%0,%1,%2,%3}, [%4];" : "=f"(kvr[4 * b]), "=f"(kvr[4 * b + 1]), "=f"(kvr[4 * b + 2]), "=f"(kvr[4 * b + 3]) : "l"(gacc + b * 128) : "memory");
      asm volatile("ld.global.cg.v2.f32 {%0,%1}, [%2];" : "=f"(kvr[16]), "=f"(kvr[17]) : "l"(gacc + 4096 - warp * 496 - g * 14 - q * 4) : "memory");
      qstep(15);
    }

    {
      uint32_t pq[4][8];
      float dn[4][20];
      auto phiq = [&](int h) INL {
        pin<16>(aq + 16 * h);
#pragma unroll
        for (int i = 0; i < 8; i++) pq[h][i] = pack_bf16(phi(aq[16 * h + 2 * i]), phi(aq[16 * h + 2 * i + 1]));
        pin<8>(pq[h]);
      };
      auto omma = [&](int h) INL {
        const uint32_t db = sbq + dlo(R_KV + h * KV_HEAD, 128);
        wg_fence();
        mma_o_init(dn[h], pq[h], db);
        mma_o(dn[h], pq[h] + 4, db + (256 >> 4));
        wg_commit();
      };
      auto onorm = [&](int h) INL {
        pin<20>(dn[h]);
        const float i0 = __fdividef(1.f, dn[h][16] + 1e-6f), i1 = __fdividef(1.f, dn[h][18] + 1e-6f);
#pragma unroll
        for (int hf = 0; hf < 2; hf++) {
          const float* a = dn[h] + 8 * hf;
          stsm4(sb + (h >> 1) * ST2 + (stm ^ (((h & 1) * 2 + hf) << 5)), pack_bf16(a[0] * i0, a[1] * i0), pack_bf16(a[2] * i1, a[3] * i1),
                pack_bf16(a[4] * i0, a[5] * i0), pack_bf16(a[6] * i1, a[7] * i1));
        }
        if (h & 1) publish(B_OW + (h >> 1));
      };
      wg_fence();
      s1(su[1], RU + 8192);
      {
        const uint32_t dst = sb + R_KV + (warp >> 1) * KV_HEAD + (warp & 1) * 256 + lane * 4;
        mbar_wait(bar(B_E2 + 2), 1);
        pin<18>(kvr);
#pragma unroll
        for (int b = 0; b < 4; b++) { sts32(dst + b * 512, pack_bf16(kvr[4 * b], kvr[4 * b + 1])); sts32(dst + b * 512 + 128, pack_bf16(kvr[4 * b + 2], kvr[4 * b + 3])); }
        sts32(dst + 2048, pack_bf16(kvr[16], kvr[16])); sts32(dst + 2176, pack_bf16(kvr[17], kvr[17]));
        publish(B_KVI);
      }
      wg_wait<1>();
      release2(15);
      TSTAMP(tid == 0, 6);
      phiq(0);
      mbar_wait(bar(B_KVI), 0);
      omma(0);
      phiq(1);
      wg_wait<0>(); onorm(0);
      omma(1); s1(sh[1], RB + 8192);
      phiq(2);
      wg_wait<1>(); onorm(1);
      TSTAMP(tid == 0, 8);
      omma(2);
      phiq(3);
      wg_wait<0>(); onorm(2);
      mbar_arrive_if(bar(B_S1), lane == 0);
      omma(3);
      inv1(z0, p0);
      wg_wait<1>(); onorm(3);
      TSTAMP(tid == 0, 9);
    }

    float acc[64];
    {
      auto own = [&](int c) INL { mbar_wait(bar(B_OW + c), 0); stage2(acc, 16 + c, c == 0); };
      uint32_t gf[4][4];
      inv1(z1, p1);
      fwd2(x0, 2);
      wg_wait<1>();
      mbar_wait(bar(B_S1), 0);
      zstore(z0, 0); zstore(z1, 1);
      wg_wait<0>();
      own(0);
      fwd2(x1, 3);
      product(p0, x0, 0); product(p0, x0, 2);
      inv1(z0, p0);
      own(1);
      wg_wait<2>();
      release2(16);
      ldg128(gf[1], d_tab + 1536 + (tid & 127) * 4); ldg128(gf[3], d_tab + 2048 + (tid & 127) * 4);
      product(p1, x1, 0); product(p1, x1, 2);
      inv1(z1, p1);
      wg_wait<2>();
      zstore(z0, 2);
#pragma unroll
      for (int i = 0; i < 4; i += 2) {
        pin<4>(gf[i + 1]);
        gf[i][0] = gf[i][1] = gf[i + 1][0]; gf[i][2] = gf[i][3] = gf[i + 1][1];
        gf[i + 1][0] = gf[i + 1][1] = gf[i + 1][2]; gf[i + 1][2] = gf[i + 1][3];
        pin<4>(gf[i]); pin<4>(gf[i + 1]);
      }
      wg_wait<0>();
      release2(17);
      zstore(z1, 3);
      publish(B_ZST);
      TSTAMP(tid == 0, 10);
      mbar_wait(bar(B_ZST), 0);
      float y[64];
      {
        const uint32_t db = sbq + wgu * ((RU + 16 - RB) >> 4) + dlo(RB, 128);
        wg_fence();
        mma_i2_init(y, gf[0], db, 0xEEEE4444u);
#pragma unroll
        for (int i = 1; i < 4; i++) mma_i2(y, gf[i], db + i * (512 >> 4), 0xEEEE4444u);
        wg_commit();
      }
      uint32_t sc[4];
      lds128(sc, sb + SM_SCALE);
      TSTAMP(tid == 0, 11);
      stage2(acc, 18, false);
      TSTAMP(tid == 0, 13);
      wg_wait<1>();
      arrive_both(bar(B_I2 + wg), lane);
      pin<64>(y);
      uint32_t yv[8][4];
#pragma unroll
      for (int i = 0; i < 8; i++)
#pragma unroll
        for (int m = 0; m < 4; m++) yv[i][m] = bmul2(pack_bf16(y[32 * (i >> 2) + (i & 3) + 8 * m], y[32 * (i >> 2) + (i & 3) + 8 * m + 4]), sc[m]);
      pin<32>(&yv[0][0]);
      stage2(acc, 19, false);
      wg_wait<1>();
      release2(18);
      mbar_wait(bar(B_I2 + wg), 0);
      const uint32_t ya = sb + RB + wg * (RU - RB) + wq * 2048 + lane * 16;
      const uint32_t yr = mapa((ya + Y_IN) ^ 64, rho ^ 1), yb = mapa(bar(B_Y), rho ^ 1);
#pragma unroll
      for (int i = 0; i < 4; i++) {
        sts128(ya + Y_OWN + i * 512, yv[i][0], yv[i][1], yv[i][2], yv[i][3]);
        st_async4(yr + i * 512, yv[4 + i][0], yv[4 + i][1], yv[4 + i][2], yv[4 + i][3], yb);
      }
      __syncwarp();
      mbar_arrive_if(bar(B_Y), lane == 0);
      TSTAMP(tid == 0, 12);
    }
#pragma unroll 1
    for (int n = 20; n < 32; n++) {
      stage2(acc, n, false);
      TSTAMP(tid == 0 && n == 26, 14);
      wg_wait<1>();
      arrive_both(bar(B_E2 + ((n - 1) & 3)), lane, n <= 28);
      QSTAMP(n);
    }
    wg_wait<0>();
    TSTAMP(tid == 0, 15);
    pin<64>(acc);
    {
      const uint32_t stg = sb + RB + wg * (RU - RB - 8192);
      const Tile T = tile_of();
#pragma unroll
      for (int c = 0; c < 2; c++) {
#pragma unroll
        for (int t = 0; t < 4; t++) {
          const float* a = acc + 32 * c + 8 * t;
          stsm4(stg + c * 8192 + (stm ^ (t << 5)), pack_bf16(a[0], a[1]), pack_bf16(a[2], a[3]), pack_bf16(a[4], a[5]), pack_bf16(a[6], a[7]));
        }
        fence_async_smem();
        bar_sync(2 + wg, 128);
        if ((warpu & 3) == 0 && elect()) { tma2d_store(&P.outa, sb + RB + wgu * (RU - RB) + c * 8192, 128 * T.j + 64 * c, 128 * T.r + 64 * wgu); bulk_commit(); }
      }
      bulk_wait_read();
      TSTAMP(tid == 0, 16);
    }
    __syncwarp();
    cluster_sync();
  } else {
    asm volatile("setmaxnreg.dec.sync.aligned.u32 %0;" :: "n"(AREGS));
    const Tile T = tile_of();
    const int j = T.j, r = T.r;
    auto kcol = [&](int n) INL {
      const int c = n >= 25, m = n - (c ? 25 : 18);
      return n < 18 ? 128 * j + 64 * (n & 1) : 128 * (m == 0 ? j ^ 1 : ((j & 6) + 1 + m) & 7) + 64 * c;
    };
    if (warpu == 8) {
      uint32_t ph = 0;
      int s = slot1(EARLY);
#pragma unroll 1
      for (int it = EARLY; it < 32; ++it, s = s + 1 == NS1 ? 0 : s + 1) {
        if (it >= NS1) { mbar_wait(bar(B_E1 + s), (ph >> s) & 1); ph ^= 1u << s; }
        if (elect()) {
          load1(it, s, j, r, true);
          if (it == 8) { prefetch_map(&P.w2); prefetch_map(&P.wo); prefetch_map(&P.o); prefetch_map(&P.q); prefetch_map(&P.outb); prefetch_map(&P.outa); }
        }
        if (RPF && !(it & 1) && it >= RPF0) {
          const int kc = (it + RPF) >> 1;
          if (kc < 16 && (RPFM >> (lane >> 4) & 1))
            pf_line(lane < 16 ? P.x_ptr + (size_t)(cta * 16 + lane) * 1024 + kc * 64 : P.w_ptr + (size_t)(kc * 64 + cl) * 3072 + 1024 + rho * 1024 + (lane & 15) * 64);
        }
        if (it >= WQPF && it < WQPF + 4) pf_line(P.w_ptr + (size_t)(cta + (2 * (it - WQPF) + (lane >> 4)) * 128) * 3072 + (lane & 15) * 64);
      }
#pragma unroll 1
      for (int n = 0; n < 16; ++n) {
        const int s = n & 3, i = n + (n >> 1);
        mbar_wait(bar(n < 4 ? B_E1 + i : B_E2 + s), n < 4 ? (ph >> i) & 1 : ((n >> 2) - 1) & 1);
        const uint32_t st = sb + s * ST2, fb = bar(B_F2 + s);
        if (elect()) {
          mbar_expect(fb, ST2);
          tma4d(st + 16384, &P.w2, 64 * n, 2 * j, 0, fb);
          tma2d_mc(st + rho * 8192, &P.x, 64 * n, 128 * r + 64 * rho, fb);
        }
        if (n < 12) pf_line((n < 8 ? P.q_ptr + cta * 16384 : P.wo_ptr + cta * 8192 - 16384) + n * 2048 + lane * 64);
      }
      auto loadw = [&](int n) INL {
        const int s = n & 3;
        mbar_wait(bar(B_E2 + s), ((n >> 2) - 1) & 1);
        if (elect()) { mbar_expect(bar(B_F2 + s), n < 18 ? 16384 : ST2); tma4d(sb + s * ST2 + 16384, &P.wo, kcol(n), 2 * j, 0, bar(B_F2 + s)); }
      };
#pragma unroll 1
      for (int n = 16; n < 20; ++n) {
        if (elect()) for (int w = 2 * n - 32; w < 2 * n - 30; w++) tma5d(sb + RA + w * 4096, &P.q, 16 * cl, 2 * rho, w & 4, w & 3, bar(B_Q));
        loadw(n);
      }
      mbar_wait(bar(B_OW + 1), 0);
#pragma unroll 1
      for (int n = 18; n < 32; ++n) {
        const int s = n & 3, kc = kcol(n);
        const uint32_t st = sb + s * ST2, fb = bar(B_F2 + s);
        if (n >= 20) loadw(n);
        if (n == 20 || n == 21) mbar_wait(bar(B_OFREE + s), 0);
        mbar_wait(bar(B_RDY + n - 18), 0);
        if (elect()) {
          if (n == 18 || n == 25) { tma2d(st, &P.o, kc, 128 * r, fb); tma2d(st + 8192, &P.o, kc, 128 * r + 64, fb); }
          else tma2d_mc(st + rho * 8192, &P.o, kc, 128 * r + 64 * rho, fb);
        }
      }
    } else {
      const int at = tid - 288, aw = warpu - 9;
      if (at < KV_WORDS / 64) reinterpret_cast<float4*>(&g_kv[j][r * (KV_WORDS / 16)])[at] = make_float4(0.f, 0.f, 0.f, 0.f);
      for (int i = at; i < 128; i += 96) sts128(sb + SM_ONES + i * 16, 0x3f803f80u, 0x3f803f80u, 0x3f803f80u, 0x3f803f80u);
      fence_async_smem();
      bar_sync(4, 96);
      if (at == 64) asm volatile("fence.release.gpu;\nred.relaxed.gpu.global.add.u32 [%0], 1;" :: "l"(&g_zflag[j * 32]) : "memory");
      const unsigned epoch = ld_relaxed(&g_epoch[cta]);
      if (aw == 1) {
#pragma unroll 1
        for (int m = 0; m < 16; m++) {
          pace(tstart, PREP0 + m * PREPGAP);
          if (elect()) {
            if (!(m & 1)) mbar_expect(bar(B_KVL + (m >> 1)), (EXP & 4) ? 0 : 8192);
            if (!(EXP & 4)) tma3d(sb + RB + m * 4096, (m & 1) ? &P.v : &P.k, 16 * cl, 32 * rho, 2 * (m & 14), bar(B_KVL + (m >> 1)));
          }
        }
      }
      if (at == 0) { flag_wait(&g_zflag[j * 32], 16u * (epoch + 1)); mbar_arrive(bar(B_ZERO)); }
      __syncwarp();
      if (at < 80 && !(EXP & 8)) pf_line(d_tab + at * 32);
      uint32_t f2[4];
      ldg128(f2, d_tab + 2560 + at * 4);
      mbar_wait_long(bar(B_KVP), 0);
      sts128(sb + SM_F2 + at * 16, f2[0], f2[1], f2[2], f2[3]);
      fence_async_smem();
      __syncwarp();
      mbar_arrive_if(bar(B_F2M), lane == 0);
      if (at == 64) {
        asm volatile("fence.release.gpu;\nred.relaxed.gpu.global.add.u32 [%0], 1;" :: "l"(&g_kvflag[j * 32]) : "memory");
        TSTAMP(true, 18);
        flag_wait(&g_kvflag[j * 32], 16u * (epoch + 1));
        mbar_arrive(bar(B_KV));
        TSTAMP(true, 19);
      }
      __syncwarp();
      if (aw < 2) {
        mbar_wait_long(bar(B_OW + aw), 0);
        if (elect()) {
          const uint32_t src = sb + aw * ST2;
          tma2d_store(&P.o, src, 128 * j + 64 * aw, 128 * r);
          tma2d_store(&P.o, src + 8192, 128 * j + 64 * aw, 128 * r + 64);
          bulk_commit();
          bulk_wait_all();
          TSTAMP(aw == 0, 21);
          asm volatile("mbarrier.arrive.shared::cluster.b64 _, [%0];\nmbarrier.arrive.shared::cluster.b64 _, [%1];"
                       :: "r"(mapa(bar(B_OFREE + aw), 0)), "r"(mapa(bar(B_OFREE + aw), 1)) : "memory");
          asm volatile("fence.release.gpu;\nst.relaxed.gpu.global.u32 [%0], %1;" :: "l"(&g_oflag[r * 32 + 2 * j + aw]), "r"(epoch + 1) : "memory");
          TSTAMP(aw == 0, 22); TSTAMP(aw == 1, 23);
        }
        __syncwarp();
      } else {
        const unsigned* fp = &g_oflag[r * 32 + (kcol(18 + min(lane, 13)) >> 6)];
        bool done = lane > 13;
        mbar_wait_long(bar(B_OW), 0);
        for (int i = 0; !__all_sync(0xffffffffu, done) && i < kSpinLimit; i++) {
          const bool now = !done && (int)(ld_relaxed(fp) - epoch) > 0;
          if (__any_sync(0xffffffffu, now)) {
            asm volatile("fence.acquire.gpu;\nfence.proxy.async.global;" ::: "memory");
            mbar_arrive_if(bar(B_RDY + lane), now);
            TSTAMP(lane == 0 && now, 24);
          }
          done |= now;
        }
        TSTAMP(lane == 0, 25);
      }
      const int trow = 1024 * rho + 512 * ((lane >> 1) & 1) + 8 * (lane >> 2);
      auto urow = [&](int u) INL { return ((u >> 2) & 3) * 128 + (u >> 4) * 4 + (u & 3); };
      mbar_wait(bar(B_Q), 0);
      mbar_wait_long(bar(B_Y), 0);
      const uint32_t ya = sb + RB + (((lane & 1) == rho ? Y_OWN : Y_IN + 64) ^ ((lane >> 1) * 16));
      uint8_t* gp = P.out + (size_t)trow * 4096 + 2048 + 32 * cl + 16 * (lane & 1);
#pragma unroll 1
      for (int u = aw; u < ((EXP & 64) ? 0 : 32); u += 3) {
        const uint32_t t0 = clock32();
        uint32_t qv[2][4], yv[2][4];
#pragma unroll
        for (int h = 0; h < 2; h++) {
          lds128(qv[h], sb + RA + u * 1024 + h * 512 + lane * 16);
          lds128(yv[h], ya + (u >> 4) * (RU - RB) + (u & 15) * 512 + h * 256);
        }
#pragma unroll
        for (int h = 0; h < 2; h++) {
#pragma unroll
          for (int m = 0; m < 4; m++) qv[h][m] = bmul2(qv[h][m], yv[h][m]);
          if (POSTTMA) sts128(sb + RA + u * 1024 + h * 512 + lane * 16, qv[h][0], qv[h][1], qv[h][2], qv[h][3]);
          else asm volatile("st.global.v4.b32 [%0], {%1,%2,%3,%4};" :: "l"(gp + (size_t)(urow(u) + 64 * h) * 4096),
                            "r"(qv[h][0]), "r"(qv[h][1]), "r"(qv[h][2]), "r"(qv[h][3]) : "memory");
        }
        if (POSTTMA) {
          fence_async_smem();
          __syncwarp();
          if (elect()) tma5d_store(&P.outb, sb + RA + u * 1024, 1024 + 16 * cl, 2 * rho, (u >> 4) * 4 + (u & 3), (u >> 2) & 3);
        }
        if (POSTGAP) pace(t0, POSTGAP);
      }
      if (POSTTMA) bulk_wait_read();
      TSTAMP(at == 0, 27);
    }
    __syncwarp();
    cluster_sync();
    if (tid == 256) g_epoch[cta] = ld_relaxed(&g_epoch[cta]) + 1;
  }
  TSTAMP(tid == 0, 61); GSTAMP(tid == 0, 63);
}

typedef CUresult (*EncodeFn)(CUtensorMap*, CUtensorMapDataType, cuuint32_t, void*, const cuuint64_t*, const cuuint64_t*,
                             const cuuint32_t*, const cuuint32_t*, CUtensorMapInterleave, CUtensorMapSwizzle,
                             CUtensorMapL2promotion, CUtensorMapFloatOOBfill);

void encode(EncodeFn fn, CUtensorMap* m, const void* p, int rank, const cuuint64_t* dims, const cuuint64_t* strides,
            const cuuint32_t* box, CUtensorMapSwizzle sw, int prom = 0) {
  const cuuint32_t es[5] = {1, 1, 1, 1, 1};
  fn(m, CU_TENSOR_MAP_DATA_TYPE_BFLOAT16, rank, const_cast<void*>(p), dims, strides, box, es, CU_TENSOR_MAP_INTERLEAVE_NONE, sw,
     (CUtensorMapL2promotion)prom, CU_TENSOR_MAP_FLOAT_OOB_FILL_NONE);
}
void encode2d(EncodeFn fn, CUtensorMap* m, const void* p, uint64_t cols, uint64_t rows, uint32_t bc, uint32_t br, CUtensorMapSwizzle sw, int prom = 0) {
  const cuuint64_t dims[2] = {cols, rows}, strides[1] = {cols * 2};
  const cuuint32_t box[2] = {bc, br};
  encode(fn, m, p, 2, dims, strides, box, sw, prom);
}
void encode3d(EncodeFn fn, CUtensorMap* m, const void* p) {
  const cuuint64_t dims[3] = {1024, 64, 32}, strides[2] = {2048 * 32, 2048};
  const cuuint32_t box[3] = {16, 32, 4};
  encode(fn, m, p, 3, dims, strides, box, CU_TENSOR_MAP_SWIZZLE_NONE, PROMK);
}
void encode4d(EncodeFn fn, CUtensorMap* m, const void* p, uint64_t cols, uint32_t rows, uint32_t nmat) {
  const cuuint64_t dims[4] = {64, 1024, 16, cols / 1024}, strides[3] = {cols * 2, 128, 2048};
  const cuuint32_t box[4] = {64, rows, 2, nmat};
  encode(fn, m, p, 4, dims, strides, box, CU_TENSOR_MAP_SWIZZLE_128B);
}
void encode5d(EncodeFn fn, CUtensorMap* m, const void* p, uint64_t cols, uint32_t n) {
  const cuuint64_t dims[5] = {cols, 4, 16, 8, 4}, strides[4] = {cols * 2 * 512, cols * 2 * 8, cols * 2, cols * 2 * 128};
  const cuuint32_t box[5] = {16, 2, 16, n, 1};
  encode(fn, m, p, 5, dims, strides, box, CU_TENSOR_MAP_SWIZZLE_NONE);
}

}

extern "C" void kernel_launch(void* const* d_in, const int* in_sizes, int n_in, void* d_out, int out_size) {
  static EncodeFn fn = nullptr;
  static void* o_ptr = nullptr;
  if (!fn) {
    cudaDriverEntryPointQueryResult qr;
    cudaGetDriverEntryPoint("cuTensorMapEncodeTiled", (void**)&fn, cudaEnableDefault, &qr);
    cudaGetSymbolAddress(&o_ptr, g_o);
    cudaFuncSetAttribute(fused_kernel, cudaFuncAttributeMaxDynamicSharedMemorySize, SM_TOTAL);
  }
  Params P;
  encode4d(fn, &P.w1, d_in[1], 3072, 32, 2);
  encode2d(fn, &P.x, d_in[0], 1024, 2048, 64, 64, CU_TENSOR_MAP_SWIZZLE_128B);
  encode4d(fn, &P.w2, d_in[1], 3072, 64, 1);
  encode4d(fn, &P.wo, d_in[2], 1024, 64, 1);
  encode2d(fn, &P.o, o_ptr, 1024, 2048, 64, 64, CU_TENSOR_MAP_SWIZZLE_128B);
  encode2d(fn, &P.outa, d_out, 2048, 2048, 64, 64, CU_TENSOR_MAP_SWIZZLE_128B);
  encode3d(fn, &P.k, d_in[4]);
  encode3d(fn, &P.v, d_in[5]);
  encode5d(fn, &P.q, d_in[3], 1024, 4);
  encode5d(fn, &P.outb, d_out, 2048, 1);
  P.shift_k = (const __nv_bfloat16*)d_in[6];
  P.ssm_k = (const __nv_bfloat16*)d_in[7];
  P.ssm_d = (const __nv_bfloat16*)d_in[8];
  P.q_ptr = (const __nv_bfloat16*)d_in[3];
  P.x_ptr = (const __nv_bfloat16*)d_in[0];
  P.k_ptr = (const __nv_bfloat16*)d_in[4];
  P.v_ptr = (const __nv_bfloat16*)d_in[5];
  P.w_ptr = (const __nv_bfloat16*)d_in[1];
  P.wo_ptr = (const __nv_bfloat16*)d_in[2];
  P.out = (uint8_t*)d_out;
  fused_kernel<<<kCtas, kThreads, SM_TOTAL>>>(P);
}
```

```cpp
#include <cuda.h>
#include <cuda_runtime.h>
#include <cuda_bf16.h>
#include <stdint.h>

#define DEVI __device__ __forceinline__
#define INL __attribute__((always_inline))

namespace {

DEVI void mma_kt_init(float* d, uint64_t da, uint64_t db) {
  asm volatile("{\nwgmma.mma_async.sync.aligned.m64n128k16.f32.bf16.bf16 {%0, %1, %2, %3, %4, %5, %6, %7, %8, %9, %10, %11, %12, %13, %14, %15, %16, %17, %18, %19, %20, %21, %22, %23, %24, %25, %26, %27, %28, %29, %30, %31, %32, %33, %34, %35, %36, %37, %38, %39, %40, %41, %42, %43, %44, %45, %46, %47, %48, %49, %50, %51, %52, %53, %54, %55, %56, %57, %58, %59, %60, %61, %62, %63}, %64, %65, 0, 1, 1, 1, 0;\n}\n"
    : "=f"(d[0]), "=f"(d[1]), "=f"(d[2]), "=f"(d[3]), "=f"(d[4]), "=f"(d[5]), "=f"(d[6]), "=f"(d[7]), "=f"(d[8]), "=f"(d[9]), "=f"(d[10]), "=f"(d[11]), "=f"(d[12]), "=f"(d[13]), "=f"(d[14]), "=f"(d[15]), "=f"(d[16]), "=f"(d[17]), "=f"(d[18]), "=f"(d[19]), "=f"(d[20]), "=f"(d[21]), "=f"(d[22]), "=f"(d[23]), "=f"(d[24]), "=f"(d[25]), "=f"(d[26]), "=f"(d[27]), "=f"(d[28]), "=f"(d[29]), "=f"(d[30]), "=f"(d[31]), "=f"(d[32]), "=f"(d[33]), "=f"(d[34]), "=f"(d[35]), "=f"(d[36]), "=f"(d[37]), "=f"(d[38]), "=f"(d[39]), "=f"(d[40]), "=f"(d[41]), "=f"(d[42]), "=f"(d[43]), "=f"(d[44]), "=f"(d[45]), "=f"(d[46]), "=f"(d[47]), "=f"(d[48]), "=f"(d[49]), "=f"(d[50]), "=f"(d[51]), "=f"(d[52]), "=f"(d[53]), "=f"(d[54]), "=f"(d[55]), "=f"(d[56]), "=f"(d[57]), "=f"(d[58]), "=f"(d[59]), "=f"(d[60]), "=f"(d[61]), "=f"(d[62]), "=f"(d[63])
    : "l"(da), "l"(db));
}
DEVI void mma_kt(float* d, uint64_t da, uint64_t db) {
  asm volatile("{\nwgmma.mma_async.sync.aligned.m64n128k16.f32.bf16.bf16 {%0, %1, %2, %3, %4, %5, %6, %7, %8, %9, %10, %11, %12, %13, %14, %15, %16, %17, %18, %19, %20, %21, %22, %23, %24, %25, %26, %27, %28, %29, %30, %31, %32, %33, %34, %35, %36, %37, %38, %39, %40, %41, %42, %43, %44, %45, %46, %47, %48, %49, %50, %51, %52, %53, %54, %55, %56, %57, %58, %59, %60, %61, %62, %63}, %64, %65, 1, 1, 1, 1, 0;\n}\n"
    : "+f"(d[0]), "+f"(d[1]), "+f"(d[2]), "+f"(d[3]), "+f"(d[4]), "+f"(d[5]), "+f"(d[6]), "+f"(d[7]), "+f"(d[8]), "+f"(d[9]), "+f"(d[10]), "+f"(d[11]), "+f"(d[12]), "+f"(d[13]), "+f"(d[14]), "+f"(d[15]), "+f"(d[16]), "+f"(d[17]), "+f"(d[18]), "+f"(d[19]), "+f"(d[20]), "+f"(d[21]), "+f"(d[22]), "+f"(d[23]), "+f"(d[24]), "+f"(d[25]), "+f"(d[26]), "+f"(d[27]), "+f"(d[28]), "+f"(d[29]), "+f"(d[30]), "+f"(d[31]), "+f"(d[32]), "+f"(d[33]), "+f"(d[34]), "+f"(d[35]), "+f"(d[36]), "+f"(d[37]), "+f"(d[38]), "+f"(d[39]), "+f"(d[40]), "+f"(d[41]), "+f"(d[42]), "+f"(d[43]), "+f"(d[44]), "+f"(d[45]), "+f"(d[46]), "+f"(d[47]), "+f"(d[48]), "+f"(d[49]), "+f"(d[50]), "+f"(d[51]), "+f"(d[52]), "+f"(d[53]), "+f"(d[54]), "+f"(d[55]), "+f"(d[56]), "+f"(d[57]), "+f"(d[58]), "+f"(d[59]), "+f"(d[60]), "+f"(d[61]), "+f"(d[62]), "+f"(d[63])
    : "l"(da), "l"(db));
}
DEVI void mma_n128_init(float* d, uint64_t da, uint64_t db) {
  asm volatile("{\nwgmma.mma_async.sync.aligned.m64n128k16.f32.bf16.bf16 {%0, %1, %2, %3, %4, %5, %6, %7, %8, %9, %10, %11, %12, %13, %14, %15, %16, %17, %18, %19, %20, %21, %22, %23, %24, %25, %26, %27, %28, %29, %30, %31, %32, %33, %34, %35, %36, %37, %38, %39, %40, %41, %42, %43, %44, %45, %46, %47, %48, %49, %50, %51, %52, %53, %54, %55, %56, %57, %58, %59, %60, %61, %62, %63}, %64, %65, 0, 1, 1, 0, 1;\n}\n"
    : "=f"(d[0]), "=f"(d[1]), "=f"(d[2]), "=f"(d[3]), "=f"(d[4]), "=f"(d[5]), "=f"(d[6]), "=f"(d[7]), "=f"(d[8]), "=f"(d[9]), "=f"(d[10]), "=f"(d[11]), "=f"(d[12]), "=f"(d[13]), "=f"(d[14]), "=f"(d[15]), "=f"(d[16]), "=f"(d[17]), "=f"(d[18]), "=f"(d[19]), "=f"(d[20]), "=f"(d[21]), "=f"(d[22]), "=f"(d[23]), "=f"(d[24]), "=f"(d[25]), "=f"(d[26]), "=f"(d[27]), "=f"(d[28]), "=f"(d[29]), "=f"(d[30]), "=f"(d[31]), "=f"(d[32]), "=f"(d[33]), "=f"(d[34]), "=f"(d[35]), "=f"(d[36]), "=f"(d[37]), "=f"(d[38]), "=f"(d[39]), "=f"(d[40]), "=f"(d[41]), "=f"(d[42]), "=f"(d[43]), "=f"(d[44]), "=f"(d[45]), "=f"(d[46]), "=f"(d[47]), "=f"(d[48]), "=f"(d[49]), "=f"(d[50]), "=f"(d[51]), "=f"(d[52]), "=f"(d[53]), "=f"(d[54]), "=f"(d[55]), "=f"(d[56]), "=f"(d[57]), "=f"(d[58]), "=f"(d[59]), "=f"(d[60]), "=f"(d[61]), "=f"(d[62]), "=f"(d[63])
    : "l"(da), "l"(db));
}
DEVI void mma_n128(float* d, uint64_t da, uint64_t db) {
  asm volatile("{\nwgmma.mma_async.sync.aligned.m64n128k16.f32.bf16.bf16 {%0, %1, %2, %3, %4, %5, %6, %7, %8, %9, %10, %11, %12, %13, %14, %15, %16, %17, %18, %19, %20, %21, %22, %23, %24, %25, %26, %27, %28, %29, %30, %31, %32, %33, %34, %35, %36, %37, %38, %39, %40, %41, %42, %43, %44, %45, %46, %47, %48, %49, %50, %51, %52, %53, %54, %55, %56, %57, %58, %59, %60, %61, %62, %63}, %64, %65, 1, 1, 1, 0, 1;\n}\n"
    : "+f"(d[0]), "+f"(d[1]), "+f"(d[2]), "+f"(d[3]), "+f"(d[4]), "+f"(d[5]), "+f"(d[6]), "+f"(d[7]), "+f"(d[8]), "+f"(d[9]), "+f"(d[10]), "+f"(d[11]), "+f"(d[12]), "+f"(d[13]), "+f"(d[14]), "+f"(d[15]), "+f"(d[16]), "+f"(d[17]), "+f"(d[18]), "+f"(d[19]), "+f"(d[20]), "+f"(d[21]), "+f"(d[22]), "+f"(d[23]), "+f"(d[24]), "+f"(d[25]), "+f"(d[26]), "+f"(d[27]), "+f"(d[28]), "+f"(d[29]), "+f"(d[30]), "+f"(d[31]), "+f"(d[32]), "+f"(d[33]), "+f"(d[34]), "+f"(d[35]), "+f"(d[36]), "+f"(d[37]), "+f"(d[38]), "+f"(d[39]), "+f"(d[40]), "+f"(d[41]), "+f"(d[42]), "+f"(d[43]), "+f"(d[44]), "+f"(d[45]), "+f"(d[46]), "+f"(d[47]), "+f"(d[48]), "+f"(d[49]), "+f"(d[50]), "+f"(d[51]), "+f"(d[52]), "+f"(d[53]), "+f"(d[54]), "+f"(d[55]), "+f"(d[56]), "+f"(d[57]), "+f"(d[58]), "+f"(d[59]), "+f"(d[60]), "+f"(d[61]), "+f"(d[62]), "+f"(d[63])
    : "l"(da), "l"(db));
}
DEVI void mma_kv_init(float* d, const uint32_t* a, uint64_t db) {
  asm volatile("{\nwgmma.mma_async.sync.aligned.m64n72k16.f32.bf16.bf16 {%0, %1, %2, %3, %4, %5, %6, %7, %8, %9, %10, %11, %12, %13, %14, %15, %16, %17, %18, %19, %20, %21, %22, %23, %24, %25, %26, %27, %28, %29, %30, %31, %32, %33, %34, %35}, {%36,%37,%38,%39}, %40, 0, 1, 1, 1;\n}\n"
    : "=f"(d[0]), "=f"(d[1]), "=f"(d[2]), "=f"(d[3]), "=f"(d[4]), "=f"(d[5]), "=f"(d[6]), "=f"(d[7]), "=f"(d[8]), "=f"(d[9]), "=f"(d[10]), "=f"(d[11]), "=f"(d[12]), "=f"(d[13]), "=f"(d[14]), "=f"(d[15]), "=f"(d[16]), "=f"(d[17]), "=f"(d[18]), "=f"(d[19]), "=f"(d[20]), "=f"(d[21]), "=f"(d[22]), "=f"(d[23]), "=f"(d[24]), "=f"(d[25]), "=f"(d[26]), "=f"(d[27]), "=f"(d[28]), "=f"(d[29]), "=f"(d[30]), "=f"(d[31]), "=f"(d[32]), "=f"(d[33]), "=f"(d[34]), "=f"(d[35])
    : "r"(a[0]), "r"(a[1]), "r"(a[2]), "r"(a[3]), "l"(db));
}
DEVI void mma_kv(float* d, const uint32_t* a, uint64_t db) {
  asm volatile("{\nwgmma.mma_async.sync.aligned.m64n72k16.f32.bf16.bf16 {%0, %1, %2, %3, %4, %5, %6, %7, %8, %9, %10, %11, %12, %13, %14, %15, %16, %17, %18, %19, %20, %21, %22, %23, %24, %25, %26, %27, %28, %29, %30, %31, %32, %33, %34, %35}, {%36,%37,%38,%39}, %40, 1, 1, 1, 1;\n}\n"
    : "+f"(d[0]), "+f"(d[1]), "+f"(d[2]), "+f"(d[3]), "+f"(d[4]), "+f"(d[5]), "+f"(d[6]), "+f"(d[7]), "+f"(d[8]), "+f"(d[9]), "+f"(d[10]), "+f"(d[11]), "+f"(d[12]), "+f"(d[13]), "+f"(d[14]), "+f"(d[15]), "+f"(d[16]), "+f"(d[17]), "+f"(d[18]), "+f"(d[19]), "+f"(d[20]), "+f"(d[21]), "+f"(d[22]), "+f"(d[23]), "+f"(d[24]), "+f"(d[25]), "+f"(d[26]), "+f"(d[27]), "+f"(d[28]), "+f"(d[29]), "+f"(d[30]), "+f"(d[31]), "+f"(d[32]), "+f"(d[33]), "+f"(d[34]), "+f"(d[35])
    : "r"(a[0]), "r"(a[1]), "r"(a[2]), "r"(a[3]), "l"(db));
}
DEVI void mma_o_init(float* d, const uint32_t* a, uint64_t db) {
  asm volatile("{\nwgmma.mma_async.sync.aligned.m64n40k16.f32.bf16.bf16 {%0, %1, %2, %3, %4, %5, %6, %7, %8, %9, %10, %11, %12, %13, %14, %15, %16, %17, %18, %19}, {%20,%21,%22,%23}, %24, 0, 1, 1, 1;\n}\n"
    : "=f"(d[0]), "=f"(d[1]), "=f"(d[2]), "=f"(d[3]), "=f"(d[4]), "=f"(d[5]), "=f"(d[6]), "=f"(d[7]), "=f"(d[8]), "=f"(d[9]), "=f"(d[10]), "=f"(d[11]), "=f"(d[12]), "=f"(d[13]), "=f"(d[14]), "=f"(d[15]), "=f"(d[16]), "=f"(d[17]), "=f"(d[18]), "=f"(d[19])
    : "r"(a[0]), "r"(a[1]), "r"(a[2]), "r"(a[3]), "l"(db));
}
DEVI void mma_o(float* d, const uint32_t* a, uint64_t db) {
  asm volatile("{\nwgmma.mma_async.sync.aligned.m64n40k16.f32.bf16.bf16 {%0, %1, %2, %3, %4, %5, %6, %7, %8, %9, %10, %11, %12, %13, %14, %15, %16, %17, %18, %19}, {%20,%21,%22,%23}, %24, 1, 1, 1, 1;\n}\n"
    : "+f"(d[0]), "+f"(d[1]), "+f"(d[2]), "+f"(d[3]), "+f"(d[4]), "+f"(d[5]), "+f"(d[6]), "+f"(d[7]), "+f"(d[8]), "+f"(d[9]), "+f"(d[10]), "+f"(d[11]), "+f"(d[12]), "+f"(d[13]), "+f"(d[14]), "+f"(d[15]), "+f"(d[16]), "+f"(d[17]), "+f"(d[18]), "+f"(d[19])
    : "r"(a[0]), "r"(a[1]), "r"(a[2]), "r"(a[3]), "l"(db));
}
DEVI void mma_s1_init(uint32_t* d, const uint32_t* a, uint64_t db) {
  asm volatile("{\nwgmma.mma_async.sync.aligned.m64n128k16.f16.f16.f16 {%0, %1, %2, %3, %4, %5, %6, %7, %8, %9, %10, %11, %12, %13, %14, %15, %16, %17, %18, %19, %20, %21, %22, %23, %24, %25, %26, %27, %28, %29, %30, %31}, {%32,%33,%34,%35}, %36, 0, 1, 1, 1;\n}\n"
    : "=r"(d[0]), "=r"(d[1]), "=r"(d[2]), "=r"(d[3]), "=r"(d[4]), "=r"(d[5]), "=r"(d[6]), "=r"(d[7]), "=r"(d[8]), "=r"(d[9]), "=r"(d[10]), "=r"(d[11]), "=r"(d[12]), "=r"(d[13]), "=r"(d[14]), "=r"(d[15]), "=r"(d[16]), "=r"(d[17]), "=r"(d[18]), "=r"(d[19]), "=r"(d[20]), "=r"(d[21]), "=r"(d[22]), "=r"(d[23]), "=r"(d[24]), "=r"(d[25]), "=r"(d[26]), "=r"(d[27]), "=r"(d[28]), "=r"(d[29]), "=r"(d[30]), "=r"(d[31])
    : "r"(a[0]), "r"(a[1]), "r"(a[2]), "r"(a[3]), "l"(db));
}
DEVI void mma_s1(uint32_t* d, const uint32_t* a, uint64_t db) {
  asm volatile("{\nwgmma.mma_async.sync.aligned.m64n128k16.f16.f16.f16 {%0, %1, %2, %3, %4, %5, %6, %7, %8, %9, %10, %11, %12, %13, %14, %15, %16, %17, %18, %19, %20, %21, %22, %23, %24, %25, %26, %27, %28, %29, %30, %31}, {%32,%33,%34,%35}, %36, 1, 1, 1, 1;\n}\n"
    : "+r"(d[0]), "+r"(d[1]), "+r"(d[2]), "+r"(d[3]), "+r"(d[4]), "+r"(d[5]), "+r"(d[6]), "+r"(d[7]), "+r"(d[8]), "+r"(d[9]), "+r"(d[10]), "+r"(d[11]), "+r"(d[12]), "+r"(d[13]), "+r"(d[14]), "+r"(d[15]), "+r"(d[16]), "+r"(d[17]), "+r"(d[18]), "+r"(d[19]), "+r"(d[20]), "+r"(d[21]), "+r"(d[22]), "+r"(d[23]), "+r"(d[24]), "+r"(d[25]), "+r"(d[26]), "+r"(d[27]), "+r"(d[28]), "+r"(d[29]), "+r"(d[30]), "+r"(d[31])
    : "r"(a[0]), "r"(a[1]), "r"(a[2]), "r"(a[3]), "l"(db));
}
DEVI void mma_s2_init(uint32_t* d, const uint32_t* a, uint64_t db) {
  asm volatile("{\nwgmma.mma_async.sync.aligned.m64n32k16.f16.f16.f16 {%0, %1, %2, %3, %4, %5, %6, %7}, {%8,%9,%10,%11}, %12, 0, 1, 1, 0;\n}\n"
    : "=r"(d[0]), "=r"(d[1]), "=r"(d[2]), "=r"(d[3]), "=r"(d[4]), "=r"(d[5]), "=r"(d[6]), "=r"(d[7])
    : "r"(a[0]), "r"(a[1]), "r"(a[2]), "r"(a[3]), "l"(db));
}
DEVI void mma_s2(uint32_t* d, const uint32_t* a, uint64_t db) {
  asm volatile("{\nwgmma.mma_async.sync.aligned.m64n32k16.f16.f16.f16 {%0, %1, %2, %3, %4, %5, %6, %7}, {%8,%9,%10,%11}, %12, 1, 1, 1, 0;\n}\n"
    : "+r"(d[0]), "+r"(d[1]), "+r"(d[2]), "+r"(d[3]), "+r"(d[4]), "+r"(d[5]), "+r"(d[6]), "+r"(d[7])
    : "r"(a[0]), "r"(a[1]), "r"(a[2]), "r"(a[3]), "l"(db));
}
DEVI void mma_s2_neg(uint32_t* d, const uint32_t* a, uint64_t db) {
  asm volatile("{\nwgmma.mma_async.sync.aligned.m64n32k16.f16.f16.f16 {%0, %1, %2, %3, %4, %5, %6, %7}, {%8,%9,%10,%11}, %12, 1, -1, 1, 0;\n}\n"
    : "+r"(d[0]), "+r"(d[1]), "+r"(d[2]), "+r"(d[3]), "+r"(d[4]), "+r"(d[5]), "+r"(d[6]), "+r"(d[7])
    : "r"(a[0]), "r"(a[1]), "r"(a[2]), "r"(a[3]), "l"(db));
}
DEVI void mma_i2_init(float* d, const uint32_t* a, uint64_t db, uint32_t meta) {
  asm volatile("{\nwgmma.mma_async.sp.sync.aligned.m64n128k32.f32.f16.f16 {%0, %1, %2, %3, %4, %5, %6, %7, %8, %9, %10, %11, %12, %13, %14, %15, %16, %17, %18, %19, %20, %21, %22, %23, %24, %25, %26, %27, %28, %29, %30, %31, %32, %33, %34, %35, %36, %37, %38, %39, %40, %41, %42, %43, %44, %45, %46, %47, %48, %49, %50, %51, %52, %53, %54, %55, %56, %57, %58, %59, %60, %61, %62, %63}, {%64,%65,%66,%67}, %68, %69, 0, 0, 1, 1, 1;\n}\n"
    : "=f"(d[0]), "=f"(d[1]), "=f"(d[2]), "=f"(d[3]), "=f"(d[4]), "=f"(d[5]), "=f"(d[6]), "=f"(d[7]), "=f"(d[8]), "=f"(d[9]), "=f"(d[10]), "=f"(d[11]), "=f"(d[12]), "=f"(d[13]), "=f"(d[14]), "=f"(d[15]), "=f"(d[16]), "=f"(d[17]), "=f"(d[18]), "=f"(d[19]), "=f"(d[20]), "=f"(d[21]), "=f"(d[22]), "=f"(d[23]), "=f"(d[24]), "=f"(d[25]), "=f"(d[26]), "=f"(d[27]), "=f"(d[28]), "=f"(d[29]), "=f"(d[30]), "=f"(d[31]), "=f"(d[32]), "=f"(d[33]), "=f"(d[34]), "=f"(d[35]), "=f"(d[36]), "=f"(d[37]), "=f"(d[38]), "=f"(d[39]), "=f"(d[40]), "=f"(d[41]), "=f"(d[42]), "=f"(d[43]), "=f"(d[44]), "=f"(d[45]), "=f"(d[46]), "=f"(d[47]), "=f"(d[48]), "=f"(d[49]), "=f"(d[50]), "=f"(d[51]), "=f"(d[52]), "=f"(d[53]), "=f"(d[54]), "=f"(d[55]), "=f"(d[56]), "=f"(d[57]), "=f"(d[58]), "=f"(d[59]), "=f"(d[60]), "=f"(d[61]), "=f"(d[62]), "=f"(d[63])
    : "r"(a[0]), "r"(a[1]), "r"(a[2]), "r"(a[3]), "l"(db), "r"(meta));
}
DEVI void mma_i2(float* d, const uint32_t* a, uint64_t db, uint32_t meta) {
  asm volatile("{\nwgmma.mma_async.sp.sync.aligned.m64n128k32.f32.f16.f16 {%0, %1, %2, %3, %4, %5, %6, %7, %8, %9, %10, %11, %12, %13, %14, %15, %16, %17, %18, %19, %20, %21, %22, %23, %24, %25, %26, %27, %28, %29, %30, %31, %32, %33, %34, %35, %36, %37, %38, %39, %40, %41, %42, %43, %44, %45, %46, %47, %48, %49, %50, %51, %52, %53, %54, %55, %56, %57, %58, %59, %60, %61, %62, %63}, {%64,%65,%66,%67}, %68, %69, 0, 1, 1, 1, 1;\n}\n"
    : "+f"(d[0]), "+f"(d[1]), "+f"(d[2]), "+f"(d[3]), "+f"(d[4]), "+f"(d[5]), "+f"(d[6]), "+f"(d[7]), "+f"(d[8]), "+f"(d[9]), "+f"(d[10]), "+f"(d[11]), "+f"(d[12]), "+f"(d[13]), "+f"(d[14]), "+f"(d[15]), "+f"(d[16]), "+f"(d[17]), "+f"(d[18]), "+f"(d[19]), "+f"(d[20]), "+f"(d[21]), "+f"(d[22]), "+f"(d[23]), "+f"(d[24]), "+f"(d[25]), "+f"(d[26]), "+f"(d[27]), "+f"(d[28]), "+f"(d[29]), "+f"(d[30]), "+f"(d[31]), "+f"(d[32]), "+f"(d[33]), "+f"(d[34]), "+f"(d[35]), "+f"(d[36]), "+f"(d[37]), "+f"(d[38]), "+f"(d[39]), "+f"(d[40]), "+f"(d[41]), "+f"(d[42]), "+f"(d[43]), "+f"(d[44]), "+f"(d[45]), "+f"(d[46]), "+f"(d[47]), "+f"(d[48]), "+f"(d[49]), "+f"(d[50]), "+f"(d[51]), "+f"(d[52]), "+f"(d[53]), "+f"(d[54]), "+f"(d[55]), "+f"(d[56]), "+f"(d[57]), "+f"(d[58]), "+f"(d[59]), "+f"(d[60]), "+f"(d[61]), "+f"(d[62]), "+f"(d[63])
    : "r"(a[0]), "r"(a[1]), "r"(a[2]), "r"(a[3]), "l"(db), "r"(meta));
}
__device__ const __align__(128) uint32_t d_tab[2944] = {
  0x3bf63c00,0x2e460000,0x391339a8,0x3a2f39a8,0x3ba83bd9,0x34a5323e,0x378b3872,0x3b0e3aa7,0x3b0e3b64,0x378b361f,0x34a5361f,0x3ba83b64,
  0x3a2f3aa7,0x39133872,0x2e46323e,0x3bf63bd9,0x3b0e3c00,0x378b0000,0xb4a5b9a8,0xbba8b9a8,0x2e463872,0x3bf63aa7,0x3913323e,0xba2fbbd9,
  0xba2fb61f,0x39133b64,0x3bf63b64,0x2e46b61f,0xbba8bbd9,0xb4a5323e,0x378b3aa7,0x3b0e3872,0x39133c00,0x3a2f0000,0xae4639a8,0x3bf639a8,
  0xbb0eb23e,0x378b3bd9,0xbba8baa7,0xb4a53872,0xb4a5bb64,0xbba8b61f,0x378bb61f,0xbb0ebb64,0x3bf63872,0xae46baa7,0x3a2f3bd9,0x3913b23e,
  0x34a53c00,0x3ba80000,0x378bb9a8,0xbb0eb9a8,0xba2fbaa7,0xb9133872,0x2e463bd9,0x3bf6323e,0x3bf6361f,0x2e46bb64,0xb913bb64,0xba2f361f,
  0xbb0e323e,0x378b3bd9,0x3ba83872,0x34a5baa7,0xae463c00,0x3bf60000,0xba2f39a8,0x391339a8,0x34a5bbd9,0xbba8b23e,0x3b0eb872,0xb78bbaa7,
  0xb78b3b64,0x3b0e361f,0xbba8361f,0x34a53b64,0x3913baa7,0xba2fb872,0x3bf6b23e,0xae46bbd9,0xb78b3c00,0x3b0e0000,0x3ba8b9a8,0xb4a5b9a8,
  0x3bf6b872,0xae46baa7,0xba2fb23e,0xb9133bd9,0xb913b61f,0xba2f3b64,0xae463b64,0x3bf6b61f,0xb4a53bd9,0x3ba8b23e,0x3b0ebaa7,0xb78bb872,
  0xba2f3c00,0x39130000,0xbbf639a8,0xae4639a8,0x378b323e,0x3b0ebbd9,0xb4a53aa7,0x3ba8b872,0x3ba8bb64,0xb4a5b61f,0x3b0eb61f,0x378bbb64,
  0xae46b872,0xbbf63aa7,0x3913bbd9,0xba2f323e,0xbba83c00,0x34a50000,0x3b0eb9a8,0x378bb9a8,0xb9133aa7,0x3a2fb872,0x3bf6bbd9,0xae46b23e,
  0xae46361f,0x3bf6bb64,0x3a2fbb64,0xb913361f,0x378bb23e,0x3b0ebbd9,0x34a5b872,0xbba83aa7,0xbbf63c00,0xae460000,0xb91339a8,0xba2f39a8,
  0xbba83bd9,0xb4a5323e,0xb78b3872,0xbb0e3aa7,0xbb0e3b64,0xb78b361f,0xb4a5361f,0xbba83b64,0xba2f3aa7,0xb9133872,0xae46323e,0xbbf63bd9,
  0xbb0e3c00,0xb78b0000,0x34a5b9a8,0x3ba8b9a8,0xae463872,0xbbf63aa7,0xb913323e,0x3a2fbbd9,0x3a2fb61f,0xb9133b64,0xbbf63b64,0xae46b61f,
  0x3ba8bbd9,0x34a5323e,0xb78b3aa7,0xbb0e3872,0xb9133c00,0xba2f0000,0x2e4639a8,0xbbf639a8,0x3b0eb23e,0xb78b3bd9,0x3ba8baa7,0x34a53872,
  0x34a5bb64,0x3ba8b61f,0xb78bb61f,0x3b0ebb64,0xbbf63872,0x2e46baa7,0xba2f3bd9,0xb913b23e,0xb4a53c00,0xbba80000,0xb78bb9a8,0x3b0eb9a8,
  0x3a2fbaa7,0x39133872,0xae463bd9,0xbbf6323e,0xbbf6361f,0xae46bb64,0x3913bb64,0x3a2f361f,0x3b0e323e,0xb78b3bd9,0xbba83872,0xb4a5baa7,
  0x2e463c00,0xbbf60000,0x3a2f39a8,0xb91339a8,0xb4a5bbd9,0x3ba8b23e,0xbb0eb872,0x378bbaa7,0x378b3b64,0xbb0e361f,0x3ba8361f,0xb4a53b64,
  0xb913baa7,0x3a2fb872,0xbbf6b23e,0x2e46bbd9,0x378b3c00,0xbb0e0000,0xbba8b9a8,0x34a5b9a8,0xbbf6b872,0x2e46baa7,0x3a2fb23e,0x39133bd9,
  0x3913b61f,0x3a2f3b64,0x2e463b64,0xbbf6b61f,0x34a53bd9,0xbba8b23e,0xbb0ebaa7,0x378bb872,0x3a2f3c00,0xb9130000,0x3bf639a8,0x2e4639a8,
  0xb78b323e,0xbb0ebbd9,0x34a53aa7,0xbba8b872,0xbba8bb64,0x34a5b61f,0xbb0eb61f,0xb78bbb64,0x2e46b872,0x3bf63aa7,0xb913bbd9,0x3a2f323e,
  0x3ba83c00,0xb4a50000,0xbb0eb9a8,0xb78bb9a8,0x39133aa7,0xba2fb872,0xbbf6bbd9,0x2e46b23e,0x2e46361f,0xbbf6bb64,0xba2fbb64,0x3913361f,
  0xb78bb23e,0xbb0ebbd9,0xb4a5b872,0x3ba83aa7,0x3bf63c00,0x2e460000,0x391339a8,0x3a2f39a8,0x3ba83bd9,0x34a5323e,0x378b3872,0x3b0e3aa7,
  0x3b0e3b64,0x378b361f,0x34a5361f,0x3ba83b64,0x3a2f3aa7,0x39133872,0x2e46323e,0x3bf63bd9,0x3b0e3c00,0x378b0000,0xb4a5b9a8,0xbba8b9a8,
  0x2e463872,0x3bf63aa7,0x3913323e,0xba2fbbd9,0xba2fb61f,0x39133b64,0x3bf63b64,0x2e46b61f,0xbba8bbd9,0xb4a5323e,0x378b3aa7,0x3b0e3872,
  0x39133c00,0x3a2f0000,0xae4639a8,0x3bf639a8,0xbb0eb23e,0x378b3bd9,0xbba8baa7,0xb4a53872,0xb4a5bb64,0xbba8b61f,0x378bb61f,0xbb0ebb64,
  0x3bf63872,0xae46baa7,0x3a2f3bd9,0x3913b23e,0x34a53c00,0x3ba80000,0x378bb9a8,0xbb0eb9a8,0xba2fbaa7,0xb9133872,0x2e463bd9,0x3bf6323e,
  0x3bf6361f,0x2e46bb64,0xb913bb64,0xba2f361f,0xbb0e323e,0x378b3bd9,0x3ba83872,0x34a5baa7,0xae463c00,0x3bf60000,0xba2f39a8,0x391339a8,
  0x34a5bbd9,0xbba8b23e,0x3b0eb872,0xb78bbaa7,0xb78b3b64,0x3b0e361f,0xbba8361f,0x34a53b64,0x3913baa7,0xba2fb872,0x3bf6b23e,0xae46bbd9,
  0xb78b3c00,0x3b0e0000,0x3ba8b9a8,0xb4a5b9a8,0x3bf6b872,0xae46baa7,0xba2fb23e,0xb9133bd9,0xb913b61f,0xba2f3b64,0xae463b64,0x3bf6b61f,
  0xb4a53bd9,0x3ba8b23e,0x3b0ebaa7,0xb78bb872,0xba2f3c00,0x39130000,0xbbf639a8,0xae4639a8,0x378b323e,0x3b0ebbd9,0xb4a53aa7,0x3ba8b872,
  0x3ba8bb64,0xb4a5b61f,0x3b0eb61f,0x378bbb64,0xae46b872,0xbbf63aa7,0x3913bbd9,0xba2f323e,0xbba83c00,0x34a50000,0x3b0eb9a8,0x378bb9a8,
  0xb9133aa7,0x3a2fb872,0x3bf6bbd9,0xae46b23e,0xae46361f,0x3bf6bb64,0x3a2fbb64,0xb913361f,0x378bb23e,0x3b0ebbd9,0x34a5b872,0xbba83aa7,
  0xbbf63c00,0xae460000,0xb91339a8,0xba2f39a8,0xbba83bd9,0xb4a5323e,0xb78b3872,0xbb0e3aa7,0xbb0e3b64,0xb78b361f,0xb4a5361f,0xbba83b64,
  0xba2f3aa7,0xb9133872,0xae46323e,0xbbf63bd9,0xbb0e3c00,0xb78b0000,0x34a5b9a8,0x3ba8b9a8,0xae463872,0xbbf63aa7,0xb913323e,0x3a2fbbd9,
  0x3a2fb61f,0xb9133b64,0xbbf63b64,0xae46b61f,0x3ba8bbd9,0x34a5323e,0xb78b3aa7,0xbb0e3872,0xb9133c00,0xba2f0000,0x2e4639a8,0xbbf639a8,
  0x3b0eb23e,0xb78b3bd9,0x3ba8baa7,0x34a53872,0x34a5bb64,0x3ba8b61f,0xb78bb61f,0x3b0ebb64,0xbbf63872,0x2e46baa7,0xba2f3bd9,0xb913b23e,
  0xb4a53c00,0xbba80000,0xb78bb9a8,0x3b0eb9a8,0x3a2fbaa7,0x39133872,0xae463bd9,0xbbf6323e,0xbbf6361f,0xae46bb64,0x3913bb64,0x3a2f361f,
  0x3b0e323e,0xb78b3bd9,0xbba83872,0xb4a5baa7,0x2e463c00,0xbbf60000,0x3a2f39a8,0xb91339a8,0xb4a5bbd9,0x3ba8b23e,0xbb0eb872,0x378bbaa7,
  0x378b3b64,0xbb0e361f,0x3ba8361f,0xb4a53b64,0xb913baa7,0x3a2fb872,0xbbf6b23e,0x2e46bbd9,0x378b3c00,0xbb0e0000,0xbba8b9a8,0x34a5b9a8,
  0xbbf6b872,0x2e46baa7,0x3a2fb23e,0x39133bd9,0x3913b61f,0x3a2f3b64,0x2e463b64,0xbbf6b61f,0x34a53bd9,0xbba8b23e,0xbb0ebaa7,0x378bb872,
  0x3a2f3c00,0xb9130000,0x3bf639a8,0x2e4639a8,0xb78b323e,0xbb0ebbd9,0x34a53aa7,0xbba8b872,0xbba8bb64,0x34a5b61f,0xbb0eb61f,0xb78bbb64,
  0x2e46b872,0x3bf63aa7,0xb913bbd9,0x3a2f323e,0x3ba83c00,0xb4a50000,0xbb0eb9a8,0xb78bb9a8,0x39133aa7,0xba2fb872,0xbbf6bbd9,0x2e46b23e,
  0x2e46361f,0xbbf6bb64,0xba2fbb64,0x3913361f,0xb78bb23e,0xbb0ebbd9,0xb4a5b872,0x3ba83aa7,0x3bea3bfe,0x30b22a48,0x38c4395f,0x3a6d39ed,
  0x3b883bc3,0x356433c6,0x36d7381d,0x3b3b3add,0x3add3b3b,0x381d36d7,0x33c63564,0x3bc33b88,0x39ed3a6d,0x395f38c4,0x2a4830b2,0x3bfe3bea,
  0x39ed3bc3,0x395f33c6,0xaa48b81d,0xbbfebadd,0xb0b23564,0x3bea3b88,0x3a6d36d7,0xb8c4bb3b,0xbb3bb8c4,0x36d73a6d,0x3b883bea,0x3564b0b2,
  0xbaddbbfe,0xb81daa48,0x33c6395f,0x3bc339ed,0x33c63b3b,0x3bc336d7,0xb81d3564,0x3add3b88,0xbbfeb8c4,0x2a483a6d,0xb9edbbea,0xb95f30b2,
  0x30b2b95f,0xbbeab9ed,0x3a6d2a48,0xb8c4bbfe,0x3b883add,0x3564b81d,0x36d73bc3,0x3b3b33c6,0xb5643a6d,0x3b8838c4,0x3b3bb0b2,0xb6d7bbea,
  0xb3c6bbfe,0xbbc3aa48,0xb81d395f,0x3add39ed,0x39ed3add,0x395fb81d,0xaa48bbc3,0xbbfeb3c6,0xbbeab6d7,0xb0b23b3b,0x38c43b88,0x3a6db564,
  0xba6d395f,0x38c439ed,0xbbeaaa48,0xb0b23bfe,0x3b3bb81d,0xb6d7badd,0x3b8833c6,0x3564bbc3,0xbbc33564,0x33c63b88,0xbaddb6d7,0xb81d3b3b,
  0x3bfeb0b2,0xaa48bbea,0x39ed38c4,0x395fba6d,0xbbfe381d,0x2a483add,0x39ed33c6,0x395fbbc3,0x38c436d7,0x3a6dbb3b,0x30b2bb88,0xbbea3564,
  0x3564bbea,0xbb8830b2,0xbb3b3a6d,0x36d738c4,0xbbc3395f,0x33c639ed,0x3add2a48,0x381dbbfe,0xbadd3564,0xb81d3b88,0xb3c6b6d7,0xbbc33b3b,
  0xb95f3bea,0x39edb0b2,0xbbfe3a6d,0x2a4838c4,0x38c42a48,0x3a6dbbfe,0xb0b239ed,0x3beab95f,0x3b3bbbc3,0xb6d7b3c6,0x3b88b81d,0x3564badd,
  0xb6d730b2,0xbb3b3bea,0xb56438c4,0x3b88ba6d,0xbadd395f,0xb81d39ed,0x33c62a48,0x3bc3bbfe,0xbbfe3bc3,0x2a4833c6,0x39edb81d,0x395fbadd,
  0xba6d3b88,0x38c4b564,0x3beabb3b,0x30b2b6d7,0x30b2aa48,0xbbea3bfe,0x3a6db9ed,0xb8c4395f,0x3564b3c6,0xbb883bc3,0x3b3bbadd,0xb6d7381d,
  0x381db6d7,0xbadd3b3b,0x3bc3bb88,0xb3c63564,0x395fb8c4,0xb9ed3a6d,0x3bfebbea,0xaa4830b2,0x395fb3c6,0xb9ed3bc3,0xbbfe3add,0x2a48b81d,
  0x3beabb88,0x30b23564,0xb8c43b3b,0xba6d36d7,0x36d7ba6d,0x3b3bb8c4,0x356430b2,0xbb883bea,0xb81d2a48,0x3addbbfe,0x3bc3b9ed,0xb3c6395f,
  0x3bc3b6d7,0xb3c63b3b,0x3addbb88,0x381d3564,0x2a48ba6d,0x3bfeb8c4,0xb95fb0b2,0x39edbbea,0xbbea39ed,0xb0b2b95f,0xb8c43bfe,0xba6d2a48,
  0x3564381d,0xbb883add,0x3b3bb3c6,0xb6d73bc3,0x3b88b8c4,0x35643a6d,0xb6d73bea,0xbb3bb0b2,0xbbc32a48,0x33c6bbfe,0x3addb9ed,0x381d395f,
  0x395f381d,0xb9ed3add,0xbbfe33c6,0x2a48bbc3,0xb0b2bb3b,0x3beab6d7,0x3a6d3564,0xb8c43b88,0x38c4b9ed,0x3a6d395f,0xb0b2bbfe,0x3beaaa48,
  0xb6d73add,0xbb3bb81d,0x35643bc3,0xbb8833c6,0x33c6bb88,0x3bc33564,0xb81dbb3b,0x3addb6d7,0xaa483bea,0xbbfeb0b2,0x395f3a6d,0xb9ed38c4,
  0x2a48badd,0x3bfe381d,0x395f3bc3,0xb9ed33c6,0x3a6d3b3b,0xb8c436d7,0xbbeab564,0xb0b2bb88,0xbb88b0b2,0xb564bbea,0x36d7b8c4,0x3b3b3a6d,
  0x33c6b9ed,0x3bc3395f,0x381d3bfe,0xbadd2a48,0xb81dbb88,0x3add3564,0xbbc3bb3b,0x33c6b6d7,0x39ed30b2,0x395f3bea,0x2a48b8c4,0x3bfe3a6d,
  0x3a6d3bfe,0xb8c42a48,0x3bea395f,0x30b239ed,0xb6d733c6,0xbb3bbbc3,0x35643add,0xbb88b81d,0xbb3bbbea,0x36d730b2,0x3b883a6d,0x356438c4,
  0xb81db9ed,0x3add395f,0x3bc33bfe,0xb3c62a48,0x2a48b3c6,0x3bfe3bc3,0x395f3add,0xb9edb81d,0x38c43564,0x3a6d3b88,0x30b236d7,0xbbeabb3b,
  0xbbeabbfe,0xb0b2aa48,0xb8c4b95f,0xba6db9ed,0xbb88bbc3,0xb564b3c6,0xb6d7b81d,0xbb3bbadd,0xbaddbb3b,0xb81db6d7,0xb3c6b564,0xbbc3bb88,
  0xb9edba6d,0xb95fb8c4,0xaa48b0b2,0xbbfebbea,0xb9edbbc3,0xb95fb3c6,0x2a48381d,0x3bfe3add,0x30b2b564,0xbbeabb88,0xba6db6d7,0x38c43b3b,
  0x3b3b38c4,0xb6d7ba6d,0xbb88bbea,0xb56430b2,0x3add3bfe,0x381d2a48,0xb3c6b95f,0xbbc3b9ed,0xb3c6bb3b,0xbbc3b6d7,0x381db564,0xbaddbb88,
  0x3bfe38c4,0xaa48ba6d,0x39ed3bea,0x395fb0b2,0xb0b2395f,0x3bea39ed,0xba6daa48,0x38c43bfe,0xbb88badd,0xb564381d,0xb6d7bbc3,0xbb3bb3c6,
  0x3564ba6d,0xbb88b8c4,0xbb3b30b2,0x36d73bea,0x33c63bfe,0x3bc32a48,0x381db95f,0xbaddb9ed,0xb9edbadd,0xb95f381d,0x2a483bc3,0x3bfe33c6,
  0x3bea36d7,0x30b2bb3b,0xb8c4bb88,0xba6d3564,0x3a6db95f,0xb8c4b9ed,0x3bea2a48,0x30b2bbfe,0xbb3b381d,0x36d73add,0xbb88b3c6,0xb5643bc3,
  0x3bc3b564,0xb3c6bb88,0x3add36d7,0x381dbb3b,0xbbfe30b2,0x2a483bea,0xb9edb8c4,0xb95f3a6d,0x3bfeb81d,0xaa48badd,0xb9edb3c6,0xb95f3bc3,
  0xb8c4b6d7,0xba6d3b3b,0xb0b23b88,0x3beab564,0xb5643bea,0x3b88b0b2,0x3b3bba6d,0xb6d7b8c4,0x3bc3b95f,0xb3c6b9ed,0xbaddaa48,0xb81d3bfe,
  0x3addb564,0x381dbb88,0x33c636d7,0x3bc3bb3b,0x395fbbea,0xb9ed30b2,0x3bfeba6d,0xaa48b8c4,0xb8c4aa48,0xba6d3bfe,0x30b2b9ed,0xbbea395f,
  0xbb3b3bc3,0x36d733c6,0xbb88381d,0xb5643add,0x36d7b0b2,0x3b3bbbea,0x3564b8c4,0xbb883a6d,0x3addb95f,0x381db9ed,0xb3c6aa48,0xbbc33bfe,
  0x3bfebbc3,0xaa48b3c6,0xb9ed381d,0xb95f3add,0x3a6dbb88,0xb8c43564,0xbbea3b3b,0xb0b236d7,0xb0b22a48,0x3beabbfe,0xba6d39ed,0x38c4b95f,
  0xb56433c6,0x3b88bbc3,0xbb3b3add,0x36d7b81d,0xb81d36d7,0x3addbb3b,0xbbc33b88,0x33c6b564,0xb95f38c4,0x39edba6d,0xbbfe3bea,0x2a48b0b2,
  0xb95f33c6,0x39edbbc3,0x3bfebadd,0xaa48381d,0xbbea3b88,0xb0b2b564,0x38c4bb3b,0x3a6db6d7,0xb6d73a6d,0xbb3b38c4,0xb564b0b2,0x3b88bbea,
  0x381daa48,0xbadd3bfe,0xbbc339ed,0x33c6b95f,0xbbc336d7,0x33c6bb3b,0xbadd3b88,0xb81db564,0xaa483a6d,0xbbfe38c4,0x395f30b2,0xb9ed3bea,
  0x3beab9ed,0x30b2395f,0x38c4bbfe,0x3a6daa48,0xb564b81d,0x3b88badd,0xbb3b33c6,0x36d7bbc3,0xbb8838c4,0xb564ba6d,0x36d7bbea,0x3b3b30b2,
  0x3bc3aa48,0xb3c63bfe,0xbadd39ed,0xb81db95f,0xb95fb81d,0x39edbadd,0x3bfeb3c6,0xaa483bc3,0x30b23b3b,0xbbea36d7,0xba6db564,0x38c4bb88,
  0xb8c439ed,0xba6db95f,0x30b23bfe,0xbbea2a48,0x36d7badd,0x3b3b381d,0xb564bbc3,0x3b88b3c6,0xb3c63b88,0xbbc3b564,0x381d3b3b,0xbadd36d7,
  0x2a48bbea,0x3bfe30b2,0xb95fba6d,0x39edb8c4,0xaa483add,0xbbfeb81d,0xb95fbbc3,0x39edb3c6,0xba6dbb3b,0x38c4b6d7,0x3bea3564,0x30b23b88,
  0x3b8830b2,0x35643bea,0xb6d738c4,0xbb3bba6d,0xb3c639ed,0xbbc3b95f,0xb81dbbfe,0x3addaa48,0x381d3b88,0xbaddb564,0x3bc33b3b,0xb3c636d7,
  0xb9edb0b2,0xb95fbbea,0xaa4838c4,0xbbfeba6d,0xba6dbbfe,0x38c4aa48,0xbbeab95f,0xb0b2b9ed,0x36d7b3c6,0x3b3b3bc3,0xb564badd,0x3b88381d,
  0x3b3b3bea,0xb6d7b0b2,0xbb88ba6d,0xb564b8c4,0x381d39ed,0xbaddb95f,0xbbc3bbfe,0x33c6aa48,0xaa4833c6,0xbbfebbc3,0xb95fbadd,0x39ed381d,
  0xb8c4b564,0xba6dbb88,0xb0b2b6d7,0x3bea3b3b,0x3c003c00,0x1a480000,0x3bff3bff,0x27112648,0x3c003c00,0x20b61e48,0x3bff3bff,0x285227da,
  0x3c003c00,0x23db2248,0x3bfe3bff,0x291b28b6,0x3c003c00,0x257f24b6,0x3bfe3bfe,0x29e3297f,0x3c003c00,0x23db0000,0x3bed3bf1,0x30672fd6,
  0x3bfe3bff,0x29e327da,0x3be33be8,0x316030e4,0x3bfa3bfc,0x2ce72bd9,0x3bd73bdd,0x325731db,0x3bf43bf7,0x2edc2de2,0x3bca3bd1,0x334c32d2,
  0x3bff3c00,0x27110000,0x3bc13bce,0x33df3303,0x3bf93bfd,0x2d4c2b11,0x3ba23bb2,0x34c9345d,0x3bed3bf4,0x30672f0e,0x3b7d3b91,0x359f3534,
  0x3bda3be4,0x32263147,0x3b533b69,0x36703608,0x3bfe3c00,0x291b0000,0x3b7d3b99,0x359f3505,0x3bf13bf9,0x2fa42d1a,0x3b3e3b5f,0x36cc3637,
  0x3bd73be6,0x32573115,0x3af33b1a,0x37ee375e,0x3bb13bc6,0x34693396,0x3a9c3ac9,0x3881383d,0x3bfd3c00,0x2aac0000,0x3b223b50,0x373d367c,
  0x3be73bf5,0x30fd2eaa,0x3ab83af0,0x385837f9,0x3bbb3bd4,0x342032a1,0x3a3b3a7c,0x390538b0,0x3b793b9d,0x35b634ed,0x39ad39f6,0x39a43956,
  0x3bfc3c00,0x2c1f0000,0x3ab13af6,0x386237e3,0x3bda3bef,0x3226301d,0x3a133a65,0x393538ce,0x3b973bbc,0x35113414,0x395b39ba,0x39f23996,
  0x3b333b69,0x36f93608,0x388c38f6,0x3a953a47,0x3bfa3c00,0x2ce70000,0x3a2b3a8a,0x3918389b,0x3bca3be8,0x334c30e4,0x395139c3,0x39fa398d,
  0x3b6b3ba0,0x35fd34d5,0x385838d8,0x3ab83a5e,0x3ae03b2b,0x3817371b,0x368737a1,0x3b4e3b08,0x3bf83c00,0x2db00000,0x39923a0f,0x39be393a,
  0x3bb73be0,0x343831aa,0x38773909,0x3aa33a37,0x3b393b80,0x36e33593,0x367037b7,0x3b533b02,0x3a7f3ae3,0x38ab3812,0x337d351d,0x3bc73b95,
  0x3bf63c00,0x2e780000,0x38e73984,0x3a5239cb,0x3ba23bd6,0x34c9326f,0x3710383d,0x3b2e3ac9,0x3aff3b5a,0x37c2364e,0x34083593,0x3bbe3b80,
  0x3a133a92,0x39353891,0x2aac30e4,0x3bfd3be8,0x3bf33c00,0x2f400000,0x382d38ec,0x3ad33a4f,0x3b8a3bcb,0x35583334,0x351136c1,0x3b973b41,
  0x3abf3b30,0x384d3705,0x2e1432a1,0x3bf73bd4,0x399b3a37,0x39b53909,0xb036a4b6,0x3bee3c00,0x3bf03c00,0x30040000,0x36cc3848,0x3b3e3ac2,
  0x3b703bc0,0x35e533f7,0x31f434ed,0x3bdc3b9d,0x3a783b02,0x38b537b7,0xac1f2bd9,0x3bfc3bfc,0x391839d4,0x3a2b397b,0xb4f9b20d,0x3b9b3bdb,
  0x3bed3c00,0x30670000,0x35293732,0x3b933b25,0x3b533bb2,0x3670345d,0x2aac320d,0x3bfd3bdb,0x3a2b3ad0,0x39183832,0xb31bad7e,0x3bcd3bf8,
  0x388c3969,0x3a9539e5,0xb7acb5ab,0x3b053b7b,0x3be93c00,0x30cb0000,0x32ea35c2,0x3bd03b77,0x3b333ba4,0x36f934bd,0xad4c2c51,0x3bf93bfb,
  0x39d83a99,0x39763887,0xb5fdb365,0x3b6b3bc9,0x37ee38f6,0x3af33a47,0xb90eb812,0x3a333ae3,0x3be53c00,0x312e0000,0x2edc3444,0x3bf43bb6,
  0x3b113b95,0x3780351d,0xb2eaab11,0x3bd03bfd,0x39803a5e,0x39d038d8,0xb822b5f1,0x3ad93b6e,0x36b5387c,0x3b433aa0,0xba1bb930,0x392b3a17,
  0x3be13c00,0x31910000,0x9a483179,0x3c003be2,0x3aed3b84,0x3802357c,0xb587b1aa,0x3b823be0,0x39223a1f,0x3a233927,0xb92bb807,0x3a1b3ae9,
  0x357037f9,0x3b863af0,0xbaf3ba27,0x37ee391d,0x3bdc3c00,0x31f40000,0xaf402cb5,0x3bf33bfa,0x3ac63b72,0x384235da,0xb780b4bd,0x3b113ba4,
  0x38bf39dc,0x3a713972,0xba13b900,0x39353a3f,0x342036ee,0x3bbb3b36,0xbb8fbaf0,0x354037f9,0x3bd73c00,0x32570000,0xb31ba648,0x3bcd3bff,
  0x3a9c3b5f,0x38813637,0xb8abb693,0x3a7f3b4b,0x38583996,0x3ab839ba,0xbad3b9dc,0x382d3972,0x319135da,0x3be13b72,0xbbe9bb84,0x30cb357c,
  0x3bd23c00,0x32b90000,0xb540afd6,0x3b8f3bf1,0x3a713b4b,0x38bf3693,0xb980b828,0x39d03ad6,0x37d8394d,0x3af939fe,0xbb67ba99,0x36143887,
  0x2db034bd,0x3bf83ba4,0xbbffbbe0,0xa85231aa,0x3bcd3c00,0x331b0000,0xb6e3b303,0x3b393bce,0x3a433b36,0x38fb36ee,0xba3bb8f6,0x39053a47,
  0x36f93900,0x3b333a3f,0xbbcabb30,0x334c3705,0x1a483334,0x3c003bcb,0xbbd0bc00,0xb2ea1e48,0x3bc73c00,0x337d0000,0xb838b505,0x3acc3b99,
  0x3a133b20,0x39353748,0xbad9b9b1,0x3822399f,0x361438b0,0x3b673a7c,0xbbfbbba0,0x2c8334d5,0xad4c30e4,0x3bf93be8,0xbb5dbbe4,0xb642b147,
  0x3bc13c00,0x33df0000,0xb8f1b67c,0x3a4b3b50,0x39e13b08,0x396d37a1,0xbb58ba56,0x365938e2,0x3529385d,0x3b933ab5,0xbbf8bbe6,0xadb03115,
  0xb1602d1a,0x3be33bf9,0xbaaabb8c,0xb86db54c,0x3bbb3c00,0x34200000,0xb99bb7e3,0x39b53af6,0x39ad3af0,0x39a437f9,0xbbb4bae3,0x34513812,
  0x34383807,0x3bb73ae9,0xbbc1bc00,0xb3df2248,0xb4081e48,0x3bbe3c00,0xb9bebafc,0xb992b7cd,0x3bb43c00,0x34510000,0xba33b89b,0x390e3a8a,
  0x39763ad6,0x39d83828,0xbbedbb55,0x30673665,0x3288375e,0x3bd53b1a,0xbb58bbed,0xb659b04e,0xb558ac51,0x3b8a3bfb,0xb8a0ba37,0xba87b909,
  0x3bad3c00,0x34810000,0xbab8b93a,0x38583a0f,0x393e3abc,0x3a0b3852,0xbc00bbab,0x1a48348d,0x309936aa,0x3beb3b46,0xbabfbbaf,0xb84db475,
  0xb69eb080,0x3b493bec,0xb6b5b943,0xbb43ba07,0x3ba63c00,0x34b10000,0xbb28b9cb,0x37263984,0x39053aa0,0x3a3b387c,0xbbeebbe4,0xb0363147,
  0x2d4c35f1,0x3bf93b6e,0xb9fabb46,0xb951b6aa,0xb7d8b2d2,0x3af93bd1,0xb3dfb828,0xbbc1bad6,0x3b9e3c00,0x34e10000,0xbb82ba4f,0x358738ec,
  0x38c93a83,0x3a6938a6,0xbbb7bbfe,0xb438297f,0x257f3534,0x3c003b91,0xb90ebab5,0xba33b85d,0xb881b48d,0x3a9c3bab,0xac1fb5da,0xbbfcbb72,
  0x3b973c00,0x35110000,0xbbc4bac2,0x33ae3848,0x388c3a65,0x3a9538ce,0xbb5dbbf9,0xb642ad1a,0xa91b3475,0x3bfe3baf,0xb802b9fe,0xbaedb94d,
  0xb90eb5ab,0x3a333b7b,0x2fa4b26f,0xbbf1bbd6,0x3b8f3c00,0x35400000,0xbbeebb25,0x30363732,0x384d3a47,0x3abf38f6,0xbae0bbd6,0xb817b26f,
  0xae783365,0x3bf63bc9,0xb5b6b927,0xbb79ba1f,0xb992b6c1,0x39be3b41,0x34c9a7da,0xbba2bbff,0x3b863c00,0x35700000,0xbc00bb77,0x257f35c2,
  0x380d3a27,0x3ae6391d,0xba43bb95,0xb8fbb51d,0xb12e31db,0x3be53bdd,0xb288b832,0xbbd5bad0,0xba0bb7cd,0x393e3afc,0x37803080,0xbb11bbec,
  0x3b7d3c00,0x359f0000,0xbbf8bbb6,0xadb03444,0x37963a07,0x3b0b3943,0xb989bb36,0xb9c7b6ee,0xb31b304e,0x3bcd3bed,0xa9e3b64e,0xbbfebb5a,
  0xba78b867,0x38b53aae,0x38fb34ed,0xba43bb9d,0x3b743c00,0x35ce0000,0xbbd7bbe2,0xb2573179,0x371039e5,0x3b2e3969,0xb8b5babc,0xba78b852,
  0xb4812d7e,0x3bad3bf8,0x2f40b414,0xbbf3bbbc,0xbad9b8e2,0x38223a56,0x3a0b3775,0xb93ebb14,0x3b6b3c00,0x35fd0000,0xbb9ebbfa,0xb4e12cb5,
  0x368739c3,0x3b4e398d,0xb796ba27,0xbb0bb91d,0xb57028b6,0x3b863bff,0x3451af0e,0xbbb4bbf4,0xbb2eb956,0x371039f6,0x3ae638e2,0xb80dba56,
  0x80003c00,0x80003c00,0x80003c00,0x80003c00,0x80003c00,0x80003c00,0x80003c00,0x80003c00,0x80003c00,0x80003c00,0x80003c00,0x80003c00,
  0x80003c00,0x80003c00,0x80003c00,0x80003c00,0xaa483bfe,0xb9ed395f,0xbbfeaa48,0xb95fb9ed,0xb3c63bc3,0xbadd381d,0xbbc3b3c6,0xb81dbadd,
  0xb6d73b3b,0xbb883564,0xbb3bb6d7,0xb564bb88,0xb8c43a6d,0xbbea30b2,0xba6db8c4,0xb0b2bbea,0xae463bf6,0xbbf6ae46,0x2e46bbf6,0x3bf62e46,
  0xb78b3b0e,0xbb0eb78b,0x378bbb0e,0x3b0e378b,0xba2f3913,0xb913ba2f,0x3a2fb913,0x39133a2f,0xbba834a5,0xb4a5bba8,0x3ba8b4a5,0x34a53ba8,
  0xb0b23bea,0xb8c4ba6d,0x3bea30b2,0xba6d38c4,0xb95f39ed,0xaa48bbfe,0x39ed395f,0xbbfe2a48,0xbbc333c6,0x381dbadd,0x33c63bc3,0xbaddb81d,
  0xbb88b564,0x3b3bb6d7,0xb5643b88,0xb6d7bb3b,0xb23e3bd9,0x323ebbd9,0xb23e3bd9,0x323ebbd9,0xbaa73872,0x3aa7b872,0xbaa73872,0x3aa7b872,
  0xbbd9b23e,0x3bd9323e,0xbbd9b23e,0x3bd9323e,0xb872baa7,0x38723aa7,0xb872baa7,0x38723aa7,0xb3c63bc3,0x3addb81d,0xbbc3b3c6,0x381d3add,
  0xbb883564,0x3b3b36d7,0xb564bb88,0xb6d73b3b,0xba6db8c4,0x30b23bea,0x38c4ba6d,0xbbea30b2,0x2a48bbfe,0xb9ed395f,0x3bfe2a48,0xb95fb9ed,
  0xb4a53ba8,0x3ba834a5,0x34a5bba8,0xbba8b4a5,0xbbf62e46,0x2e463bf6,0x3bf6ae46,0xae46bbf6,0xb78bbb0e,0xbb0e378b,0x378b3b0e,0x3b0eb78b,
  0x3913ba2f,0xba2fb913,0xb9133a2f,0x3a2f3913,0xb5643b88,0x36d73b3b,0x3b883564,0x3b3bb6d7,0xbbeab0b2,0xba6d38c4,0xb0b23bea,0x38c43a6d,
  0xaa48bbfe,0xb9edb95f,0xbbfe2a48,0xb95f39ed,0x3bc3b3c6,0x381dbadd,0xb3c6bbc3,0xbaddb81d,0xb61f3b64,0xb61f3b64,0xb61f3b64,0xb61f3b64,
  0xbb64b61f,0xbb64b61f,0xbb64b61f,0xbb64b61f,0x361fbb64,0x361fbb64,0x361fbb64,0x361fbb64,0x3b64361f,0x3b64361f,0x3b64361f,0x3b64361f,
  0xb6d73b3b,0xbb883564,0xbb3bb6d7,0xb564bb88,0xba6db8c4,0xb0b2bbea,0x38c4ba6d,0x3beab0b2,0x39edb95f,0x3bfe2a48,0x395f39ed,0xaa483bfe,
  0x381d3add,0xb3c63bc3,0xbadd381d,0xbbc3b3c6,0xb78b3b0e,0xbb0eb78b,0x378bbb0e,0x3b0e378b,0xb913ba2f,0x3a2fb913,0x39133a2f,0xba2f3913,
  0x3ba8b4a5,0x34a53ba8,0xbba834a5,0xb4a5bba8,0xae463bf6,0xbbf6ae46,0x2e46bbf6,0x3bf62e46,0xb81d3add,0xb3c6bbc3,0x3add381d,0xbbc333c6,
  0xb6d7bb3b,0x3b883564,0xbb3b36d7,0x3564bb88,0x3bea30b2,0xba6d38c4,0x30b2bbea,0x38c43a6d,0xb95f39ed,0xaa48bbfe,0x39ed395f,0xbbfe2a48,
  0xb8723aa7,0x3872baa7,0xb8723aa7,0x3872baa7,0xb23ebbd9,0x323e3bd9,0xb23ebbd9,0x323e3bd9,0x3aa73872,0xbaa7b872,0x3aa73872,0xbaa7b872,
  0xbbd9323e,0x3bd9b23e,0xbbd9323e,0x3bd9b23e,0xb8c43a6d,0x3beab0b2,0xba6db8c4,0x30b23bea,0x2a48bbfe,0xb9ed395f,0x3bfe2a48,0xb95fb9ed,
  0x381d3add,0x33c6bbc3,0xbadd381d,0x3bc333c6,0xbb3bb6d7,0x35643b88,0x36d7bb3b,0xbb883564,0xb9133a2f,0x3a2f3913,0x3913ba2f,0xba2fb913,
  0x34a5bba8,0xbba8b4a5,0xb4a53ba8,0x3ba834a5,0x2e463bf6,0x3bf6ae46,0xae46bbf6,0xbbf62e46,0xb78bbb0e,0xbb0e378b,0x378b3b0e,0x3b0eb78b,
  0xb95f39ed,0x2a483bfe,0x39ed395f,0x3bfeaa48,0x381dbadd,0xb3c6bbc3,0xbaddb81d,0xbbc333c6,0xb5643b88,0x36d73b3b,0x3b883564,0x3b3bb6d7,
  0x30b2bbea,0xb8c4ba6d,0xbbeab0b2,0xba6d38c4,0xb9a839a8,0xb9a839a8,0xb9a839a8,0xb9a839a8,0x39a8b9a8,0x39a8b9a8,0x39a8b9a8,0x39a8b9a8,
  0xb9a839a8,0xb9a839a8,0xb9a839a8,0xb9a839a8,0x39a8b9a8,0x39a8b9a8,0x39a8b9a8,0x39a8b9a8,0xb9ed395f,0xbbfeaa48,0xb95fb9ed,0x2a48bbfe,
  0x3addb81d,0x3bc333c6,0x381d3add,0xb3c63bc3,0xbb883564,0xbb3bb6d7,0xb564bb88,0x36d7bb3b,0x3beab0b2,0x3a6d38c4,0x30b23bea,0xb8c43a6d,
  0xba2f3913,0xb913ba2f,0x3a2fb913,0x39133a2f,0x3ba8b4a5,0x34a53ba8,0xbba834a5,0xb4a5bba8,0xbbf6ae46,0x2e46bbf6,0x3bf62e46,0xae463bf6,
  0x3b0e378b,0xb78b3b0e,0xbb0eb78b,0x378bbb0e,0xba6d38c4,0x30b2bbea,0x38c43a6d,0xbbeab0b2,0x3bfeaa48,0xb95f39ed,0xaa48bbfe,0x39ed395f,
  0xbaddb81d,0x3bc3b3c6,0xb81d3add,0xb3c6bbc3,0x36d73b3b,0xbb88b564,0x3b3bb6d7,0xb5643b88,0xbaa73872,0x3aa7b872,0xbaa73872,0x3aa7b872,
  0x3bd9323e,0xbbd9b23e,0x3bd9323e,0xbbd9b23e,0xb872baa7,0x38723aa7,0xb872baa7,0x38723aa7,0xb23e3bd9,0x323ebbd9,0xb23e3bd9,0x323ebbd9,
  0xbadd381d,0x3bc333c6,0xb81dbadd,0xb3c63bc3,0x3b3b36d7,0xb564bb88,0xb6d73b3b,0x3b88b564,0xb0b2bbea,0xb8c43a6d,0x3beab0b2,0xba6db8c4,
  0xb9ed395f,0x3bfe2a48,0xb95fb9ed,0xaa483bfe,0xbb0e378b,0x378b3b0e,0x3b0eb78b,0xb78bbb0e,0x3a2f3913,0x3913ba2f,0xba2fb913,0xb9133a2f,
  0x34a5bba8,0xbba8b4a5,0xb4a53ba8,0x3ba834a5,0xbbf62e46,0x2e463bf6,0x3bf6ae46,0xae46bbf6,0xbb3b36d7,0xb5643b88,0x36d73b3b,0x3b883564,
  0x38c43a6d,0x3bea30b2,0x3a6db8c4,0x30b2bbea,0x395fb9ed,0xaa48bbfe,0xb9edb95f,0xbbfe2a48,0xbaddb81d,0xbbc333c6,0xb81d3add,0x33c63bc3,
  0xbb64361f,0xbb64361f,0xbb64361f,0xbb64361f,0x361f3b64,0x361f3b64,0x361f3b64,0x361f3b64,0x3b64b61f,0x3b64b61f,0x3b64b61f,0x3b64b61f,
  0xb61fbb64,0xb61fbb64,0xb61fbb64,0xb61fbb64,0xbb883564,0xbb3bb6d7,0xb564bb88,0x36d7bb3b,0x30b23bea,0xb8c43a6d,0xbbea30b2,0xba6db8c4,
  0x3bfe2a48,0x395f39ed,0xaa483bfe,0xb9ed395f,0x33c6bbc3,0x3addb81d,0x3bc333c6,0x381d3add,0xbba834a5,0xb4a5bba8,0x3ba8b4a5,0x34a53ba8,
  0xae463bf6,0xbbf6ae46,0x2e46bbf6,0x3bf62e46,0x3b0e378b,0xb78b3b0e,0xbb0eb78b,0x378bbb0e,0x3a2fb913,0x39133a2f,0xba2f3913,0xb913ba2f,
  0xbbc333c6,0x381dbadd,0x33c63bc3,0xbaddb81d,0xb5643b88,0xb6d7bb3b,0x3b883564,0xbb3b36d7,0x38c43a6d,0xbbeab0b2,0x3a6db8c4,0xb0b23bea,
  0x3bfeaa48,0xb95f39ed,0xaa48bbfe,0x39ed395f,0xbbd9323e,0x3bd9b23e,0xbbd9323e,0x3bd9b23e,0xb8723aa7,0x3872baa7,0xb8723aa7,0x3872baa7,
  0x323e3bd9,0xb23ebbd9,0x323e3bd9,0xb23ebbd9,0x3aa73872,0xbaa7b872,0x3aa73872,0xbaa7b872,0xbbea30b2,0x3a6d38c4,0xb0b2bbea,0xb8c43a6d,
  0xb9ed395f,0x3bfe2a48,0xb95fb9ed,0xaa483bfe,0xb3c63bc3,0x3addb81d,0xbbc3b3c6,0x381d3add,0x35643b88,0x36d7bb3b,0xbb883564,0x3b3b36d7,
  0xbbf62e46,0x2e463bf6,0x3bf6ae46,0xae46bbf6,0xbb0e378b,0x378b3b0e,0x3b0eb78b,0xb78bbb0e,0xb9133a2f,0x3a2f3913,0x3913ba2f,0xba2fb913,
  0xb4a53ba8,0x3ba834a5,0x34a5bba8,0xbba8b4a5,0xbbfe2a48,0xb95f39ed,0x2a483bfe,0x39ed395f,0xbbc333c6,0xb81d3add,0x33c63bc3,0x3add381d,
  0xbb3b36d7,0xb5643b88,0x36d73b3b,0x3b883564,0xba6d38c4,0xb0b23bea,0x38c43a6d,0x3bea30b2,0x80003c00,0x80003c00,0x80003c00,0x80003c00,
  0x80003c00,0x80003c00,0x80003c00,0x80003c00,0x80003c00,0x80003c00,0x80003c00,0x80003c00,0x80003c00,0x80003c00,0x80003c00,0x80003c00,
  0x2a48bbfe,0x39edb95f,0x3bfe2a48,0x395f39ed,0x33c6bbc3,0x3addb81d,0x3bc333c6,0x381d3add,0x36d7bb3b,0x3b88b564,0x3b3b36d7,0x35643b88,
  0x38c4ba6d,0x3beab0b2,0x3a6d38c4,0x30b23bea,0xae463bf6,0xbbf6ae46,0x2e46bbf6,0x3bf62e46,0xb78b3b0e,0xbb0eb78b,0x378bbb0e,0x3b0e378b,
  0xba2f3913,0xb913ba2f,0x3a2fb913,0x39133a2f,0xbba834a5,0xb4a5bba8,0x3ba8b4a5,0x34a53ba8,0x30b2bbea,0x38c43a6d,0xbbeab0b2,0x3a6db8c4,
  0x395fb9ed,0x2a483bfe,0xb9edb95f,0x3bfeaa48,0x3bc3b3c6,0xb81d3add,0xb3c6bbc3,0x3add381d,0x3b883564,0xbb3b36d7,0x3564bb88,0x36d73b3b,
  0xb23e3bd9,0x323ebbd9,0xb23e3bd9,0x323ebbd9,0xbaa73872,0x3aa7b872,0xbaa73872,0x3aa7b872,0xbbd9b23e,0x3bd9323e,0xbbd9b23e,0x3bd9323e,
  0xb872baa7,0x38723aa7,0xb872baa7,0x38723aa7,0x33c6bbc3,0xbadd381d,0x3bc333c6,0xb81dbadd,0x3b88b564,0xbb3bb6d7,0x35643b88,0x36d7bb3b,
  0x3a6d38c4,0xb0b2bbea,0xb8c43a6d,0x3beab0b2,0xaa483bfe,0x39edb95f,0xbbfeaa48,0x395f39ed,0xb4a53ba8,0x3ba834a5,0x34a5bba8,0xbba8b4a5,
  0xbbf62e46,0x2e463bf6,0x3bf6ae46,0xae46bbf6,0xb78bbb0e,0xbb0e378b,0x378b3b0e,0x3b0eb78b,0x3913ba2f,0xba2fb913,0xb9133a2f,0x3a2f3913,
  0x3564bb88,0xb6d7bb3b,0xbb88b564,0xbb3b36d7,0x3bea30b2,0x3a6db8c4,0x30b2bbea,0xb8c4ba6d,0x2a483bfe,0x39ed395f,0x3bfeaa48,0x395fb9ed,
  0xbbc333c6,0xb81d3add,0x33c63bc3,0x3add381d,0xb61f3b64,0xb61f3b64,0xb61f3b64,0xb61f3b64,0xbb64b61f,0xbb64b61f,0xbb64b61f,0xbb64b61f,
  0x361fbb64,0x361fbb64,0x361fbb64,0x361fbb64,0x3b64361f,0x3b64361f,0x3b64361f,0x3b64361f,0x36d7bb3b,0x3b88b564,0x3b3b36d7,0x35643b88,
  0x3a6d38c4,0x30b23bea,0xb8c43a6d,0xbbea30b2,0xb9ed395f,0xbbfeaa48,0xb95fb9ed,0x2a48bbfe,0xb81dbadd,0x33c6bbc3,0x3addb81d,0x3bc333c6,
  0xb78b3b0e,0xbb0eb78b,0x378bbb0e,0x3b0e378b,0xb913ba2f,0x3a2fb913,0x39133a2f,0xba2f3913,0x3ba8b4a5,0x34a53ba8,0xbba834a5,0xb4a5bba8,
  0xae463bf6,0xbbf6ae46,0x2e46bbf6,0x3bf62e46,0x381dbadd,0x33c63bc3,0xbaddb81d,0x3bc3b3c6,0x36d73b3b,0xbb88b564,0x3b3bb6d7,0xb5643b88,
  0xbbeab0b2,0x3a6db8c4,0xb0b23bea,0xb8c4ba6d,0x395fb9ed,0x2a483bfe,0xb9edb95f,0x3bfeaa48,0xb8723aa7,0x3872baa7,0xb8723aa7,0x3872baa7,
  0xb23ebbd9,0x323e3bd9,0xb23ebbd9,0x323e3bd9,0x3aa73872,0xbaa7b872,0x3aa73872,0xbaa7b872,0xbbd9323e,0x3bd9b23e,0xbbd9323e,0x3bd9b23e,
  0x38c4ba6d,0xbbea30b2,0x3a6d38c4,0xb0b2bbea,0xaa483bfe,0x39edb95f,0xbbfeaa48,0x395f39ed,0xb81dbadd,0xb3c63bc3,0x3addb81d,0xbbc3b3c6,
  0x3b3b36d7,0xb564bb88,0xb6d73b3b,0x3b88b564,0xb9133a2f,0x3a2f3913,0x3913ba2f,0xba2fb913,0x34a5bba8,0xbba8b4a5,0xb4a53ba8,0x3ba834a5,
  0x2e463bf6,0x3bf6ae46,0xae46bbf6,0xbbf62e46,0xb78bbb0e,0xbb0e378b,0x378b3b0e,0x3b0eb78b,0x395fb9ed,0xaa48bbfe,0xb9edb95f,0xbbfe2a48,
  0xb81d3add,0x33c63bc3,0x3add381d,0x3bc3b3c6,0x3564bb88,0xb6d7bb3b,0xbb88b564,0xbb3b36d7,0xb0b23bea,0x38c43a6d,0x3bea30b2,0x3a6db8c4,
  0xb9a839a8,0xb9a839a8,0xb9a839a8,0xb9a839a8,0x39a8b9a8,0x39a8b9a8,0x39a8b9a8,0x39a8b9a8,0xb9a839a8,0xb9a839a8,0xb9a839a8,0xb9a839a8,
  0x39a8b9a8,0x39a8b9a8,0x39a8b9a8,0x39a8b9a8,0x39edb95f,0x3bfe2a48,0x395f39ed,0xaa483bfe,0xbadd381d,0xbbc3b3c6,0xb81dbadd,0x33c6bbc3,
  0x3b88b564,0x3b3b36d7,0x35643b88,0xb6d73b3b,0xbbea30b2,0xba6db8c4,0xb0b2bbea,0x38c4ba6d,0xba2f3913,0xb913ba2f,0x3a2fb913,0x39133a2f,
  0x3ba8b4a5,0x34a53ba8,0xbba834a5,0xb4a5bba8,0xbbf6ae46,0x2e46bbf6,0x3bf62e46,0xae463bf6,0x3b0e378b,0xb78b3b0e,0xbb0eb78b,0x378bbb0e,
  0x3a6db8c4,0xb0b23bea,0xb8c4ba6d,0x3bea30b2,0xbbfe2a48,0x395fb9ed,0x2a483bfe,0xb9edb95f,0x3add381d,0xbbc333c6,0x381dbadd,0x33c63bc3,
  0xb6d7bb3b,0x3b883564,0xbb3b36d7,0x3564bb88,0xbaa73872,0x3aa7b872,0xbaa73872,0x3aa7b872,0x3bd9323e,0xbbd9b23e,0x3bd9323e,0xbbd9b23e,
  0xb872baa7,0x38723aa7,0xb872baa7,0x38723aa7,0xb23e3bd9,0x323ebbd9,0xb23e3bd9,0x323ebbd9,0x3addb81d,0xbbc3b3c6,0x381d3add,0x33c6bbc3,
  0xbb3bb6d7,0x35643b88,0x36d7bb3b,0xbb883564,0x30b23bea,0x38c4ba6d,0xbbea30b2,0x3a6d38c4,0x39edb95f,0xbbfeaa48,0x395f39ed,0x2a48bbfe,
  0xbb0e378b,0x378b3b0e,0x3b0eb78b,0xb78bbb0e,0x3a2f3913,0x3913ba2f,0xba2fb913,0xb9133a2f,0x34a5bba8,0xbba8b4a5,0xb4a53ba8,0x3ba834a5,
  0xbbf62e46,0x2e463bf6,0x3bf6ae46,0xae46bbf6,0x3b3bb6d7,0x3564bb88,0xb6d7bb3b,0xbb88b564,0xb8c4ba6d,0xbbeab0b2,0xba6d38c4,0xb0b23bea,
  0xb95f39ed,0x2a483bfe,0x39ed395f,0x3bfeaa48,0x3add381d,0x3bc3b3c6,0x381dbadd,0xb3c6bbc3,0xbb64361f,0xbb64361f,0xbb64361f,0xbb64361f,
  0x361f3b64,0x361f3b64,0x361f3b64,0x361f3b64,0x3b64b61f,0x3b64b61f,0x3b64b61f,0x3b64b61f,0xb61fbb64,0xb61fbb64,0xb61fbb64,0xb61fbb64,
  0x3b88b564,0x3b3b36d7,0x35643b88,0xb6d73b3b,0xb0b2bbea,0x38c4ba6d,0x3beab0b2,0x3a6d38c4,0xbbfeaa48,0xb95fb9ed,0x2a48bbfe,0x39edb95f,
  0xb3c63bc3,0xbadd381d,0xbbc3b3c6,0xb81dbadd,0xbba834a5,0xb4a5bba8,0x3ba8b4a5,0x34a53ba8,0xae463bf6,0xbbf6ae46,0x2e46bbf6,0x3bf62e46,
  0x3b0e378b,0xb78b3b0e,0xbb0eb78b,0x378bbb0e,0x3a2fb913,0x39133a2f,0xba2f3913,0xb913ba2f,0x3bc3b3c6,0xb81d3add,0xb3c6bbc3,0x3add381d,
  0x3564bb88,0x36d73b3b,0xbb88b564,0x3b3bb6d7,0xb8c4ba6d,0x3bea30b2,0xba6d38c4,0x30b2bbea,0xbbfe2a48,0x395fb9ed,0x2a483bfe,0xb9edb95f,
  0xbbd9323e,0x3bd9b23e,0xbbd9323e,0x3bd9b23e,0xb8723aa7,0x3872baa7,0xb8723aa7,0x3872baa7,0x323e3bd9,0xb23ebbd9,0x323e3bd9,0xb23ebbd9,
  0x3aa73872,0xbaa7b872,0x3aa73872,0xbaa7b872,0x3beab0b2,0xba6db8c4,0x30b23bea,0x38c4ba6d,0x39edb95f,0xbbfeaa48,0x395f39ed,0x2a48bbfe,
  0x33c6bbc3,0xbadd381d,0x3bc333c6,0xb81dbadd,0xb564bb88,0xb6d73b3b,0x3b88b564,0xbb3bb6d7,0xbbf62e46,0x2e463bf6,0x3bf6ae46,0xae46bbf6,
  0xbb0e378b,0x378b3b0e,0x3b0eb78b,0xb78bbb0e,0xb9133a2f,0x3a2f3913,0x3913ba2f,0xba2fb913,0xb4a53ba8,0x3ba834a5,0x34a5bba8,0xbba8b4a5,
  0x3bfeaa48,0x395fb9ed,0xaa48bbfe,0xb9edb95f,0x3bc3b3c6,0x381dbadd,0xb3c6bbc3,0xbaddb81d,0x3b3bb6d7,0x3564bb88,0xb6d7bb3b,0xbb88b564,
  0x3a6db8c4,0x30b2bbea,0xb8c4ba6d,0xbbeab0b2,0x00000000,0x00000000,0x00000000,0x00000000,0xaa1f0000,0xaf64ada8,0xaf64b000,0xaa1fada8,
  0xada80000,0xada8b000,0x2da88000,0x2da83000,0xaf640000,0x2a1fada8,0x2a1f3000,0xaf64ada8,0xb0000000,0x30008000,0xb0000000,0x30008000,
  0xaf640000,0x2a1f2da8,0x2a1fb000,0xaf642da8,0xada80000,0xada83000,0x2da88000,0x2da8b000,0xaa1f0000,0xaf642da8,0xaf643000,0xaa1f2da8,
  0x00000000,0x00000000,0x00000000,0x00000000,0x2a1f8000,0x2f642da8,0x2f643000,0x2a1f2da8,0xada80000,0xada8b000,0x2da88000,0x2da83000,
  0x2f648000,0xaa1f2da8,0xaa1fb000,0x2f642da8,0xb0000000,0x30008000,0xb0000000,0x30008000,0x2f648000,0xaa1fada8,0xaa1f3000,0x2f64ada8,
  0xada80000,0xada83000,0x2da88000,0x2da8b000,0x2a1f8000,0x2f64ada8,0x2f64b000,0x2a1fada8,0x80000000,0x80000000,0x80000000,0x80000000,
  0x2a1f0000,0x2f64ada8,0x2f64b000,0x2a1fada8,0x2da80000,0x2da8b000,0xada88000,0xada83000,0x2f640000,0xaa1fada8,0xaa1f3000,0x2f64ada8,
  0x30000000,0xb0008000,0x30000000,0xb0008000,0x2f640000,0xaa1f2da8,0xaa1fb000,0x2f642da8,0x2da80000,0x2da83000,0xada88000,0xada8b000,
  0x2a1f0000,0x2f642da8,0x2f643000,0x2a1f2da8,0x80000000,0x80000000,0x80000000,0x80000000,0xaa1f8000,0xaf642da8,0xaf643000,0xaa1f2da8,
  0x2da80000,0x2da8b000,0xada88000,0xada83000,0xaf648000,0x2a1f2da8,0x2a1fb000,0xaf642da8,0x30000000,0xb0008000,0x30000000,0xb0008000,
  0xaf648000,0x2a1fada8,0x2a1f3000,0xaf64ada8,0x2da80000,0x2da83000,0xada88000,0xada8b000,0xaa1f8000,0xaf64ada8,0xaf64b000,0xaa1fada8,
  0x30003000,0x30003000,0x30003000,0x30003000,0x2f643000,0x2a1f2da8,0xaa1f0000,0xaf64ada8,0x2da83000,0xada80000,0xada8b000,0x2da88000,
  0x2a1f3000,0xaf64ada8,0x2f648000,0xaa1f2da8,0x00003000,0x8000b000,0x00003000,0x8000b000,0xaa1f3000,0x2f64ada8,0xaf640000,0x2a1f2da8,
  0xada83000,0x2da88000,0x2da8b000,0xada80000,0xaf643000,0xaa1f2da8,0x2a1f8000,0x2f64ada8,0x30003000,0x30003000,0x30003000,0x30003000,
  0xaf64b000,0xaa1fada8,0x2a1f8000,0x2f642da8,0x2da83000,0xada80000,0xada8b000,0x2da88000,0xaa1fb000,0x2f642da8,0xaf640000,0x2a1fada8,
  0x00003000,0x8000b000,0x00003000,0x8000b000,0x2a1fb000,0xaf642da8,0x2f648000,0xaa1fada8,0xada83000,0x2da88000,0x2da8b000,0xada80000,
  0x2f64b000,0x2a1fada8,0xaa1f0000,0xaf642da8,0xb0003000,0xb0003000,0xb0003000,0xb0003000,0xaf643000,0xaa1f2da8,0x2a1f0000,0x2f64ada8,
  0xada83000,0x2da80000,0x2da8b000,0xada88000,0xaa1f3000,0x2f64ada8,0xaf648000,0x2a1f2da8,0x80003000,0x0000b000,0x80003000,0x0000b000,
  0x2a1f3000,0xaf64ada8,0x2f640000,0xaa1f2da8,0x2da83000,0xada88000,0xada8b000,0x2da80000,0x2f643000,0x2a1f2da8,0xaa1f8000,0xaf64ada8,
  0xb0003000,0xb0003000,0xb0003000,0xb0003000,0x2f64b000,0x2a1fada8,0xaa1f8000,0xaf642da8,0xada83000,0x2da80000,0x2da8b000,0xada88000,
  0x2a1fb000,0xaf642da8,0x2f640000,0xaa1fada8,0x80003000,0x0000b000,0x80003000,0x0000b000,0xaa1fb000,0x2f642da8,0xaf648000,0x2a1fada8,
  0x2da83000,0xada88000,0xada8b000,0x2da80000,0xaf64b000,0xaa1fada8,0x2a1f0000,0x2f642da8,0x80008000,0x80008000,0x80008000,0x80008000,
  0x2a1f8000,0x2f642da8,0x2f643000,0x2a1f2da8,0x2da88000,0x2da83000,0xada80000,0xada8b000,0x2f648000,0xaa1f2da8,0xaa1fb000,0x2f642da8,
  0x30008000,0xb0000000,0x30008000,0xb0000000,0x2f648000,0xaa1fada8,0xaa1f3000,0x2f64ada8,0x2da88000,0x2da8b000,0xada80000,0xada83000,
  0x2a1f8000,0x2f64ada8,0x2f64b000,0x2a1fada8,0x80008000,0x80008000,0x80008000,0x80008000,0xaa1f0000,0xaf64ada8,0xaf64b000,0xaa1fada8,
  0x2da88000,0x2da83000,0xada80000,0xada8b000,0xaf640000,0x2a1fada8,0x2a1f3000,0xaf64ada8,0x30008000,0xb0000000,0x30008000,0xb0000000,
  0xaf640000,0x2a1f2da8,0x2a1fb000,0xaf642da8,0x2da88000,0x2da8b000,0xada80000,0xada83000,0xaa1f0000,0xaf642da8,0xaf643000,0xaa1f2da8,
  0x00008000,0x00008000,0x00008000,0x00008000,0xaa1f8000,0xaf642da8,0xaf643000,0xaa1f2da8,0xada88000,0xada83000,0x2da80000,0x2da8b000,
  0xaf648000,0x2a1f2da8,0x2a1fb000,0xaf642da8,0xb0008000,0x30000000,0xb0008000,0x30000000,0xaf648000,0x2a1fada8,0x2a1f3000,0xaf64ada8,
  0xada88000,0xada8b000,0x2da80000,0x2da83000,0xaa1f8000,0xaf64ada8,0xaf64b000,0xaa1fada8,0x00008000,0x00008000,0x00008000,0x00008000,
  0x2a1f0000,0x2f64ada8,0x2f64b000,0x2a1fada8,0xada88000,0xada83000,0x2da80000,0x2da8b000,0x2f640000,0xaa1fada8,0xaa1f3000,0x2f64ada8,
  0xb0008000,0x30000000,0xb0008000,0x30000000,0x2f640000,0xaa1f2da8,0xaa1fb000,0x2f642da8,0xada88000,0xada8b000,0x2da80000,0x2da83000,
  0x2a1f0000,0x2f642da8,0x2f643000,0x2a1f2da8,
};

constexpr int kThreads = 384;
constexpr int kCtas = 128;

#define EARLY 2
#define HT0 13800
#define HGAP 500
#define PREP0 1200
#define PREPGAP 700
#define U0 5
#define UNUM 11
#define UDEN 4
#define UCV 28
#define UPRE 0
#define WQT 11800
#define QGAP 400
#define QT 17800
#define QSCH 0x554210
#define PSEQ 0
#define REDF 0
#define DELEG 0
#define S18 0
#define KVS 16
#define KVL 14
#define OSEQ 2
#define TAIL 3
#define TAILE 0
#define ENDS 0
#define PU 2
#define POSTGAP 600
#define SAFE 1
#define EXP 0

constexpr int NS1 = 6;
__host__ __device__ constexpr int slot1(int it) { return (it + 4) % NS1; }
__host__ __device__ constexpr uint32_t w1_off(int s) { return (1 + s + (s >> 1)) * 16384; }
__host__ __device__ constexpr uint32_t x1_off(int it) { return ((it >> 1) & 3) * 49152; }
constexpr uint32_t ST2 = 32768;
constexpr uint32_t RA = 131072;
constexpr uint32_t R_KV = RA + 20480;
constexpr uint32_t RB = 163840;
constexpr uint32_t RU = 196608;
constexpr uint32_t Y_OWN = RU, Y_IN = RU + 16384;
constexpr uint32_t SM_ONES = 229376;
constexpr uint32_t SM_F2 = SM_ONES + 128;
constexpr uint32_t SM_BAR = 231424;
constexpr uint32_t SM_SCALE = SM_ONES + 1792;
constexpr uint32_t SM_MAX = SM_BAR + 512;
constexpr uint32_t SM_TOTAL = 232448;
constexpr uint32_t SM_BASE = 1024;
constexpr uint32_t KV_HEAD = 2560;

enum Bar { B_F1 = 0, B_F2 = 6, B_H = B_F2 + 4, B_KVL = 12, B_RDY = 16, B_Q = 30, B_MAX, B_ZERO, B_U, B_KV,
           B_E1 = 35, B_E2 = 41, B_I2 = B_E2 + 4,
           B_KVE = 47, B_VST = 51, B_KVM, B_KVP, B_KVI, B_OW, B_S1 = 57, B_ZST,
           B_OFREE = 59, B_F2M = 61, B_STG, B_Y, B_COUNT, B_U2 = B_KVL };
__host__ __device__ constexpr int slot2(int n) { return n < 22 ? n & 3 : (0x1032510325ull >> (4 * (n - 22))) & 7; }
__host__ __device__ constexpr int par2(int n) { return n < 22 ? (n >> 2) & 1 : (0x326 >> (n - 22)) & 1; }

struct Params {
  CUtensorMap w1, x, k, v, w2, wo, o, outa, q, outb;
  const __nv_bfloat16* shift_k;
  const __nv_bfloat16* ssm_k;
  const __nv_bfloat16* ssm_d;
  const __nv_bfloat16* q_ptr;
  const __nv_bfloat16* k_ptr;
  const __nv_bfloat16* w_ptr;
  const __nv_bfloat16* wo_ptr;
  uint64_t zero;
};

constexpr int KV_WORDS = 4096 + 128;
__device__ __align__(128) float g_kv[8][KV_WORDS];
__device__ unsigned g_kvflag[8 * 32], g_zflag[8 * 32];
__device__ __align__(128) unsigned g_oflag[16 * 32];
__device__ unsigned g_epoch[kCtas];
__device__ __align__(128) __nv_bfloat16 g_o[2048 * 1024];

#define TSTAMP(cond, i) do { } while (0)
#define GSTAMP(cond, i) do { } while (0)
#define KSTAMP(n) do { } while (0)
#define QSTAMP(n) do { } while (0)

constexpr int kSpinLimit = 1 << 17;

DEVI void mbar_init(uint32_t a, uint32_t c) { asm volatile("mbarrier.init.shared::cta.b64 [%0], %1;" :: "r"(a), "r"(c) : "memory"); }
DEVI void mbar_expect(uint32_t a, uint32_t b) { asm volatile("mbarrier.arrive.expect_tx.shared::cta.b64 _, [%0], %1;" :: "r"(a), "r"(b) : "memory"); }
DEVI void mbar_arrive(uint32_t a) { asm volatile("mbarrier.arrive.shared::cta.b64 _, [%0];" :: "r"(a) : "memory"); }
DEVI void mbar_arrive_if(uint32_t a, bool pred) {
  asm volatile("{\n.reg .pred p;\nsetp.ne.b32 p, %1, 0;\n@p mbarrier.arrive.shared::cta.b64 _, [%0];\n}" :: "r"(a), "r"((int)pred) : "memory");
}
DEVI void mbar_wait(uint32_t a, uint32_t parity) {
  asm volatile("{\n.reg .pred p;\n.reg .u32 n;\nmov.u32 n, 0;\nW_LOOP:\n"
               "mbarrier.try_wait.parity.shared::cta.b64 p, [%0], %1;\n@p bra W_DONE;\n"
               "add.u32 n, n, 1;\nsetp.lt.u32 p, n, %2;\n@p bra W_LOOP;\nW_DONE:\n}"
               :: "r"(a), "r"(parity), "n"(kSpinLimit) : "memory");
}
DEVI void mbar_wait_long(uint32_t a, uint32_t parity) {
  asm volatile("{\n.reg .pred p;\n.reg .u32 n;\nmov.u32 n, 0;\nW_LOOP:\n"
               "mbarrier.try_wait.parity.shared::cta.b64 p, [%0], %1, %3;\n@p bra W_DONE;\n"
               "add.u32 n, n, 1;\nsetp.lt.u32 p, n, %2;\n@p bra W_LOOP;\nW_DONE:\n}"
               :: "r"(a), "r"(parity), "n"(kSpinLimit), "r"(4000) : "memory");
}
DEVI void flag_wait(const unsigned* p, unsigned target) {
  int n = 0; unsigned v;
  do {
    asm volatile("ld.acquire.gpu.global.u32 %0, [%1];" : "=r"(v) : "l"(p) : "memory");
  } while ((int)(v - target) < 0 && ++n < kSpinLimit);
}
DEVI unsigned ld_relaxed(const unsigned* p) { unsigned v; asm volatile("ld.relaxed.gpu.global.u32 %0, [%1];" : "=r"(v) : "l"(p) : "memory"); return v; }
DEVI uint32_t clock32() { uint32_t t; asm volatile("mov.u32 %0, %%clock;" : "=r"(t)); return t; }
DEVI void pace(uint32_t t0, uint32_t n) { while (clock32() - t0 < n) __nanosleep(20); }
DEVI bool elect() { uint32_t p; asm volatile("{\n.reg .pred p;\nelect.sync _|p, 0xffffffff;\nselp.u32 %0, 1, 0, p;\n}" : "=r"(p)); return p; }
DEVI void fence_async_smem() { asm volatile("fence.proxy.async.shared::cta;" ::: "memory"); }
DEVI void bar_sync(int id, int n) { asm volatile("bar.sync %0, %1;" :: "r"(id), "r"(n) : "memory"); }
DEVI void cluster_sync() { asm volatile("barrier.cluster.arrive.relaxed.aligned;\nbarrier.cluster.wait.aligned;" ::: "memory"); }
DEVI void wg_fence() { asm volatile("wgmma.fence.sync.aligned;" ::: "memory"); }
DEVI void wg_commit() { asm volatile("wgmma.commit_group.sync.aligned;" ::: "memory"); }
template <int N> DEVI void wg_wait() { asm volatile("wgmma.wait_group.sync.aligned %0;" :: "n"(N) : "memory"); }
template <int N> DEVI void pin(uint32_t* r) {
#pragma unroll
  for (int i = 0; i < N; i++) asm volatile("" : "+r"(r[i]));
}
template <int N> DEVI void pin(float* r) {
#pragma unroll
  for (int i = 0; i < N; i++) asm volatile("" : "+f"(r[i]));
}

DEVI void tma2d(uint32_t dst, const CUtensorMap* m, int c0, int c1, uint32_t bar) {
  asm volatile("cp.async.bulk.tensor.2d.shared::cluster.global.mbarrier::complete_tx::bytes [%0], [%1, {%3, %4}], [%2];"
               :: "r"(dst), "l"(m), "r"(bar), "r"(c0), "r"(c1) : "memory");
}
DEVI void tma2d_mc(uint32_t dst, const CUtensorMap* m, int c0, int c1, uint32_t bar) {
  asm volatile("cp.async.bulk.tensor.2d.shared::cluster.global.mbarrier::complete_tx::bytes.multicast::cluster [%0], [%1, {%3, %4}], [%2], %5;"
               :: "r"(dst), "l"(m), "r"(bar), "r"(c0), "r"(c1), "h"((uint16_t)3) : "memory");
}
DEVI void tma3d(uint32_t dst, const CUtensorMap* m, int c0, int c1, int c2, uint32_t bar) {
  asm volatile("cp.async.bulk.tensor.3d.shared::cluster.global.mbarrier::complete_tx::bytes [%0], [%1, {%3, %4, %5}], [%2];"
               :: "r"(dst), "l"(m), "r"(bar), "r"(c0), "r"(c1), "r"(c2) : "memory");
}
DEVI void tma4d(uint32_t dst, const CUtensorMap* m, int c1, int c2, int c3, uint32_t bar) {
  asm volatile("cp.async.bulk.tensor.4d.shared::cluster.global.mbarrier::complete_tx::bytes [%0], [%1, {%3, %4, %5, %6}], [%2];"
               :: "r"(dst), "l"(m), "r"(bar), "r"(0), "r"(c1), "r"(c2), "r"(c3) : "memory");
}
DEVI void tma5d(uint32_t dst, const CUtensorMap* m, int c0, int c1, int c3, int c4, uint32_t bar) {
  asm volatile("cp.async.bulk.tensor.5d.shared::cluster.global.mbarrier::complete_tx::bytes [%0], [%1, {%3, %4, %5, %6, %7}], [%2];"
               :: "r"(dst), "l"(m), "r"(bar), "r"(c0), "r"(c1), "r"(0), "r"(c3), "r"(c4) : "memory");
}
DEVI void tma2d_store(const CUtensorMap* m, uint32_t src, int c0, int c1) {
  asm volatile("cp.async.bulk.tensor.2d.global.shared::cta.bulk_group [%0, {%2, %3}], [%1];" :: "l"(m), "r"(src), "r"(c0), "r"(c1) : "memory");
}
DEVI void tma2d_store_e(const CUtensorMap* m, uint32_t src, int c0, int c1) {
  asm volatile("{\n.reg .pred e;\nelect.sync _|e, 0xffffffff;\n@e cp.async.bulk.tensor.2d.global.shared::cta.bulk_group [%0, {%2, %3}], [%1];\n"
               "@e cp.async.bulk.commit_group;\n}" :: "l"(m), "r"(src), "r"(c0), "r"(c1) : "memory");
}
DEVI void tma5d_store(const CUtensorMap* m, uint32_t src, int c0, int c1, int c3, int c4) {
  asm volatile("cp.async.bulk.tensor.5d.global.shared::cta.bulk_group [%0, {%2, %3, %4, %5, %6}], [%1];\ncp.async.bulk.commit_group;"
               :: "l"(m), "r"(src), "r"(c0), "r"(c1), "r"(0), "r"(c3), "r"(c4) : "memory");
}
DEVI void bulk_load(uint32_t dst, const void* src, uint32_t bytes, uint32_t bar) {
  asm volatile("cp.async.bulk.shared::cluster.global.mbarrier::complete_tx::bytes [%0], [%1], %2, [%3];" :: "r"(dst), "l"(src), "r"(bytes), "r"(bar) : "memory");
}
DEVI uint32_t mapa(uint32_t a, int rank) { uint32_t r; asm("mapa.shared::cluster.u32 %0, %1, %2;" : "=r"(r) : "r"(a), "r"(rank)); return r; }
DEVI void st_async4(uint32_t dst, uint32_t a, uint32_t b, uint32_t c, uint32_t d, uint32_t bar) {
  asm volatile("st.async.weak.shared::cluster.mbarrier::complete_tx::bytes.v4.b32 [%0], {%1,%2,%3,%4}, [%5];"
               :: "r"(dst), "r"(a), "r"(b), "r"(c), "r"(d), "r"(bar) : "memory");
}
DEVI void st_either4(bool local, uint32_t dst, uint32_t a, uint32_t b, uint32_t c, uint32_t d, uint32_t bar) {
  asm volatile("{\n.reg .pred p;\nsetp.ne.b32 p, %6, 0;\n@p st.shared.v4.b32 [%0], {%1,%2,%3,%4};\n"
               "@!p st.async.weak.shared::cluster.mbarrier::complete_tx::bytes.v4.b32 [%0], {%1,%2,%3,%4}, [%5];\n}"
               :: "r"(dst), "r"(a), "r"(b), "r"(c), "r"(d), "r"(bar), "r"((int)local) : "memory");
}
DEVI void st_async1_if(uint32_t dst, uint32_t a, uint32_t bar, bool pred) {
  asm volatile("{\n.reg .pred p;\nsetp.ne.b32 p, %3, 0;\n@p st.async.weak.shared::cluster.mbarrier::complete_tx::bytes.b32 [%0], %1, [%2];\n}"
               :: "r"(dst), "r"(a), "r"(bar), "r"((int)pred) : "memory");
}
DEVI void pf_line(const void* p) { asm volatile("prefetch.global.L2 [%0];" :: "l"(p) : "memory"); }
DEVI void bulk_commit() { asm volatile("cp.async.bulk.commit_group;" ::: "memory"); }
DEVI void bulk_wait_all() { asm volatile("cp.async.bulk.wait_group 0;" ::: "memory"); }
DEVI void bulk_wait_read() { asm volatile("cp.async.bulk.wait_group.read 0;" ::: "memory"); }
DEVI void prefetch_map(const CUtensorMap* m) { asm volatile("prefetch.tensormap [%0];" :: "l"(m) : "memory"); }

__host__ __device__ constexpr uint32_t dlo(uint32_t off, uint32_t lbo) { return (off >> 4) + ((lbo >> 4) << 16); }
struct Desc {
  uint64_t v;
  DEVI Desc(uint64_t z, uint32_t base, uint32_t sbo, uint32_t mode) : v(z + (base | (uint64_t)((sbo >> 4) | (mode << 30)) << 32)) { asm volatile("" : "+l"(v)); }
  DEVI void renew(uint64_t z) { asm volatile("add.s64 %0, %0, %1;" : "+l"(v) : "l"(z)); }
  DEVI uint64_t at(uint32_t lo) const { uint64_t r; asm volatile("add.s64 %0, %1, %2;" : "=l"(r) : "l"(v), "l"((int64_t)(int32_t)lo)); return r; }
};
DEVI uint32_t pack_bf16(float lo, float hi) { uint32_t r; asm("cvt.rn.bf16x2.f32 %0, %1, %2;" : "=r"(r) : "f"(hi), "f"(lo)); return r; }
DEVI uint32_t pack_f16(float lo, float hi) { uint32_t r; asm("cvt.rn.f16x2.f32 %0, %1, %2;" : "=r"(r) : "f"(hi), "f"(lo)); return r; }
DEVI void stsm4(uint32_t addr, uint32_t r0, uint32_t r1, uint32_t r2, uint32_t r3) {
  asm volatile("stmatrix.sync.aligned.m8n8.x4.shared.b16 [%0], {%1,%2,%3,%4};" :: "r"(addr), "r"(r0), "r"(r1), "r"(r2), "r"(r3) : "memory");
}
DEVI void sts128(uint32_t addr, uint32_t a, uint32_t b, uint32_t c, uint32_t d) {
  asm volatile("st.shared.v4.b32 [%0], {%1,%2,%3,%4};" :: "r"(addr), "r"(a), "r"(b), "r"(c), "r"(d) : "memory");
}
DEVI void sts32(uint32_t addr, uint32_t v) { asm volatile("st.shared.b32 [%0], %1;" :: "r"(addr), "r"(v) : "memory"); }
DEVI uint32_t lds32(uint32_t a) { uint32_t v; asm volatile("ld.shared.b32 %0, [%1];" : "=r"(v) : "r"(a)); return v; }
DEVI void lds128(uint32_t* v, uint32_t a) {
  asm volatile("ld.shared.v4.b32 {%0,%1,%2,%3}, [%4];" : "=r"(v[0]), "=r"(v[1]), "=r"(v[2]), "=r"(v[3]) : "r"(a));
}
DEVI void ldg128(uint32_t* v, const void* p) {
  asm volatile("ld.global.nc.L1::no_allocate.v4.b32 {%0,%1,%2,%3}, [%4];" : "=r"(v[0]), "=r"(v[1]), "=r"(v[2]), "=r"(v[3]) : "l"(p));
}
DEVI uint32_t ldg32(const void* p) { uint32_t v; asm volatile("ld.global.nc.L1::no_allocate.b32 %0, [%1];" : "=r"(v) : "l"(p)); return v; }
DEVI float rcp(float x) { float r; asm("rcp.approx.ftz.f32 %0, %1;" : "=f"(r) : "f"(x)); return r; }
DEVI float exp_sat(float t) {
  float e, s;
  asm("ex2.approx.ftz.f32 %0, %1;" : "=f"(e) : "f"(t * 1.4426950408889634f));
  asm("add.sat.f32 %0, %1, 0f358637BD;" : "=f"(s) : "f"(e));
  return s;
}
DEVI uint32_t phi2(float a, float b) {
  uint32_t r, o;
  asm("cvt.rn.relu.bf16x2.f32 %0, %1, %2;" : "=r"(r) : "f"(b), "f"(a));
  asm("add.rn.bf16x2 %0, %1, %2;" : "=r"(o) : "r"(r), "r"(pack_bf16(exp_sat(a), exp_sat(b))));
  return o;
}
DEVI void arrive_both(uint32_t bar, int lane, bool pred = true) {
  asm volatile("{\n.reg .pred p;\n.reg .b32 r;\nsetp.ne.b32 p, %2, 0;\nmapa.shared::cluster.u32 r, %0, %1;\n@p mbarrier.arrive.shared::cluster.b64 _, [r];\n}"
               :: "r"(bar), "r"(lane & 1), "r"((int)(pred && lane < 2)) : "memory");
}
DEVI uint32_t bmul2(uint32_t a, uint32_t b) { uint32_t r; asm("mul.rn.bf16x2 %0, %1, %2;" : "=r"(r) : "r"(a), "r"(b)); return r; }
DEVI uint32_t bfma2(uint32_t a, uint32_t b, uint32_t c) { uint32_t r; asm("fma.rn.bf16x2 %0, %1, %2, %3;" : "=r"(r) : "r"(a), "r"(b), "r"(c)); return r; }
DEVI uint32_t bamax2(uint32_t a, uint32_t b) { uint32_t r; asm("max.NaN.xorsign.abs.bf16x2 %0, %1, %2;" : "=r"(r) : "r"(a), "r"(b)); return r; }
DEVI uint32_t hmul2(uint32_t a, uint32_t b) { uint32_t r; asm("mul.rn.f16x2 %0, %1, %2;" : "=r"(r) : "r"(a), "r"(b)); return r; }
DEVI uint32_t hadd2(uint32_t a, uint32_t b) { uint32_t r; asm("add.rn.f16x2 %0, %1, %2;" : "=r"(r) : "r"(a), "r"(b)); return r; }
DEVI uint32_t hsub2(uint32_t a, uint32_t b) { uint32_t r; asm("sub.rn.f16x2 %0, %1, %2;" : "=r"(r) : "r"(a), "r"(b)); return r; }
DEVI uint32_t hfma2(uint32_t a, uint32_t b, uint32_t c) { uint32_t r; asm("fma.rn.f16x2 %0, %1, %2, %3;" : "=r"(r) : "r"(a), "r"(b), "r"(c)); return r; }
DEVI uint32_t hfnma2(uint32_t a, uint32_t b, uint32_t c) {
  uint32_t r; asm("{\n.reg .b32 n;\nneg.f16x2 n, %1;\nfma.rn.f16x2 %0, n, %2, %3;\n}" : "=r"(r) : "r"(a), "r"(b), "r"(c)); return r;
}
DEVI float bf_lo(uint32_t w) { return __uint_as_float(w << 16); }
DEVI float bf_hi(uint32_t w) { return __uint_as_float(w & 0xffff0000u); }

DEVI uint32_t chan_exponent(const uint32_t* w) {
  uint32_t m[4];
#pragma unroll
  for (int i = 0; i < 4; i++) m[i] = bamax2(w[i], w[i + 4]);
#pragma unroll
  for (int i = 8; i < 32; i++) m[i & 3] = bamax2(m[i & 3], w[i]);
  uint32_t x = bamax2(bamax2(m[0], m[1]), bamax2(m[2], m[3])) & 0x7fff7fffu;
  x = max(x >> 16, x & 0xffffu);
  x = __reduce_max_sync(0xffffffffu, x);
  return min(x >> 7, 251u);
}
DEVI uint32_t to_f16(uint32_t w, uint32_t mul) { const uint32_t y = bmul2(w, mul); return pack_f16(bf_lo(y), bf_hi(y)); }

struct Tile { int j, r; };
DEVI Tile tile_of() {
  int cta; asm volatile("mov.u32 %0, %%ctaid.x;" : "=r"(cta));
  const int cl = cta >> 1, lo = (cl - 4) >> 31, hi = (35 - cl) >> 31;
  const int p = cl - 4 + (lo & (36 + 7 * cl)) + (hi & ((((cl - 36) * 37) >> 8) + 1)), g = p & 7, rr = p >> 3;
  return Tile{(g & 6) | (cta & 1), 2 * rr + (g & 1)};
}

__host__ __device__ constexpr int upiece(int it) {
  for (int m = 0; m < 8; m++) if (U0 + m * UNUM / UDEN == it) return m;
  return -1;
}
__host__ __device__ constexpr bool prew(int it) { return it >= UCV && it < UCV + 4 && it < 31; }

DEVI void twiddle(uint32_t& ore, uint32_t& oim, uint32_t re, uint32_t im, uint32_t c, uint32_t s) {
  ore = hfnma2(im, s, hmul2(re, c));
  oim = hfma2(re, s, hmul2(im, c));
}

__global__ void __cluster_dims__(2, 1, 1) __launch_bounds__(kThreads, 1)
fused_kernel(const __grid_constant__ Params P) {
  extern __shared__ __align__(1024) uint8_t smem[];
  const uint32_t sb = (uint32_t)__cvta_generic_to_shared(smem);
  const int tid = threadIdx.x, lane = tid & 31;
  const int warp = tid >> 5, warpu = __shfl_sync(0xffffffffu, tid >> 5, 0);
  const int cta = blockIdx.x, rho = cta & 1, cl = cta >> 1;
  const uint32_t tstart = clock32();
  auto bar = [&](int i) INL { return sb + SM_BAR + 8u * i; };
  auto load1 = [&](int it, int s, int j, int r, bool mc) INL {
    const uint32_t fb = bar(B_F1 + s), xs = sb + x1_off(it);
    mbar_expect(fb, (it & 1) ? 16384 : 32768);
    tma4d(sb + w1_off(s), &P.w1, 32 * it, 2 * j, 1, fb);
    if (!(it & 1)) {
      if (mc) tma2d_mc(xs + rho * 8192, &P.x, 32 * it, 128 * r + 64 * rho, fb);
      else { tma2d(xs, &P.x, 32 * it, 128 * r, fb); tma2d(xs + 8192, &P.x, 32 * it, 128 * r + 64, fb); }
    }
  };
  TSTAMP(tid == 0, 0); GSTAMP(tid == 0, 62);

  if (warpu == 8 && elect()) {
    prefetch_map(&P.w1); prefetch_map(&P.x);
    for (int i = 0; i < NS1; i++) mbar_init(bar(B_F1 + i), 1);
    fence_async_smem();
    const Tile T = tile_of();
    for (int i = 0; i < EARLY; i++) load1(i, slot1(i), T.j, T.r, false);
    TSTAMP(true, 26);
    asm volatile("fence.mbarrier_init.release.cluster;" ::: "memory");
  }
  if (warpu == 9 && elect()) {
    if (sb != SM_BASE + (rho << 24)) __trap();
#pragma unroll
    for (int i = B_F2; i < B_Q; i++) mbar_init(bar(i), 1);
    mbar_expect(bar(B_H), 32768);
    asm volatile("fence.mbarrier_init.release.cluster;" ::: "memory");
  }
  if (warpu == 10 && elect()) {
#pragma unroll
    for (int i = B_Q; i < B_KVE; i++) mbar_init(bar(i), i < B_E1 ? 1 : 16);
    mbar_expect(bar(B_Q), 32768); mbar_expect(bar(B_U), 16384); mbar_expect(bar(B_MAX), 512);
    asm volatile("fence.mbarrier_init.release.cluster;" ::: "memory");
  }
  if (warpu == 11 && elect()) {
#pragma unroll
    for (int i = B_KVE; i < B_COUNT; i++) mbar_init(bar(i), i < B_OFREE ? 8 : i < B_F2M ? 2 : i == B_F2M ? 3 : i == B_STG ? 4 : 9);
    mbar_expect(bar(B_Y), 16384);
    asm volatile("fence.mbarrier_init.release.cluster;" ::: "memory");
  }
  __syncwarp();
  cluster_sync();

  if (warpu < 8) {
    asm volatile("setmaxnreg.inc.sync.aligned.u32 %0;" :: "n"(232));
    const int wg = warp >> 2, wq = warp & 3, g = lane >> 2, q = lane & 3;
    constexpr uint32_t sbq = SM_BASE >> 4;
    const uint32_t sb = SM_BASE + (rho << 24);
    auto bar = [&](int i) INL { return sb + SM_BAR + 8u * i; };
    const uint32_t wgu = warpu >> 2;
    const uint64_t z64 = P.zero;
    Desc dA(z64, sbq + wgu * 512, 1024, 1), dB(z64, sbq, 1024, 1);
    const int srow = wg * 64 + wq * 16 + (lane & 15);
    const uint32_t stm = srow * 128 + (((lane >> 4) ^ (srow & 7)) << 4);
    auto stage2 = [&](float* acc, int n, bool first) INL {
      const int s = slot2(n);
      mbar_wait(bar(B_F2 + s), par2(n));
      const uint32_t da = s * (ST2 >> 4) + dlo(0, 16), db = s * (ST2 >> 4) + dlo(16384, 8192);
      wg_fence();
      const uint64_t a0 = dA.at(da), b0 = dB.at(db);
      if (first) mma_n128_init(acc, a0, b0); else mma_n128(acc, a0, b0);
#pragma unroll
      for (int kk = 1; kk < 4; kk++) mma_n128(acc, a0 + 2 * kk, b0 + kk * (2048 >> 4));
      wg_commit();
    };
    auto release2 = [&](int n) INL { arrive_both(bar(B_E2 + slot2(n)), lane); };
    auto publish = [&](int b) INL { fence_async_smem(); __syncwarp(); mbar_arrive_if(bar(b), lane == 0); };

    float aq[64];
    uint32_t f1[8], tw[4];
    uint32_t su[2][32], sh[2][32];
    uint32_t x0[4][8], x1[4][8], p0[2][8], p1[2][8], z0[2][8], z1[2][8];
    auto s1 = [&](uint32_t* d, uint32_t base) INL {
      Desc db(z64, sbq + wgu * 1024 + dlo(base, 128), 512, 0);
      mma_s1_init(d, f1, db.v);
      mma_s1(d, f1 + 4, db.at(256 >> 4));
      wg_commit();
    };
    const uint64_t dre = Desc(z64, sbq + dlo(SM_F2 + 512, 128), 256, 0).v, dim = Desc(z64, sbq + dlo(SM_F2, 128), 256, 0).v;
    auto fwd2 = [&](uint32_t (*x)[8], int c) INL {
      uint32_t a[4][8];
#pragma unroll
      for (int t = 0; t < 4; t++) {
        uint32_t* s = (t < 2 ? sh[c >> 1] : su[c >> 1]) + 16 * (c & 1) + 8 * (t & 1);
        pin<8>(s);
#pragma unroll
        for (int i = 0; i < 4; i++) twiddle(a[t][i], a[t][4 + i], s[4 * (i & 1) + (i & 2)], s[4 * (i & 1) + (i & 2) + 1], tw[i & 2], tw[(i & 2) + 1]);
      }
      wg_fence();
#pragma unroll
      for (int t = 0; t < 4; t++) { mma_s2_init(x[t], a[t], dre); mma_s2(x[t], a[t] + 4, dim); }
      wg_commit();
    };
    auto half2 = [&](uint32_t (*x)[8], uint32_t* s) INL {
      uint32_t a[2][8];
      pin<16>(s);
#pragma unroll
      for (int t = 0; t < 2; t++)
#pragma unroll
        for (int i = 0; i < 4; i++) twiddle(a[t][i], a[t][4 + i], s[8 * t + 4 * (i & 1) + (i & 2)], s[8 * t + 4 * (i & 1) + (i & 2) + 1], tw[i & 2], tw[(i & 2) + 1]);
      wg_fence();
#pragma unroll
      for (int t = 0; t < 2; t++) { mma_s2_init(x[t], a[t], dre); mma_s2(x[t], a[t] + 4, dim); }
      wg_commit();
    };
    auto product = [&](uint32_t (*a)[8], uint32_t (*x)[8], int i) INL {
#pragma unroll
      for (int t = 0; t < 4; t++) { pin<2>(x[t] + i); pin<2>(x[t] + 4 + i); }
      auto hr = [&](int l) INL { return x[l >> 1][i + (l & 1)]; };
      auto hi = [&](int l) INL { return x[l >> 1][4 + i + (l & 1)]; };
      auto ur = [&](int l) INL { return x[2 + (l >> 1)][i + (l & 1)]; };
      auto ui = [&](int l) INL { return x[2 + (l >> 1)][4 + i + (l & 1)]; };
      uint32_t gr[4], gi[4];
      gr[0] = hr(0); gi[0] = hi(0);
#pragma unroll
      for (int l = 1; l < 4; l++) { gr[l] = hadd2(hr(l), hi(l - 1)); gi[l] = hsub2(hi(l), hr(l - 1)); }
#pragma unroll
      for (int p = 0; p < 4; p++) {
        uint32_t re = hfnma2(gi[0], ui(p), hmul2(gr[0], ur(p))), im = hfma2(gi[0], ur(p), hmul2(gr[0], ui(p)));
#pragma unroll
        for (int l = 1; l <= p; l++) {
          re = hfnma2(gi[l], ui(p - l), hfma2(gr[l], ur(p - l), re));
          im = hfma2(gi[l], ur(p - l), hfma2(gr[l], ui(p - l), im));
        }
        a[p >> 1][i + (p & 1)] = re; a[p >> 1][4 + i + (p & 1)] = im;
      }
#pragma unroll
      for (int t = 0; t < 2; t++) { pin<2>(a[t] + i); pin<2>(a[t] + 4 + i); }
    };
    auto inv1 = [&](uint32_t (*z)[8], uint32_t (*a)[8]) INL {
      wg_fence();
#pragma unroll
      for (int t = 0; t < 2; t++) { mma_s2_init(z[t], a[t], dre); mma_s2_neg(z[t], a[t] + 4, dim); }
      wg_commit();
    };
    auto zstore = [&](uint32_t (*z)[8], int c) INL {
      const uint32_t zoff = sb + RB + (q >> 1) * (RU + 16 - RB) + (8 * rho + 4 * wg) * 2048 + (4 * (8 * wq + g) + 2 * (q & 1)) * 16;
#pragma unroll
      for (int t = 0; t < 2; t++) {
        uint32_t a[8];
        pin<8>(z[t]);
#pragma unroll
        for (int i = 0; i < 4; i++) twiddle(a[i], a[4 + i], z[t][i], z[t][4 + i], tw[i & 2], tw[(i & 2) + 1]);
        const uint32_t dst = zoff + t * (16384 - rho * 32768) + c * 2048;
        sts128(dst, a[0], a[1], a[2], a[3]);
        sts128(dst + 16, a[4], a[5], a[6], a[7]);
      }
    };
    float kvr[18];
    auto kvstore = [&]() INL {
      const uint32_t dst = sb + R_KV + (warp >> 1) * KV_HEAD + (warp & 1) * 256 + lane * 4;
      pin<18>(kvr);
#pragma unroll
      for (int b = 0; b < 4; b++) { sts32(dst + b * 512, pack_bf16(kvr[4 * b], kvr[4 * b + 1])); sts32(dst + b * 512 + 128, pack_bf16(kvr[4 * b + 2], kvr[4 * b + 3])); }
      sts32(dst + 2048, pack_bf16(kvr[16], kvr[16])); sts32(dst + 2176, pack_bf16(kvr[17], kvr[17]));
      publish(B_KVI);
    };
    {
      float ak[64], av[64];
      Desc dK(z64, sbq + wgu * 256, 1024, 1);
      auto kstep = [&](int it) INL {
        const int s = slot1(it);
        if (!prew(it - 1)) mbar_wait(bar(B_F1 + s), (it / NS1) & 1);
        TSTAMP(tid == 0 && it == 0, 1);
        const uint32_t dx = dlo(x1_off(it) + (it & 1) * 64, 16), dk = dlo(w1_off(s), 16), dv = dlo(w1_off(s) + 8192, 4096);
        if (s == 0) { dK.renew(z64); dA.renew(z64); dB.renew(z64); }
        wg_fence();
        if (it == 0) { mma_kt_init(ak, dK.at(dk), dB.at(dx)); mma_n128_init(av, dA.at(dx), dB.at(dv)); }
        else { mma_kt(ak, dK.at(dk), dB.at(dx)); mma_n128(av, dA.at(dx), dB.at(dv)); }
        mma_kt(ak, dK.at(dk + (2048 >> 4)), dB.at(dx + 2));
        mma_n128(av, dA.at(dx + 2), dB.at(dv + (2048 >> 4)));
        wg_commit();
        wg_wait<1>();
        if (it > 0) arrive_both(bar(B_E1 + (s + NS1 - 1) % NS1), lane);
        if (prew(it)) mbar_wait(bar(B_F1 + slot1(it + 1)), ((it + 1) / NS1) & 1);
        KSTAMP(it);
      };
      uint32_t kk[35], u[32], sw[4], mx[16], um, umul, ud, eu;
      unsigned short dskip;
      float tap0;
      const bool local = (g >> 2) == rho;
      auto calcu = [&](int e0, int e1) INL {
#pragma unroll
        for (int e = e0; e < e1; e++) {
          pin<1>(kk + 3 + e); pin<1>(u + e);
          u[e] = bmul2(bfma2(kk[3 + e], sw[0], bfma2(kk[2 + e], sw[1], bfma2(kk[1 + e], sw[2], bmul2(kk[e], sw[3])))), u[e]);
          um = bamax2(um, u[e]);
          pin<1>(u + e);
        }
        pin<1>(&um);
      };
      ldg128(sw, P.shift_k + (cl * 16 + 2 * g) * 4);
#pragma unroll
      for (int e = 0; e < 3; e++) kk[e] = ldg32(P.k_ptr + (1021 + e) * 1024 + 16 * cl + 2 * g);
      asm volatile("ld.global.nc.b16 %0, [%1];" : "=h"(dskip) : "l"(P.ssm_d + 8 * cta + warp));
      auto side = [&](int it) INL {
        if (it == 1) {
          pin<4>(sw);
          const uint32_t t0 = __byte_perm(sw[0], sw[2], 0x5410), t1 = __byte_perm(sw[0], sw[2], 0x7632), t2 = __byte_perm(sw[1], sw[3], 0x5410);
          sw[3] = __byte_perm(sw[1], sw[3], 0x7632); sw[0] = t0; sw[1] = t1; sw[2] = t2;
          const bool halo = rho && warp + q == 0;
#pragma unroll
          for (int e = 0; e < 3; e++) kk[e] = halo ? kk[e] : 0u;
          tap0 = lane == 0 ? bf_lo(dskip) : 0.f;
          um = 0;
          pin<4>(sw); pin<3>(kk); pin<1>(&tap0);
        }
        if (upiece(it - 1) >= 0) {
          const int m = upiece(it - 1);
          calcu(m == 0 ? 3 : 4 * m, 4 * m + 4);
          if (m < 4) mbar_arrive_if(bar(B_KVE + m), lane == 0);
          if (m == 7) {
            pin<3>(kk);
            calcu(0, 3);
            um = bamax2(um, __shfl_xor_sync(0xffffffffu, um, 1));
            um = bamax2(um, __shfl_xor_sync(0xffffffffu, um, 2));
            st_async1_if(mapa(sb + SM_MAX + g * 64 + (8 * rho + warp) * 4, q & 1), um, mapa(bar(B_MAX), q & 1), q < 2);
          }
        }
        if (upiece(it) >= 0) {
          const int m = upiece(it);
          const uint32_t a = sb + RU + (m & 3) * 8192 + warp * 128 + q * 32 + g * 4;
          mbar_wait(bar(B_KVL + (m & 3)), m >> 2);
#pragma unroll
          for (int e = 0; e < 4; e++) { kk[3 + 4 * m + e] = lds32(a + e * 1024); u[4 * m + e] = lds32(a + 4096 + e * 1024); }
          if (m == 7) {
#pragma unroll
            for (int e = 0; e < 3; e++)
              asm volatile("{\n.reg .pred p;\nsetp.ne.b32 p, %2, 0;\n@p ld.shared.b32 %0, [%1];\n}" : "+r"(kk[e]) : "r"(a + (e + 1) * 1024 - 32), "r"(warp + q));
          }
        }
        if (it == UCV - 1 - UPRE) {
          mbar_wait(bar(B_MAX), 0);
          TSTAMP(tid == 0, 5);
#pragma unroll
          for (int i = 0; i < 4; i++) lds128(mx + 4 * i, sb + SM_MAX + g * 64 + i * 16);
        }
        if (it == UCV - UPRE) {
          pin<16>(mx);
#pragma unroll
          for (int i = 4; i < 16; i++) mx[i & 3] = bamax2(mx[i & 3], mx[i]);
          const uint32_t e2 = __vminu2((bamax2(bamax2(mx[0], mx[1]), bamax2(mx[2], mx[3])) >> 7) & 0x00ff00ffu, 0x00fb00fbu);
          umul = (0x00fd00fdu - e2) << 7;
          eu = (__shfl_sync(0xffffffffu, e2, 16 * rho + 4 * (warp >> 1)) >> (16 * (warp & 1))) & 0xffu;
          ud = mapa(sb + RU + (g & 3) * 8192 + (2 * rho + wg) * 1024 + (4 * wq + q) * 16, g >> 2);
        }
        if (it >= UCV && it < UCV + 4) {
          const int i = it - UCV;
          uint32_t* y = u + 8 * i;
          pin<8>(y);
#pragma unroll
          for (int e = 0; e < 8; e++) y[e] = bmul2(y[e], umul);
          const uint32_t dst = ud + (i & 1) * 512 + (i >> 1) * 256, ub = mapa(bar(B_U), rho ^ 1);
          st_either4(local, dst, pack_f16(bf_lo(y[0]), bf_lo(y[1])), pack_f16(bf_lo(y[2]), bf_lo(y[3])), pack_f16(bf_lo(y[4]), bf_lo(y[5])), pack_f16(bf_lo(y[6]), bf_lo(y[7])), ub);
          st_either4(local, dst + 4096, pack_f16(bf_hi(y[0]), bf_hi(y[1])), pack_f16(bf_hi(y[2]), bf_hi(y[3])), pack_f16(bf_hi(y[4]), bf_hi(y[5])), pack_f16(bf_hi(y[6]), bf_hi(y[7])), ub);
        }
      };
#pragma unroll
      for (int it = 0; it < 32; it++) { kstep(it); side(it); }
      auto qstep = [&](int n) INL {
        if ((n & 3) == 0) { dA.renew(z64); dB.renew(z64); }
        stage2(aq, n, n == 0);
        wg_wait<1>();
        if (n == 0) arrive_both(bar(B_E1 + NS1 - 1), lane); else release2(n - 1);
        QSTAMP(n);
      };
      uint32_t pk[32];
      auto phik = [&](int i0, int i1) INL {
#pragma unroll
        for (int i = i0; i < i1; i++) { pin<2>(ak + 2 * i); pk[i] = phi2(ak[2 * i], ak[2 * i + 1]); pin<1>(pk + i); }
      };
      auto vst = [&](int kt) INL {
        float* a = av + 8 * kt;
        pin<8>(a);
        stsm4(sb + RA + (kt >> 2) * 16384 + (stm ^ ((kt & 3) << 5)), pack_bf16(a[0], a[1]), pack_bf16(a[2], a[3]), pack_bf16(a[4], a[5]), pack_bf16(a[6], a[7]));
      };
      float dkv[36];
      Desc dV(z64, sbq + wgu * (1024u - (1024u << 16)) + dlo(RA, SM_ONES - RA), 1024, 1);
      auto kvmma = [&](int k0, int k1) INL {
        wg_fence();
#pragma unroll
        for (int ks = k0; ks < k1; ks++) {
          const uint64_t db = dV.at(ks * (128u - (128u << 16)));
          if (ks == 0) mma_kv_init(dkv, pk, db); else mma_kv(dkv, pk + 4 * ks, db);
        }
        wg_commit();
      };
      float* gacc;
      auto kvred = [&](int b) INL {
        const bool hh = wq >> 1;
        asm volatile("red.relaxed.gpu.global.add.v4.f32 [%0], {%1,%2,%3,%4};" :: "l"(gacc + b * 128), "f"(hh ? dkv[16 + 4 * b] : dkv[4 * b]),
                     "f"(hh ? dkv[17 + 4 * b] : dkv[1 + 4 * b]), "f"(hh ? dkv[18 + 4 * b] : dkv[2 + 4 * b]), "f"(hh ? dkv[19 + 4 * b] : dkv[3 + 4 * b]) : "memory");
        if (b == 3) {
          asm volatile("{\n.reg .pred p;\nsetp.eq.s32 p, %3, 0;\n@p red.relaxed.gpu.global.add.v2.f32 [%0], {%1,%2};\n}"
                       :: "l"(gacc + 4096 - warp * 496 - g * 14), "f"(dkv[32]), "f"(dkv[34]), "r"(q) : "memory");
          __syncwarp();
          mbar_arrive_if(bar(B_KVP), lane == 0);
          TSTAMP(tid == 0, 4);
        }
      };
      auto consts = [&]() INL {
        ldg128(f1, d_tab + (tid & 127) * 4); ldg128(f1 + 4, d_tab + 512 + (tid & 127) * 4); ldg128(tw, d_tab + 1024 + (tid & 127) * 4);
        gacc = &g_kv[tile_of().j][warp * 512 + lane * 4];
      };
      uint32_t w[32], hmul;
      auto hload = [&](int i0, int i1) INL {
        const uint32_t a = sb + RB + warp * 4096 + (((lane >> 2) & 1) + (lane & 2) + 4 * (lane & 1) + (((lane << 2) ^ lane) & 24)) * 16;
#pragma unroll
        for (int i = i0; i < i1; i++) lds128(w + 4 * i, a + i * 512);
      };
      auto hmax = [&]() INL {
        pin<32>(w);
        tap0 += bf_lo(w[0]);
        w[0] = pack_bf16(tap0, bf_hi(w[0]));
        hmul = (252u - chan_exponent(w)) * 0x00800080u;
        const int e = min(max((int)(eu + 128 - (hmul >> 23)), 0), 254);
        asm volatile("st.shared.b16 [%0], %1;" :: "r"(sb + SM_SCALE + 2 * warp), "h"((unsigned short)(e << 7)) : "memory");
      };
      auto hstore = [&](int i0, int i1) INL {
        const uint32_t dst = sb + RB + warp * 4096 + (lane & 6) * 128 + ((lane ^ ((lane >> 2) & 6)) & 7) * 16;
#pragma unroll
        for (int i = i0; i < i1; i++) {
          pin<4>(w + 4 * i);
          const uint32_t w0 = i == 0 ? pack_f16(tap0 * bf_lo(hmul), bf_hi(w[0]) * bf_lo(hmul)) : to_f16(w[4 * i], hmul);
          sts128(dst + (i >> 1) * 1024 + (i & 1) * 128, w0, to_f16(w[4 * i + 1], hmul), to_f16(w[4 * i + 2], hmul), to_f16(w[4 * i + 3], hmul));
        }
      };
      auto kvload = [&]() INL {
        mbar_wait(bar(B_KV), 0);
        TSTAMP(tid == 0, 7);
#pragma unroll
        for (int b = 0; b < 4; b++)
          asm volatile("ld.global.cg.v4.f32 {%0,%1,%2,%3}, [%4];" : "=f"(kvr[4 * b]), "=f"(kvr[4 * b + 1]), "=f"(kvr[4 * b + 2]), "=f"(kvr[4 * b + 3]) : "l"(gacc + b * 128) : "memory");
        asm volatile("ld.global.cg.v2.f32 {%0,%1}, [%2];" : "=f"(kvr[16]), "=f"(kvr[17]) : "l"(gacc + 4096 - warp * 496 - g * 14 - q * 4) : "memory");
      };
      qstep(0);
      TSTAMP(tid == 0, 2);
      phik(0, 4);
      mbar_wait(bar(B_E1 + NS1 - 1), 1);
      vst(0); vst(1); vst(2);
      qstep(1);
      vst(3); vst(4); vst(5); phik(4, 8);
      qstep(2);
      vst(6); vst(7);
      publish(B_VST);
      phik(8, 14);
      qstep(3);
      mbar_wait(bar(B_ZERO), 0);
      mbar_wait(bar(B_VST), 0);
      kvmma(0, 3);
      consts();
      phik(14, 24);
      qstep(4);
      kvmma(3, 6);
      mbar_wait(bar(B_H), 0);
      hload(0, 4);
      phik(24, 32);
      kvmma(6, 8);
      hload(4, 8);
      constexpr int N0 = 5;
      TSTAMP(tid == 0, 3);
      qstep(N0);
      pin<36>(dkv);
      mbar_arrive_if(bar(B_KVM), lane == 0);
      hmax();
      kvred(0);
      qstep(N0 + 1);
      mbar_wait(bar(B_U2), 0);
      if (REDF) kvred(1);
      wg_fence(); s1(su[0], RU);
      hstore(0, 4);
      kvred(1 + REDF);
      qstep(N0 + 2);
      hstore(4, 7);
      kvred(2 + REDF);
      qstep(N0 + 3);
      hstore(7, 8);
      if (DELEG) { __syncwarp(); mbar_arrive_if(bar(B_VST), lane == 0); } else publish(B_VST);
      if (!REDF) kvred(3);
      mbar_wait(bar(B_F2M), 0);
      half2(x0 + 2, su[0]);
      qstep(N0 + 4);
      if (DELEG) mbar_wait(bar(B_U2), 1); else mbar_wait(bar(B_VST), 1);
      wg_fence(); s1(sh[0], RB);
      half2(x1 + 2, su[0] + 16);
      qstep(N0 + 5);
      half2(x0, sh[0]); half2(x1, sh[0] + 16);
#pragma unroll
      for (int n = N0 + 6; n < 16; n++) {
        qstep(n);
        if (n == KVS) kvstore();
        if (n == KVL) kvload();
        if (n < N0 + 10) product(n < N0 + 8 ? p0 : p1, n < N0 + 8 ? x0 : x1, 2 * ((n - N0) & 1));
      }
    }

    float acc[64];
    {
      uint32_t pq[4][8];
      float dn[4][20];
      Desc dO(z64, sbq + dlo(R_KV, 128), 512, 0);
      auto phiq = [&](int h) INL {
        pin<16>(aq + 16 * h);
#pragma unroll
        for (int i = 0; i < 8; i++) pq[h][i] = phi2(aq[16 * h + 2 * i], aq[16 * h + 2 * i + 1]);
        pin<8>(pq[h]);
      };
      auto omma = [&](int h) INL {
        wg_fence();
        mma_o_init(dn[h], pq[h], dO.at(h * KV_HEAD >> 4));
        mma_o(dn[h], pq[h] + 4, dO.at((h * KV_HEAD + 256) >> 4));
        wg_commit();
      };
      auto onorm = [&](int h) INL {
        pin<20>(dn[h]);
        const float i0 = rcp(dn[h][16] + 1e-6f), i1 = rcp(dn[h][18] + 1e-6f);
#pragma unroll
        for (int hf = 0; hf < 2; hf++) {
          const float* a = dn[h] + 8 * hf;
          stsm4(sb + (h >> 1) * ST2 + (stm ^ (((h & 1) * 2 + hf) << 5)), pack_bf16(a[0] * i0, a[1] * i0), pack_bf16(a[2] * i1, a[3] * i1),
                pack_bf16(a[4] * i0, a[5] * i0), pack_bf16(a[6] * i1, a[7] * i1));
        }
        if (h & 1) publish(B_OW + (h >> 1));
      };
      wg_fence();
      s1(su[1], RU + 8192);
      if (KVS == 16) kvstore();
      wg_wait<1>();
      release2(15);
      TSTAMP(tid == 0, 6);
      auto own = [&](int c) INL { if (c == 0) { dA.renew(z64); dB.renew(z64); } mbar_wait(bar(B_OW + c), 0); stage2(acc, 16 + c, c == 0); };
      auto s1done = [&]() INL { mbar_arrive_if(bar(B_S1), lane == 0); };
      uint32_t gf[4][4];
#define WKV mbar_wait(bar(B_KVI), 0)
#define W(n) wg_wait<n>()
#define S1H wg_fence(); s1(sh[1], RB + 8192)
#define T8 TSTAMP(tid == 0, 8)
#define T9 TSTAMP(tid == 0, 9)
#define WS1 mbar_wait(bar(B_S1), 0)
#define PR(p, x) product(p, x, 0); product(p, x, 2)
#define FIN PR(p0, x0); inv1(z0, p0); own(1); W(2); release2(16)
      phiq(0); phiq(1); WKV; omma(0); omma(1); W(1); onorm(0); W(0); onorm(1); T8; S1H; phiq(2); omma(2); phiq(3); W(0); onorm(2); s1done(); omma(3); inv1(z0, p0); W(1); onorm(3); T9; inv1(z1, p1); fwd2(x0, 2); W(1); WS1; zstore(z0, 0); zstore(z1, 1); W(0); own(0); fwd2(x1, 3); FIN;
      ldg128(gf[1], d_tab + 1536 + (tid & 127) * 4); ldg128(gf[3], d_tab + 2048 + (tid & 127) * 4);
      product(p1, x1, 0); product(p1, x1, 2);
      inv1(z1, p1);
      if (S18 == 3) { stage2(acc, 18, false); wg_wait<3>(); } else wg_wait<2>();
      zstore(z0, 2);
#pragma unroll
      for (int i = 0; i < 4; i += 2) {
        pin<4>(gf[i + 1]);
        gf[i][0] = gf[i][1] = gf[i + 1][0]; gf[i][2] = gf[i][3] = gf[i + 1][1];
        gf[i + 1][0] = gf[i + 1][1] = gf[i + 1][2]; gf[i + 1][2] = gf[i + 1][3];
        pin<4>(gf[i]); pin<4>(gf[i + 1]);
      }
      if (S18 == 1) { stage2(acc, 18, false); wg_wait<1>(); } else if (S18 == 3) wg_wait<1>(); else wg_wait<0>();
      release2(17);
      zstore(z1, 3);
      publish(B_ZST);
      TSTAMP(tid == 0, 10);
      if (S18 == 2) stage2(acc, 18, false);
      mbar_wait(bar(B_ZST), 0);
      float y[64];
      {
        Desc db(z64, sbq + wgu * ((RU + 16 - RB) >> 4) + dlo(RB, 128), 2048, 0);
        wg_fence();
        mma_i2_init(y, gf[0], db.v, 0xEEEE4444u);
#pragma unroll
        for (int i = 1; i < 4; i++) mma_i2(y, gf[i], db.at(i * (512 >> 4)), 0xEEEE4444u);
        wg_commit();
      }
      uint32_t sc[4];
      lds128(sc, sb + SM_SCALE);
      TSTAMP(tid == 0, 11);
      constexpr int NY = S18 ? 19 : 18;
      stage2(acc, NY, false);
      TSTAMP(tid == 0, 13);
      wg_wait<1>();
      if (S18) release2(18);
      arrive_both(bar(B_I2), lane);
      pin<64>(y);
      uint32_t yv[8][4];
#pragma unroll
      for (int i = 0; i < 8; i++)
#pragma unroll
        for (int m = 0; m < 4; m++) yv[i][m] = bmul2(pack_bf16(y[32 * (i >> 2) + (i & 3) + 8 * m], y[32 * (i >> 2) + (i & 3) + 8 * m + 4]), sc[m]);
      pin<32>(&yv[0][0]);
      stage2(acc, NY + 1, false);
      wg_wait<1>();
      release2(NY);
      mbar_wait(bar(B_I2), 0);
      const uint32_t ya = sb + tid * 16 + warp * 1536;
      const uint32_t yr = mapa((ya + Y_IN) ^ 64, rho ^ 1), yb = mapa(bar(B_Y), rho ^ 1);
#pragma unroll
      for (int i = 0; i < 4; i++) {
        sts128(ya + Y_OWN + i * 512, yv[i][0], yv[i][1], yv[i][2], yv[i][3]);
        st_async4(yr + i * 512, yv[4 + i][0], yv[4 + i][1], yv[4 + i][2], yv[4 + i][3], yb);
      }
      __syncwarp();
      mbar_arrive_if(bar(B_Y), lane == 0);
      TSTAMP(tid == 0, 12);
    }
#pragma unroll 1
    for (int n = S18 ? 21 : 20; n < 32 - TAIL; n++) {
      stage2(acc, n, false);
      TSTAMP(tid == 0 && n == 26, 14);
      wg_wait<1>();
      release2(n - 1);
      QSTAMP(n);
    }
    {
      const Tile T = tile_of();
      dA.renew(z64); dB.renew(z64);
      if (TAIL > 1) mbar_wait(bar(B_STG), wgu ^ 1);
#pragma unroll
      for (int n = 32 - TAIL; n < 32; n++) {
        if (n == 31 && TAILE) mbar_arrive_if(bar(B_STG), wgu == 0 && lane == 0);
        stage2(acc, n, false);
      }
      if (!TAILE) mbar_arrive_if(bar(B_STG), wgu == 0 && lane == 0);
      mbar_wait(bar(B_E2 + 5), 1);
      wg_wait<0>();
      TSTAMP(tid == 0, 17); TSTAMP(tid == 128, 15);
      pin<64>(acc);
#pragma unroll
      for (int c = 0; c < 2; c++) {
#pragma unroll
        for (int t = 0; t < 4; t++) {
          const float* a = acc + 32 * c + 8 * t;
          stsm4(sb + RB + c * 16384 + (stm ^ (t << 5)), pack_bf16(a[0], a[1]), pack_bf16(a[2], a[3]), pack_bf16(a[4], a[5]), pack_bf16(a[6], a[7]));
        }
        fence_async_smem();
        __syncwarp();
        tma2d_store_e(&P.outa, sb + RB + c * 16384 + warpu * 2048, 128 * T.j + 64 * c, 128 * T.r + 16 * warpu);
      }
      bulk_wait_read();
      TSTAMP(tid == 128, 16);
    }
    if (ENDS) { __syncwarp(); cluster_sync(); }
  } else {
    asm volatile("setmaxnreg.dec.sync.aligned.u32 %0;" :: "n"(40));
    const Tile T = tile_of();
    const int j = T.j, r = T.r;
    auto kcol = [&](int n) INL {
      return n < 20 ? 128 * (j ^ ((n >> 1) & 1)) + 64 * (n & 1) : 128 * (((j & 6) + n - (n < 26 ? 18 : 24)) & 7) + (n < 26 ? 0 : 64);
    };
    if (warpu == 8) {
      uint32_t ph = 0;
      int s = slot1(EARLY);
#pragma unroll 1
      for (int it = EARLY; it < 32; ++it, s = s + 1 == NS1 ? 0 : s + 1) {
        if (it >= NS1) { mbar_wait(bar(B_E1 + s), (ph >> s) & 1); ph ^= 1u << s; }
        if (elect()) load1(it, s, j, r, true);
      }
#pragma unroll 1
      for (int n = 0; n < 16; ++n) {
        const int s = n & 3, i = n + (n >> 1);
        mbar_wait(bar(n < 4 ? B_E1 + i : B_E2 + s), n < 4 ? (ph >> i) & 1 : ((n >> 2) - 1) & 1);
        const uint32_t st = sb + s * ST2, fb = bar(B_F2 + s);
        if (elect()) {
          mbar_expect(fb, ST2);
          tma4d(st + 16384, &P.w2, 64 * n, 2 * j, 0, fb);
          tma2d_mc(st + rho * 8192, &P.x, 64 * n, 128 * r + 64 * rho, fb);
        }
      }
      auto loadw = [&](int n) INL {
        const int s = n & 3;
        mbar_wait(bar(B_E2 + s), ((n >> 2) - 1) & 1);
        if (elect()) { mbar_expect(bar(B_F2 + s), n < 18 ? 16384 : ST2); tma4d(sb + s * ST2 + 16384, &P.wo, kcol(n), 2 * j, 0, bar(B_F2 + s)); }
      };
#pragma unroll 1
      for (int n = 16; n < 21; ++n) {
        if (elect()) for (int w = (QSCH >> (4 * n - 64)) & 15; w < ((QSCH >> (4 * n - 60)) & 15); w++) tma5d(sb + RA + w * 4096, &P.q, 16 * cl, 2 * rho, w & 4, w & 3, bar(B_Q));
        if (n < 20) loadw(n);
      }
#pragma unroll 1
      for (int n = 18; n < 20; ++n) {
        const uint32_t st = sb + (n & 3) * ST2, fb = bar(B_F2 + (n & 3));
        mbar_wait(bar(B_RDY + n - 18), 0);
        asm volatile("fence.proxy.async.global;" ::: "memory");
        if (elect()) { tma2d(st, &P.o, kcol(n), 128 * r, fb); tma2d(st + 8192, &P.o, kcol(n), 128 * r + 64, fb); }
      }
#pragma unroll 1
      for (int n = 20; n < 32; ++n) {
        const int s = slot2(n), kc = 128 * (((j & 6) + n - (n < 26 ? 18 : 24)) & 7) + (n < 26 ? 0 : 64);
        const uint32_t st = sb + s * ST2, fb = bar(B_F2 + s);
        if (n < 22) mbar_wait(bar(B_OFREE + s), 0);
        mbar_wait(bar(B_RDY + n - 18), 0);
        mbar_wait(bar(n == 22 ? B_I2 : B_E2 + s), n == 22 ? 0 : par2(n) ^ 1);
        if (elect()) {
          mbar_expect(fb, ST2);
          tma4d(st + 16384, &P.wo, kc, 2 * j, 0, fb);
          tma2d_mc(st + rho * 8192, &P.o, kc, 128 * r + 64 * rho, fb);
        }
      }
    } else {
      const int at = tid - 288, aw = warpu - 9;
      if (at < KV_WORDS / 64) reinterpret_cast<float4*>(&g_kv[j][r * (KV_WORDS / 16)])[at] = make_float4(0.f, 0.f, 0.f, 0.f);
      for (int i = at; i < 128; i += 96) sts128(sb + SM_ONES + i * 16, 0x3f803f80u, 0x3f803f80u, 0x3f803f80u, 0x3f803f80u);
      fence_async_smem();
      bar_sync(4, 96);
      if (at == 64) asm volatile("fence.release.gpu;\nred.relaxed.gpu.global.add.u32 [%0], 1;" :: "l"(&g_zflag[j * 32]) : "memory");
      const unsigned epoch = ld_relaxed(&g_epoch[cta]);
      if (aw == 1) {
#pragma unroll 1
        for (int m = 0; m < 16; m++) {
          const int s = (m >> 1) & 3;
          pace(tstart, PREP0 + m * PREPGAP);
          if (m >= 8) mbar_wait(bar(B_KVE + s), 0);
          if (elect()) {
            if (!(m & 1)) mbar_expect(bar(B_KVL + s), 8192);
            tma3d(sb + RU + (m & 7) * 4096, (m & 1) ? &P.v : &P.k, 16 * cl, 32 * rho, 2 * (m & 14), bar(B_KVL + s));
          }
        }
#pragma unroll 1
        for (int m = 0; m < 8; m++) {
          pace(tstart, HT0 + m * HGAP);
          if (elect()) bulk_load(sb + RB + m * 4096, P.ssm_k + (size_t)(8 * cta + m) * 2048, 4096, bar(B_H));
        }
      }
      if (at == 0) { flag_wait(&g_zflag[j * 32], 16u * (epoch + 1)); mbar_arrive(bar(B_ZERO)); }
      __syncwarp();
      if (at < 80) pf_line(d_tab + at * 32);
      if (aw == 2) {
        if (elect()) { prefetch_map(&P.w2); prefetch_map(&P.wo); prefetch_map(&P.o); prefetch_map(&P.q); prefetch_map(&P.outb); prefetch_map(&P.outa); }
#pragma unroll 1
        for (int m = 0; m < 16; m++) {
          pace(tstart, m < 4 ? WQT + m * 500 : QT + (m - 4) * QGAP);
          pf_line(m < 4 ? P.w_ptr + (size_t)(cta + (2 * m + (lane >> 4)) * 128) * 3072 + (lane & 15) * 64
                        : (m < 12 ? P.q_ptr + cta * 16384 - 8192 : P.wo_ptr + cta * 8192 - 24576) + m * 2048 + lane * 64);
        }
      }
      uint32_t f2[4];
      ldg128(f2, d_tab + 2560 + at * 4);
      if (at == 0) { mbar_wait_long(bar(B_U), 0); fence_async_smem(); mbar_arrive(bar(B_U2)); }
      mbar_wait_long(bar(B_KVM), 0);
      sts128(sb + SM_F2 + at * 16, f2[0], f2[1], f2[2], f2[3]);
      fence_async_smem();
      __syncwarp();
      mbar_arrive_if(bar(B_F2M), lane == 0);
      if (DELEG && at == 0) { mbar_wait_long(bar(B_VST), 1); fence_async_smem(); mbar_arrive(bar(B_U2)); }
      if (at == 64) {
        mbar_wait(bar(B_KVP), 0);
        asm volatile("fence.release.gpu;\nred.relaxed.gpu.global.add.u32 [%0], 1;" :: "l"(&g_kvflag[j * 32]) : "memory");
        TSTAMP(true, 18);
        flag_wait(&g_kvflag[j * 32], 16u * (epoch + 1));
        mbar_arrive(bar(B_KV));
        TSTAMP(true, 19);
      }
      __syncwarp();
      if (aw < 2) {
        mbar_wait_long(bar(B_OW + aw), 0);
        if (elect()) {
          const uint32_t src = sb + aw * ST2;
          tma2d_store(&P.o, src, 128 * j + 64 * aw, 128 * r);
          tma2d_store(&P.o, src + 8192, 128 * j + 64 * aw, 128 * r + 64);
          bulk_commit();
          bulk_wait_all();
          TSTAMP(aw == 0, 21);
          asm volatile("mbarrier.arrive.shared::cluster.b64 _, [%0];\nmbarrier.arrive.shared::cluster.b64 _, [%1];"
                       :: "r"(mapa(bar(B_OFREE + aw), 0)), "r"(mapa(bar(B_OFREE + aw), 1)) : "memory");
          asm volatile("fence.release.gpu;\nst.relaxed.gpu.global.u32 [%0], %1;" :: "l"(&g_oflag[r * 32 + 2 * j + aw]), "r"(epoch + 1) : "memory");
          asm volatile("mbarrier.arrive.shared::cluster.b64 _, [%0];" :: "r"(mapa(bar(B_RDY + aw), rho ^ 1)) : "memory");
          TSTAMP(aw == 0, 22); TSTAMP(aw == 1, 23);
          if (aw == 1) for (int w = 5; w < 8; w++) tma5d(sb + RA + w * 4096, &P.q, 16 * cl, 2 * rho, w & 4, w & 3, bar(B_Q));
        }
        __syncwarp();
      } else {
        const unsigned* fp = &g_oflag[r * 32 + (kcol(18 + min(lane, 13)) >> 6)];
        bool done = lane > 13 || lane < 2;
        mbar_wait_long(bar(B_OW), 0);
        for (int i = 0; !__all_sync(0xffffffffu, done) && i < kSpinLimit; i++) {
          const bool now = !done && (int)(ld_relaxed(fp) - epoch) > 0;
          if (__any_sync(0xffffffffu, now)) {
            asm volatile("fence.acquire.gpu;\nfence.proxy.async.global;" ::: "memory");
            mbar_arrive_if(bar(B_RDY + lane), now);
            TSTAMP(lane == 2 && now, 24);
          }
          done |= now;
        }
        if (lane == 0) g_epoch[cta] = epoch + 1;
        TSTAMP(lane == 0, 25);
      }
      mbar_wait(bar(B_Q), 0);
      mbar_wait_long(bar(B_Y), 0);
      TSTAMP(at == 0, 20);
      const uint32_t ya = sb + (((lane & 1) == rho ? Y_OWN : Y_IN + 64) ^ ((lane >> 1) * 16));
#pragma unroll 1
      for (int u = PU * aw; u < 32; u += 3 * PU) {
        const uint32_t t0 = clock32();
#pragma unroll
        for (int i = 0; i < PU; i++) {
          const uint32_t qa = sb + RA + (u + i) * 1024 + lane * 16, yu = ya + (u + i) * 512;
          uint32_t qv[2][4], yv[2][4];
#pragma unroll
          for (int h = 0; h < 2; h++) { lds128(qv[h], qa + h * 512); lds128(yv[h], yu + h * 256); }
#pragma unroll
          for (int h = 0; h < 2; h++) sts128(qa + h * 512, bmul2(qv[h][0], yv[h][0]), bmul2(qv[h][1], yv[h][1]), bmul2(qv[h][2], yv[h][2]), bmul2(qv[h][3], yv[h][3]));
        }
        fence_async_smem();
        __syncwarp();
        if (elect()) tma5d_store(&P.outb, sb + RA + u * 1024, 1024 + 16 * cl, 2 * rho, (u >> 4) * 4 + (u & 3), (u >> 2) & 3);
        if (POSTGAP) pace(t0, POSTGAP);
      }
      bulk_wait_read();
      TSTAMP(at == 0, 27);
    }
    if (ENDS) { __syncwarp(); cluster_sync(); }
  }
  TSTAMP(tid == 128, 61); GSTAMP(tid == 128, 63);
}

typedef CUresult (*EncodeFn)(CUtensorMap*, CUtensorMapDataType, cuuint32_t, void*, const cuuint64_t*, const cuuint64_t*,
                             const cuuint32_t*, const cuuint32_t*, CUtensorMapInterleave, CUtensorMapSwizzle,
                             CUtensorMapL2promotion, CUtensorMapFloatOOBfill);

void encode(EncodeFn fn, CUtensorMap* m, const void* p, int rank, const cuuint64_t* dims, const cuuint64_t* strides,
            const cuuint32_t* box, CUtensorMapSwizzle sw, int prom = 0) {
  const cuuint32_t es[5] = {1, 1, 1, 1, 1};
  fn(m, CU_TENSOR_MAP_DATA_TYPE_BFLOAT16, rank, const_cast<void*>(p), dims, strides, box, es, CU_TENSOR_MAP_INTERLEAVE_NONE, sw,
     (CUtensorMapL2promotion)prom, CU_TENSOR_MAP_FLOAT_OOB_FILL_NONE);
}
void encode2d(EncodeFn fn, CUtensorMap* m, const void* p, uint64_t cols, uint64_t rows, uint32_t bc, uint32_t br, CUtensorMapSwizzle sw, int prom = 0) {
  const cuuint64_t dims[2] = {cols, rows}, strides[1] = {cols * 2};
  const cuuint32_t box[2] = {bc, br};
  encode(fn, m, p, 2, dims, strides, box, sw, prom);
}
void encode3d(EncodeFn fn, CUtensorMap* m, const void* p) {
  const cuuint64_t dims[3] = {1024, 64, 32}, strides[2] = {2048 * 32, 2048};
  const cuuint32_t box[3] = {16, 32, 4};
  encode(fn, m, p, 3, dims, strides, box, CU_TENSOR_MAP_SWIZZLE_NONE);
}
void encode4d(EncodeFn fn, CUtensorMap* m, const void* p, uint64_t cols, uint32_t rows, uint32_t nmat) {
  const cuuint64_t dims[4] = {64, 1024, 16, cols / 1024}, strides[3] = {cols * 2, 128, 2048};
  const cuuint32_t box[4] = {64, rows, 2, nmat};
  encode(fn, m, p, 4, dims, strides, box, CU_TENSOR_MAP_SWIZZLE_128B);
}
void encode5d(EncodeFn fn, CUtensorMap* m, const void* p, uint64_t cols, uint32_t n) {
  const cuuint64_t dims[5] = {cols, 4, 16, 8, 4}, strides[4] = {cols * 2 * 512, cols * 2 * 8, cols * 2, cols * 2 * 128};
  const cuuint32_t box[5] = {16, 2, 16, n, 1};
  encode(fn, m, p, 5, dims, strides, box, CU_TENSOR_MAP_SWIZZLE_NONE);
}

}

extern "C" void kernel_launch(void* const* d_in, const int* in_sizes, int n_in, void* d_out, int out_size) {
  static EncodeFn fn = nullptr;
  static void* o_ptr = nullptr;
  if (!fn) {
    cudaDriverEntryPointQueryResult qr;
    cudaGetDriverEntryPoint("cuTensorMapEncodeTiled", (void**)&fn, cudaEnableDefault, &qr);
    cudaGetSymbolAddress(&o_ptr, g_o);
    cudaFuncSetAttribute(fused_kernel, cudaFuncAttributeMaxDynamicSharedMemorySize, SM_TOTAL);
  }
  Params P;
  encode4d(fn, &P.w1, d_in[1], 3072, 32, 2);
  encode2d(fn, &P.x, d_in[0], 1024, 2048, 64, 64, CU_TENSOR_MAP_SWIZZLE_128B);
  encode4d(fn, &P.w2, d_in[1], 3072, 64, 1);
  encode4d(fn, &P.wo, d_in[2], 1024, 64, 1);
  encode2d(fn, &P.o, o_ptr, 1024, 2048, 64, 64, CU_TENSOR_MAP_SWIZZLE_128B);
  encode2d(fn, &P.outa, d_out, 2048, 2048, 64, 16, CU_TENSOR_MAP_SWIZZLE_128B);
  encode3d(fn, &P.k, d_in[4]);
  encode3d(fn, &P.v, d_in[5]);
  encode5d(fn, &P.q, d_in[3], 1024, 4);
  encode5d(fn, &P.outb, d_out, 2048, PU);
  P.shift_k = (const __nv_bfloat16*)d_in[6];
  P.ssm_k = (const __nv_bfloat16*)d_in[7];
  P.ssm_d = (const __nv_bfloat16*)d_in[8];
  P.q_ptr = (const __nv_bfloat16*)d_in[3];
  P.k_ptr = (const __nv_bfloat16*)d_in[4];
  P.w_ptr = (const __nv_bfloat16*)d_in[1];
  P.wo_ptr = (const __nv_bfloat16*)d_in[2];
  P.zero = 0;
  fused_kernel<<<kCtas, kThreads, SM_TOTAL>>>(P);
}
```

```cpp
#include <cuda.h>
#include <cuda_runtime.h>
#include <cuda_bf16.h>
#include <stdint.h>

#define DEVI __device__ __forceinline__
#define INL __attribute__((always_inline))

namespace {

DEVI void mma_kt_init(float* d, uint64_t da, uint64_t db) {
  asm volatile("{\nwgmma.mma_async.sync.aligned.m64n128k16.f32.bf16.bf16 {%0, %1, %2, %3, %4, %5, %6, %7, %8, %9, %10, %11, %12, %13, %14, %15, %16, %17, %18, %19, %20, %21, %22, %23, %24, %25, %26, %27, %28, %29, %30, %31, %32, %33, %34, %35, %36, %37, %38, %39, %40, %41, %42, %43, %44, %45, %46, %47, %48, %49, %50, %51, %52, %53, %54, %55, %56, %57, %58, %59, %60, %61, %62, %63}, %64, %65, 0, 1, 1, 1, 0;\n}\n"
    : "=f"(d[0]), "=f"(d[1]), "=f"(d[2]), "=f"(d[3]), "=f"(d[4]), "=f"(d[5]), "=f"(d[6]), "=f"(d[7]), "=f"(d[8]), "=f"(d[9]), "=f"(d[10]), "=f"(d[11]), "=f"(d[12]), "=f"(d[13]), "=f"(d[14]), "=f"(d[15]), "=f"(d[16]), "=f"(d[17]), "=f"(d[18]), "=f"(d[19]), "=f"(d[20]), "=f"(d[21]), "=f"(d[22]), "=f"(d[23]), "=f"(d[24]), "=f"(d[25]), "=f"(d[26]), "=f"(d[27]), "=f"(d[28]), "=f"(d[29]), "=f"(d[30]), "=f"(d[31]), "=f"(d[32]), "=f"(d[33]), "=f"(d[34]), "=f"(d[35]), "=f"(d[36]), "=f"(d[37]), "=f"(d[38]), "=f"(d[39]), "=f"(d[40]), "=f"(d[41]), "=f"(d[42]), "=f"(d[43]), "=f"(d[44]), "=f"(d[45]), "=f"(d[46]), "=f"(d[47]), "=f"(d[48]), "=f"(d[49]), "=f"(d[50]), "=f"(d[51]), "=f"(d[52]), "=f"(d[53]), "=f"(d[54]), "=f"(d[55]), "=f"(d[56]), "=f"(d[57]), "=f"(d[58]), "=f"(d[59]), "=f"(d[60]), "=f"(d[61]), "=f"(d[62]), "=f"(d[63])
    : "l"(da), "l"(db));
}
DEVI void mma_kt(float* d, uint64_t da, uint64_t db) {
  asm volatile("{\nwgmma.mma_async.sync.aligned.m64n128k16.f32.bf16.bf16 {%0, %1, %2, %3, %4, %5, %6, %7, %8, %9, %10, %11, %12, %13, %14, %15, %16, %17, %18, %19, %20, %21, %22, %23, %24, %25, %26, %27, %28, %29, %30, %31, %32, %33, %34, %35, %36, %37, %38, %39, %40, %41, %42, %43, %44, %45, %46, %47, %48, %49, %50, %51, %52, %53, %54, %55, %56, %57, %58, %59, %60, %61, %62, %63}, %64, %65, 1, 1, 1, 1, 0;\n}\n"
    : "+f"(d[0]), "+f"(d[1]), "+f"(d[2]), "+f"(d[3]), "+f"(d[4]), "+f"(d[5]), "+f"(d[6]), "+f"(d[7]), "+f"(d[8]), "+f"(d[9]), "+f"(d[10]), "+f"(d[11]), "+f"(d[12]), "+f"(d[13]), "+f"(d[14]), "+f"(d[15]), "+f"(d[16]), "+f"(d[17]), "+f"(d[18]), "+f"(d[19]), "+f"(d[20]), "+f"(d[21]), "+f"(d[22]), "+f"(d[23]), "+f"(d[24]), "+f"(d[25]), "+f"(d[26]), "+f"(d[27]), "+f"(d[28]), "+f"(d[29]), "+f"(d[30]), "+f"(d[31]), "+f"(d[32]), "+f"(d[33]), "+f"(d[34]), "+f"(d[35]), "+f"(d[36]), "+f"(d[37]), "+f"(d[38]), "+f"(d[39]), "+f"(d[40]), "+f"(d[41]), "+f"(d[42]), "+f"(d[43]), "+f"(d[44]), "+f"(d[45]), "+f"(d[46]), "+f"(d[47]), "+f"(d[48]), "+f"(d[49]), "+f"(d[50]), "+f"(d[51]), "+f"(d[52]), "+f"(d[53]), "+f"(d[54]), "+f"(d[55]), "+f"(d[56]), "+f"(d[57]), "+f"(d[58]), "+f"(d[59]), "+f"(d[60]), "+f"(d[61]), "+f"(d[62]), "+f"(d[63])
    : "l"(da), "l"(db));
}
DEVI void mma_n128_init(float* d, uint64_t da, uint64_t db) {
  asm volatile("{\nwgmma.mma_async.sync.aligned.m64n128k16.f32.bf16.bf16 {%0, %1, %2, %3, %4, %5, %6, %7, %8, %9, %10, %11, %12, %13, %14, %15, %16, %17, %18, %19, %20, %21, %22, %23, %24, %25, %26, %27, %28, %29, %30, %31, %32, %33, %34, %35, %36, %37, %38, %39, %40, %41, %42, %43, %44, %45, %46, %47, %48, %49, %50, %51, %52, %53, %54, %55, %56, %57, %58, %59, %60, %61, %62, %63}, %64, %65, 0, 1, 1, 0, 1;\n}\n"
    : "=f"(d[0]), "=f"(d[1]), "=f"(d[2]), "=f"(d[3]), "=f"(d[4]), "=f"(d[5]), "=f"(d[6]), "=f"(d[7]), "=f"(d[8]), "=f"(d[9]), "=f"(d[10]), "=f"(d[11]), "=f"(d[12]), "=f"(d[13]), "=f"(d[14]), "=f"(d[15]), "=f"(d[16]), "=f"(d[17]), "=f"(d[18]), "=f"(d[19]), "=f"(d[20]), "=f"(d[21]), "=f"(d[22]), "=f"(d[23]), "=f"(d[24]), "=f"(d[25]), "=f"(d[26]), "=f"(d[27]), "=f"(d[28]), "=f"(d[29]), "=f"(d[30]), "=f"(d[31]), "=f"(d[32]), "=f"(d[33]), "=f"(d[34]), "=f"(d[35]), "=f"(d[36]), "=f"(d[37]), "=f"(d[38]), "=f"(d[39]), "=f"(d[40]), "=f"(d[41]), "=f"(d[42]), "=f"(d[43]), "=f"(d[44]), "=f"(d[45]), "=f"(d[46]), "=f"(d[47]), "=f"(d[48]), "=f"(d[49]), "=f"(d[50]), "=f"(d[51]), "=f"(d[52]), "=f"(d[53]), "=f"(d[54]), "=f"(d[55]), "=f"(d[56]), "=f"(d[57]), "=f"(d[58]), "=f"(d[59]), "=f"(d[60]), "=f"(d[61]), "=f"(d[62]), "=f"(d[63])
    : "l"(da), "l"(db));
}
DEVI void mma_n128(float* d, uint64_t da, uint64_t db) {
  asm volatile("{\nwgmma.mma_async.sync.aligned.m64n128k16.f32.bf16.bf16 {%0, %1, %2, %3, %4, %5, %6, %7, %8, %9, %10, %11, %12, %13, %14, %15, %16, %17, %18, %19, %20, %21, %22, %23, %24, %25, %26, %27, %28, %29, %30, %31, %32, %33, %34, %35, %36, %37, %38, %39, %40, %41, %42, %43, %44, %45, %46, %47, %48, %49, %50, %51, %52, %53, %54, %55, %56, %57, %58, %59, %60, %61, %62, %63}, %64, %65, 1, 1, 1, 0, 1;\n}\n"
    : "+f"(d[0]), "+f"(d[1]), "+f"(d[2]), "+f"(d[3]), "+f"(d[4]), "+f"(d[5]), "+f"(d[6]), "+f"(d[7]), "+f"(d[8]), "+f"(d[9]), "+f"(d[10]), "+f"(d[11]), "+f"(d[12]), "+f"(d[13]), "+f"(d[14]), "+f"(d[15]), "+f"(d[16]), "+f"(d[17]), "+f"(d[18]), "+f"(d[19]), "+f"(d[20]), "+f"(d[21]), "+f"(d[22]), "+f"(d[23]), "+f"(d[24]), "+f"(d[25]), "+f"(d[26]), "+f"(d[27]), "+f"(d[28]), "+f"(d[29]), "+f"(d[30]), "+f"(d[31]), "+f"(d[32]), "+f"(d[33]), "+f"(d[34]), "+f"(d[35]), "+f"(d[36]), "+f"(d[37]), "+f"(d[38]), "+f"(d[39]), "+f"(d[40]), "+f"(d[41]), "+f"(d[42]), "+f"(d[43]), "+f"(d[44]), "+f"(d[45]), "+f"(d[46]), "+f"(d[47]), "+f"(d[48]), "+f"(d[49]), "+f"(d[50]), "+f"(d[51]), "+f"(d[52]), "+f"(d[53]), "+f"(d[54]), "+f"(d[55]), "+f"(d[56]), "+f"(d[57]), "+f"(d[58]), "+f"(d[59]), "+f"(d[60]), "+f"(d[61]), "+f"(d[62]), "+f"(d[63])
    : "l"(da), "l"(db));
}
DEVI void mma_kv_init(float* d, const uint32_t* a, uint64_t db) {
  asm volatile("{\nwgmma.mma_async.sync.aligned.m64n72k16.f32.bf16.bf16 {%0, %1, %2, %3, %4, %5, %6, %7, %8, %9, %10, %11, %12, %13, %14, %15, %16, %17, %18, %19, %20, %21, %22, %23, %24, %25, %26, %27, %28, %29, %30, %31, %32, %33, %34, %35}, {%36,%37,%38,%39}, %40, 0, 1, 1, 1;\n}\n"
    : "=f"(d[0]), "=f"(d[1]), "=f"(d[2]), "=f"(d[3]), "=f"(d[4]), "=f"(d[5]), "=f"(d[6]), "=f"(d[7]), "=f"(d[8]), "=f"(d[9]), "=f"(d[10]), "=f"(d[11]), "=f"(d[12]), "=f"(d[13]), "=f"(d[14]), "=f"(d[15]), "=f"(d[16]), "=f"(d[17]), "=f"(d[18]), "=f"(d[19]), "=f"(d[20]), "=f"(d[21]), "=f"(d[22]), "=f"(d[23]), "=f"(d[24]), "=f"(d[25]), "=f"(d[26]), "=f"(d[27]), "=f"(d[28]), "=f"(d[29]), "=f"(d[30]), "=f"(d[31]), "=f"(d[32]), "=f"(d[33]), "=f"(d[34]), "=f"(d[35])
    : "r"(a[0]), "r"(a[1]), "r"(a[2]), "r"(a[3]), "l"(db));
}
DEVI void mma_kv(float* d, const uint32_t* a, uint64_t db) {
  asm volatile("{\nwgmma.mma_async.sync.aligned.m64n72k16.f32.bf16.bf16 {%0, %1, %2, %3, %4, %5, %6, %7, %8, %9, %10, %11, %12, %13, %14, %15, %16, %17, %18, %19, %20, %21, %22, %23, %24, %25, %26, %27, %28, %29, %30, %31, %32, %33, %34, %35}, {%36,%37,%38,%39}, %40, 1, 1, 1, 1;\n}\n"
    : "+f"(d[0]), "+f"(d[1]), "+f"(d[2]), "+f"(d[3]), "+f"(d[4]), "+f"(d[5]), "+f"(d[6]), "+f"(d[7]), "+f"(d[8]), "+f"(d[9]), "+f"(d[10]), "+f"(d[11]), "+f"(d[12]), "+f"(d[13]), "+f"(d[14]), "+f"(d[15]), "+f"(d[16]), "+f"(d[17]), "+f"(d[18]), "+f"(d[19]), "+f"(d[20]), "+f"(d[21]), "+f"(d[22]), "+f"(d[23]), "+f"(d[24]), "+f"(d[25]), "+f"(d[26]), "+f"(d[27]), "+f"(d[28]), "+f"(d[29]), "+f"(d[30]), "+f"(d[31]), "+f"(d[32]), "+f"(d[33]), "+f"(d[34]), "+f"(d[35])
    : "r"(a[0]), "r"(a[1]), "r"(a[2]), "r"(a[3]), "l"(db));
}
DEVI void mma_o_init(float* d, const uint32_t* a, uint64_t db) {
  asm volatile("{\nwgmma.mma_async.sync.aligned.m64n40k16.f32.bf16.bf16 {%0, %1, %2, %3, %4, %5, %6, %7, %8, %9, %10, %11, %12, %13, %14, %15, %16, %17, %18, %19}, {%20,%21,%22,%23}, %24, 0, 1, 1, 1;\n}\n"
    : "=f"(d[0]), "=f"(d[1]), "=f"(d[2]), "=f"(d[3]), "=f"(d[4]), "=f"(d[5]), "=f"(d[6]), "=f"(d[7]), "=f"(d[8]), "=f"(d[9]), "=f"(d[10]), "=f"(d[11]), "=f"(d[12]), "=f"(d[13]), "=f"(d[14]), "=f"(d[15]), "=f"(d[16]), "=f"(d[17]), "=f"(d[18]), "=f"(d[19])
    : "r"(a[0]), "r"(a[1]), "r"(a[2]), "r"(a[3]), "l"(db));
}
DEVI void mma_o(float* d, const uint32_t* a, uint64_t db) {
  asm volatile("{\nwgmma.mma_async.sync.aligned.m64n40k16.f32.bf16.bf16 {%0, %1, %2, %3, %4, %5, %6, %7, %8, %9, %10, %11, %12, %13, %14, %15, %16, %17, %18, %19}, {%20,%21,%22,%23}, %24, 1, 1, 1, 1;\n}\n"
    : "+f"(d[0]), "+f"(d[1]), "+f"(d[2]), "+f"(d[3]), "+f"(d[4]), "+f"(d[5]), "+f"(d[6]), "+f"(d[7]), "+f"(d[8]), "+f"(d[9]), "+f"(d[10]), "+f"(d[11]), "+f"(d[12]), "+f"(d[13]), "+f"(d[14]), "+f"(d[15]), "+f"(d[16]), "+f"(d[17]), "+f"(d[18]), "+f"(d[19])
    : "r"(a[0]), "r"(a[1]), "r"(a[2]), "r"(a[3]), "l"(db));
}
DEVI void mma_s1_init(uint32_t* d, const uint32_t* a, uint64_t db) {
  asm volatile("{\nwgmma.mma_async.sync.aligned.m64n128k16.f16.f16.f16 {%0, %1, %2, %3, %4, %5, %6, %7, %8, %9, %10, %11, %12, %13, %14, %15, %16, %17, %18, %19, %20, %21, %22, %23, %24, %25, %26, %27, %28, %29, %30, %31}, {%32,%33,%34,%35}, %36, 0, 1, 1, 1;\n}\n"
    : "=r"(d[0]), "=r"(d[1]), "=r"(d[2]), "=r"(d[3]), "=r"(d[4]), "=r"(d[5]), "=r"(d[6]), "=r"(d[7]), "=r"(d[8]), "=r"(d[9]), "=r"(d[10]), "=r"(d[11]), "=r"(d[12]), "=r"(d[13]), "=r"(d[14]), "=r"(d[15]), "=r"(d[16]), "=r"(d[17]), "=r"(d[18]), "=r"(d[19]), "=r"(d[20]), "=r"(d[21]), "=r"(d[22]), "=r"(d[23]), "=r"(d[24]), "=r"(d[25]), "=r"(d[26]), "=r"(d[27]), "=r"(d[28]), "=r"(d[29]), "=r"(d[30]), "=r"(d[31])
    : "r"(a[0]), "r"(a[1]), "r"(a[2]), "r"(a[3]), "l"(db));
}
DEVI void mma_s1(uint32_t* d, const uint32_t* a, uint64_t db) {
  asm volatile("{\nwgmma.mma_async.sync.aligned.m64n128k16.f16.f16.f16 {%0, %1, %2, %3, %4, %5, %6, %7, %8, %9, %10, %11, %12, %13, %14, %15, %16, %17, %18, %19, %20, %21, %22, %23, %24, %25, %26, %27, %28, %29, %30, %31}, {%32,%33,%34,%35}, %36, 1, 1, 1, 1;\n}\n"
    : "+r"(d[0]), "+r"(d[1]), "+r"(d[2]), "+r"(d[3]), "+r"(d[4]), "+r"(d[5]), "+r"(d[6]), "+r"(d[7]), "+r"(d[8]), "+r"(d[9]), "+r"(d[10]), "+r"(d[11]), "+r"(d[12]), "+r"(d[13]), "+r"(d[14]), "+r"(d[15]), "+r"(d[16]), "+r"(d[17]), "+r"(d[18]), "+r"(d[19]), "+r"(d[20]), "+r"(d[21]), "+r"(d[22]), "+r"(d[23]), "+r"(d[24]), "+r"(d[25]), "+r"(d[26]), "+r"(d[27]), "+r"(d[28]), "+r"(d[29]), "+r"(d[30]), "+r"(d[31])
    : "r"(a[0]), "r"(a[1]), "r"(a[2]), "r"(a[3]), "l"(db));
}
DEVI void mma_s2_init(uint32_t* d, const uint32_t* a, uint64_t db) {
  asm volatile("{\nwgmma.mma_async.sync.aligned.m64n32k16.f16.f16.f16 {%0, %1, %2, %3, %4, %5, %6, %7}, {%8,%9,%10,%11}, %12, 0, 1, 1, 0;\n}\n"
    : "=r"(d[0]), "=r"(d[1]), "=r"(d[2]), "=r"(d[3]), "=r"(d[4]), "=r"(d[5]), "=r"(d[6]), "=r"(d[7])
    : "r"(a[0]), "r"(a[1]), "r"(a[2]), "r"(a[3]), "l"(db));
}
DEVI void mma_s2(uint32_t* d, const uint32_t* a, uint64_t db) {
  asm volatile("{\nwgmma.mma_async.sync.aligned.m64n32k16.f16.f16.f16 {%0, %1, %2, %3, %4, %5, %6, %7}, {%8,%9,%10,%11}, %12, 1, 1, 1, 0;\n}\n"
    : "+r"(d[0]), "+r"(d[1]), "+r"(d[2]), "+r"(d[3]), "+r"(d[4]), "+r"(d[5]), "+r"(d[6]), "+r"(d[7])
    : "r"(a[0]), "r"(a[1]), "r"(a[2]), "r"(a[3]), "l"(db));
}
DEVI void mma_s2_neg(uint32_t* d, const uint32_t* a, uint64_t db) {
  asm volatile("{\nwgmma.mma_async.sync.aligned.m64n32k16.f16.f16.f16 {%0, %1, %2, %3, %4, %5, %6, %7}, {%8,%9,%10,%11}, %12, 1, -1, 1, 0;\n}\n"
    : "+r"(d[0]), "+r"(d[1]), "+r"(d[2]), "+r"(d[3]), "+r"(d[4]), "+r"(d[5]), "+r"(d[6]), "+r"(d[7])
    : "r"(a[0]), "r"(a[1]), "r"(a[2]), "r"(a[3]), "l"(db));
}
DEVI void mma_i2_init(float* d, const uint32_t* a, uint64_t db, uint32_t meta) {
  asm volatile("{\nwgmma.mma_async.sp.sync.aligned.m64n128k32.f32.f16.f16 {%0, %1, %2, %3, %4, %5, %6, %7, %8, %9, %10, %11, %12, %13, %14, %15, %16, %17, %18, %19, %20, %21, %22, %23, %24, %25, %26, %27, %28, %29, %30, %31, %32, %33, %34, %35, %36, %37, %38, %39, %40, %41, %42, %43, %44, %45, %46, %47, %48, %49, %50, %51, %52, %53, %54, %55, %56, %57, %58, %59, %60, %61, %62, %63}, {%64,%65,%66,%67}, %68, %69, 0, 0, 1, 1, 1;\n}\n"
    : "=f"(d[0]), "=f"(d[1]), "=f"(d[2]), "=f"(d[3]), "=f"(d[4]), "=f"(d[5]), "=f"(d[6]), "=f"(d[7]), "=f"(d[8]), "=f"(d[9]), "=f"(d[10]), "=f"(d[11]), "=f"(d[12]), "=f"(d[13]), "=f"(d[14]), "=f"(d[15]), "=f"(d[16]), "=f"(d[17]), "=f"(d[18]), "=f"(d[19]), "=f"(d[20]), "=f"(d[21]), "=f"(d[22]), "=f"(d[23]), "=f"(d[24]), "=f"(d[25]), "=f"(d[26]), "=f"(d[27]), "=f"(d[28]), "=f"(d[29]), "=f"(d[30]), "=f"(d[31]), "=f"(d[32]), "=f"(d[33]), "=f"(d[34]), "=f"(d[35]), "=f"(d[36]), "=f"(d[37]), "=f"(d[38]), "=f"(d[39]), "=f"(d[40]), "=f"(d[41]), "=f"(d[42]), "=f"(d[43]), "=f"(d[44]), "=f"(d[45]), "=f"(d[46]), "=f"(d[47]), "=f"(d[48]), "=f"(d[49]), "=f"(d[50]), "=f"(d[51]), "=f"(d[52]), "=f"(d[53]), "=f"(d[54]), "=f"(d[55]), "=f"(d[56]), "=f"(d[57]), "=f"(d[58]), "=f"(d[59]), "=f"(d[60]), "=f"(d[61]), "=f"(d[62]), "=f"(d[63])
    : "r"(a[0]), "r"(a[1]), "r"(a[2]), "r"(a[3]), "l"(db), "r"(meta));
}
DEVI void mma_i2(float* d, const uint32_t* a, uint64_t db, uint32_t meta) {
  asm volatile("{\nwgmma.mma_async.sp.sync.aligned.m64n128k32.f32.f16.f16 {%0, %1, %2, %3, %4, %5, %6, %7, %8, %9, %10, %11, %12, %13, %14, %15, %16, %17, %18, %19, %20, %21, %22, %23, %24, %25, %26, %27, %28, %29, %30, %31, %32, %33, %34, %35, %36, %37, %38, %39, %40, %41, %42, %43, %44, %45, %46, %47, %48, %49, %50, %51, %52, %53, %54, %55, %56, %57, %58, %59, %60, %61, %62, %63}, {%64,%65,%66,%67}, %68, %69, 0, 1, 1, 1, 1;\n}\n"
    : "+f"(d[0]), "+f"(d[1]), "+f"(d[2]), "+f"(d[3]), "+f"(d[4]), "+f"(d[5]), "+f"(d[6]), "+f"(d[7]), "+f"(d[8]), "+f"(d[9]), "+f"(d[10]), "+f"(d[11]), "+f"(d[12]), "+f"(d[13]), "+f"(d[14]), "+f"(d[15]), "+f"(d[16]), "+f"(d[17]), "+f"(d[18]), "+f"(d[19]), "+f"(d[20]), "+f"(d[21]), "+f"(d[22]), "+f"(d[23]), "+f"(d[24]), "+f"(d[25]), "+f"(d[26]), "+f"(d[27]), "+f"(d[28]), "+f"(d[29]), "+f"(d[30]), "+f"(d[31]), "+f"(d[32]), "+f"(d[33]), "+f"(d[34]), "+f"(d[35]), "+f"(d[36]), "+f"(d[37]), "+f"(d[38]), "+f"(d[39]), "+f"(d[40]), "+f"(d[41]), "+f"(d[42]), "+f"(d[43]), "+f"(d[44]), "+f"(d[45]), "+f"(d[46]), "+f"(d[47]), "+f"(d[48]), "+f"(d[49]), "+f"(d[50]), "+f"(d[51]), "+f"(d[52]), "+f"(d[53]), "+f"(d[54]), "+f"(d[55]), "+f"(d[56]), "+f"(d[57]), "+f"(d[58]), "+f"(d[59]), "+f"(d[60]), "+f"(d[61]), "+f"(d[62]), "+f"(d[63])
    : "r"(a[0]), "r"(a[1]), "r"(a[2]), "r"(a[3]), "l"(db), "r"(meta));
}
__device__ const __align__(128) uint32_t d_tab[2944] = {
  0x3bf13bff,0x2fbd25e4,0x38ee3986,0x3a4d39c9,0x3b9a3bcf,0x34ff32f7,0x3737384a,0x3b243ac1,0x3af73b52,0x37dd3676,0x344b35c8,0x3bb53b76,
  0x3a113a8c,0x39373899,0x2cce3185,0x3bfa3be1,0x3a933bf2,0x388e2f59,0xb1b6b8f8,0xbbdfba45,0xa452374e,0x3c003b1e,0x39c034e7,0xb990bb9e,
  0xbabab7c8,0x38553afe,0x3bd23bb2,0x32c6b463,0xbb57bbf9,0xb65f2d33,0x35df3a19,0x3b71392e,0x37643bd4,0x3b183294,0xb4cf385f,0x3ba13ab3,
  0xbbaeb648,0x347b3b5c,0xbb04bb6c,0xb7b235f7,0xad97ba9b,0xbbf8b884,0x3924b1e8,0xba21bbdd,0x3bf439b8,0x2ef5b999,0x39023c00,0x3a3d217f,
  0x9cb63ba5,0x3c0034b7,0x39afb77a,0xb9a1bb13,0xb86abbab,0xbaac3493,0xb2633b0a,0x3bd7379b,0x3b60391b,0x3631ba29,0xb60ebbf7,0xbb682dfb,
  0xbbdaae91,0x32193bf5,0x3aa23a35,0x387ab90c,0xb7853b65,0x3b10361a,0xbba73625,0x34ab3b63,0x3911baa9,0xba31b86f,0x3bf6b24b,0xae5fbbd8,
  0xba2d39aa,0x391639a6,0xbbf61648,0xae2d3c00,0x3b0db874,0xb790baa5,0x3ba93232,0x349fbbd9,0xba9e3b16,0x387f376f,0x3bdcb4c3,0x3201bba3,
  0x3b6aaec3,0x3602bbf5,0xb63cb907,0xbb5e3a39,0xb27cba25,0xbbd6391f,0xb8653bf8,0x3ab02dc9,0xb99d3bac,0x39b33487,0x3c00b7a6,0x9fdbbb07,
  0xbbf33ab6,0x2f27385a,0xba4132ad,0xb8fd3bd3,0xad653994,0x3bf9b9bc,0xba1d3c00,0x3929a311,0x3bb0b889,0x346fba97,0x37bd31cf,0x3b01bbde,
  0x3759bb59,0xbb1b3654,0x3b9fbb6f,0xb4dbb5eb,0xbb733a49,0xb5d438f3,0x366baf8b,0x3b54bbf2,0xbbd03bfa,0x32de2d00,0x3abdb933,0x3850ba15,
  0xb98b3afb,0x39c5b7d2,0x3c00bbb3,0xa51bb457,0xb19e3742,0x3be0bb21,0x3a90bb9c,0xb89434f3,0xb93c39cd,0xba0d3982,0x2c9c26ad,0xbbfb3bff,
  0xb7e8389e,0xbaf43a89,0x343eb16c,0xbbb73be2,0xb50b3682,0xbb983b4f,0x372cb5bc,0xbb273b78,0xafef330f,0xbbf03bce,0x38eab845,0xba503ac4,
  0xb3403946,0xbbcb3a04,0xb83a2c38,0x3acbbbfc,0x3979b426,0xb9d63bba,0xbbff3aee,0x281fb7fe,0x3be4bb94,0x313b3523,0xb8a83b2c,0xba813715,
  0x3699ba58,0x3b4ab8e0,0x35a53029,0xbb7c3bef,0x340e38b2,0xbbbd3a7a,0x3ae8b109,0xb80a3be6,0x3b32bb45,0x36ff36af,0x353abb81,0x3b90b58d,
  0xb8d6b371,0x3a60bbc8,0xbbed3830,0x305bbad1,0xb94f3bfe,0xb9fca8e8,0x2ba739df,0xbbfc3970,0x39663815,0xb9e73ae1,0xbbfe33eb,0x29b1bbc0,
  0xb0d7bb37,0x3be8b6e8,0x3a733552,0xb8bc3b8b,0xb6c63beb,0xbb3fb08d,0xb576ba67,0x3b85b8cc,0x3ad8b9f4,0x38253958,0xb3a23bfd,0xbbc52ade,
  0x3b8736dd,0xb56a3b3a,0x3b3db55e,0x36d23b89,0xbbe9b3d3,0x30bebbc2,0xba6f381a,0xb8c1bade,0x3bfe2a7a,0x2a163bfd,0x3962b95d,0x39eb39f0,
  0xbbc330a6,0xb3babbea,0xb8203a6b,0xbadbb8c7,0x3bec3581,0x30743b83,0xb8d136bb,0xba64bb42,0xb6f438b7,0xbb35ba76,0xb546bbe7,0x3b8e30f0,
  0xb80fbbfe,0x3ae5a94d,0x3bbf396b,0xb40239e3,0x3bfd382a,0xab433ad5,0xb9f83389,0xb954bbc6,0x3a7e341a,0x38ad3bbc,0x3122b805,0x3be53aeb,
  0x39da3bfc,0xb974ac06,0x3bff3a00,0x2884394a,0xb8353042,0xbacebbee,0x33593a5c,0xbbc9b8db,0xbb7fbb92,0x3599b52f,0xbb47b70a,0xb6a4bb2f,
  0x37213153,0x3b2a3be3,0x351738a3,0xbb96ba85,0x3af1397d,0x37f339d2,0xb4322776,0xbbb8bbff,0x3bfb3bcc,0xac6a3328,0xba09b840,0xb941bac7,
  0x3a543b7a,0xb8e5b5b1,0xbbefbb4c,0xb010b68d,0x32f72fbd,0xbbcfbbf1,0x3ac13a4d,0xb84ab8ee,0x367634ff,0xbb52bb9a,0x3b763b24,0xb5c8b737,
  0x389937dd,0xba8cbaf7,0x3be13bb5,0xb185b44b,0x39c93937,0xb986ba11,0x3bff3bfa,0x25e4acce,0x392e32c6,0xba19bbd2,0xbbf9baba,0x2d333855,
  0x3bf23b71,0x2f59b5df,0xb8f8bb57,0xba45b65f,0x374e3a93,0x3b1e388e,0x34e7b1b6,0xbb9ebbdf,0xb7c8a452,0x3afe3c00,0x3bb239c0,0xb463b990,
  0x3b6c34cf,0xb5f7bba1,0x3b5c3b18,0x3648b764,0x31e83b04,0x3bdd37b2,0xb884347b,0x3a9b3bae,0xbc00b924,0xa17f3a21,0xb999bbf8,0xb9b82d97,
  0x3294b902,0xbbd4ba3d,0x3ab32ef5,0xb85fbbf4,0x3bf53631,0x2e91bb60,0xb90cbb68,0xba35360e,0xbb133219,0x377a3bda,0x3ba5387a,0x34b7baa2,
  0x379bb9a1,0xbb0ab9af,0xbbab9cb6,0x34933c00,0x2dfb3bd7,0x3bf73263,0x391bb86a,0xba29baac,0x3aa93785,0x386fbb10,0x324b3ba7,0x3bd8b4ab,
  0xb9aab911,0xb9a63a31,0x9648bbf6,0xbc002e5f,0x38743a2d,0x3aa5b916,0xb2323bf6,0x3bd92e2d,0xb625bb0d,0xbb633790,0x361abba9,0xbb65b49f,
  0x37a63865,0x3b07bab0,0x3487bbd6,0xbbac327c,0x376fbc00,0xbb161fdb,0xbba339b3,0x34c3399d,0xbbf5387f,0x2ec33a9e,0x3a393201,0x3907bbdc,
  0x391f3602,0x3a25bb6a,0x2dc9bb5e,0xbbf8363c,0x231138fd,0x3c00ba41,0xb9943bf3,0x39bcaf27,0x3bdeb929,0x31cfba1d,0x38892d65,0x3a97bbf9,
  0x35ebbb01,0xbb6f37bd,0x3b59bbb0,0xb654b46f,0xbab634db,0xb85a3b9f,0xb2adb759,0xbbd33b1b,0xb742398b,0x3b21b9c5,0x3b9cbc00,0xb4f3251b,
  0x2f8b319e,0x3bf2bbe0,0x38f3ba90,0xba493894,0x3933b66b,0x3a15bb54,0x2d00b5d4,0xbbfa3b73,0x3bb3babd,0x3457b850,0xb7d232de,0xbafb3bd0,
  0xba893a0d,0x389eb93c,0xbbe23bfb,0xb16c2c9c,0xbb4f3af4,0x3682b7e8,0xbb783bb7,0xb5bc343e,0xbbce3b98,0x330fb50b,0xbac43b27,0xb845372c,
  0xbbff3bf0,0x26adafef,0xb9cd3a50,0xb98238ea,0xbbef3a81,0x3029b8a8,0x3a58bbe4,0x38e0b13b,0xb9463b7c,0xba0435a5,0xac38b699,0x3bfcbb4a,
  0x34263340,0xbbba3bcb,0xbaee383a,0x37febacb,0x3b94b979,0xb52339d6,0xbb2c3bff,0xb715a81f,0xbb813ae8,0xb58db80a,0xb6af3bbd,0xbb45340e,
  0x3830353a,0xbad13b90,0x3bc8b6ff,0xb3713b32,0x39dfbbed,0x3970305b,0x28e8ba60,0x3bfeb8d6,0xba7a2ba7,0x38b2bbfc,0xbbe639fc,0xb109b94f,
  0xb9583b3f,0xb9f4b6c6,0xaadebb85,0x3bfdb576,0x3bc0b825,0x33eb3ad8,0xb8153bc5,0xbae1b3a2,0xbb8ba9b1,0x3552bbfe,0x3b37b966,0x36e839e7,
  0x38cc38bc,0xba673a73,0xbbeb30d7,0x308dbbe8,0xb3d33b87,0xbbc2b56a,0x381a3b3d,0xbade36d2,0x2a7abbe9,0x3bfd30be,0xb95dba6f,0x39f0b8c1,
  0x30a63bfe,0xbbea2a16,0x3a6b3962,0xb8c739eb,0xb55ebbc3,0x3b89b3ba,0xbb3ab820,0x36ddbadb,0x33893bbf,0xbbc6b402,0xbad5bae5,0x382ab80f,
  0xbb83b9f8,0x3581b954,0x3b422b43,0x36bb3bfd,0x3a76b074,0x38b73bec,0xb0f03a64,0xbbe7b8d1,0x294d3b35,0xbbfeb6f4,0xb9e3bb8e,0x396bb546,
  0x394a3be5,0xba00b122,0x3bfc3a7e,0xac0638ad,0xb8db2884,0xba5cbbff,0x304239da,0xbbeeb974,0xbb2fbbc9,0x370ab359,0xbb92b835,0xb52fbace,
  0x341ab6a4,0x3bbc3b47,0xb805bb7f,0x3aeb3599,0x3b7a3bfb,0xb5b1ac6a,0xbb4cba09,0xb68db941,0x38a33a54,0xba85b8e5,0xbbe3bbef,0x3153b010,
  0x27763517,0xbbffbb96,0xb9d2bb2a,0x397d3721,0xb840b432,0xbac7bbb8,0xb328b7f3,0x3bcc3af1,0x3be23bfb,0x316c2c9c,0x389e393c,0x3a893a0d,
  0x3b783bb7,0x35bc343e,0x368237e8,0x3b4f3af4,0x3ac43b27,0x3845372c,0x330f350b,0x3bce3b98,0x39cd3a50,0x398238ea,0x26ad2fef,0x3bff3bf0,
  0x39463b7c,0x3a0435a5,0x2c38b699,0xbbfcbb4a,0xb4263340,0x3bba3bcb,0x3aee383a,0xb7febacb,0xbb94b979,0x352339d6,0x3b2c3bff,0x3715a81f,
  0xba58bbe4,0xb8e0b13b,0x302938a8,0x3bef3a81,0x28e83a60,0x3bfe38d6,0xb970305b,0x39df3bed,0xbbe6b9fc,0xb109394f,0xb8b2bbfc,0xba7aaba7,
  0x358db80a,0xbb81bae8,0x3b45340e,0xb6afbbbd,0x3ad13b90,0x3830b53a,0x33713b32,0x3bc836ff,0xb8cc38bc,0x3a673a73,0x3beb30d7,0xb08dbbe8,
  0x2adebb85,0xbbfdb576,0xb9f436c6,0x39583b3f,0x38153bc5,0x3ae1b3a2,0x33ebbad8,0xbbc0b825,0xbb37b966,0xb6e839e7,0x35523bfe,0x3b8ba9b1,
  0xbbc2356a,0x33d33b87,0xbadeb6d2,0xb81a3b3d,0x3bfdb0be,0xaa7abbe9,0x39f038c1,0x395dba6f,0xbbeaaa16,0xb0a63bfe,0xb8c7b9eb,0xba6b3962,
  0x3b8933ba,0x355ebbc3,0x36dd3adb,0x3b3ab820,0xbb422b43,0xb6bb3bfd,0x35813954,0x3b83b9f8,0x30f03a64,0x3be7b8d1,0x38b7bbec,0xba76b074,
  0x39e3bb8e,0xb96bb546,0xbbfe36f4,0xa94d3b35,0xbbc63402,0xb3893bbf,0x382a380f,0x3ad5bae5,0xb70ab359,0xbb2f3bc9,0x352fbace,0xbb923835,
  0xbbbc3b47,0x341a36a4,0xbaeb3599,0xb8053b7f,0x2c0638ad,0x3bfcba7e,0xb94a3be5,0x3a00b122,0x3beeb974,0x3042b9da,0x38db2884,0x3a5cbbff,
  0x3328b7f3,0xbbcc3af1,0xbac73bb8,0x3840b432,0xb5b12c6a,0xbb7a3bfb,0xb68d3941,0x3b4cba09,0xba8538e5,0xb8a33a54,0x31533010,0x3be3bbef,
  0xbbff3b96,0xa7763517,0x397db721,0x39d2bb2a,0x3a4db9c9,0xb8ee3986,0x3bf1bbff,0x2fbda5e4,0x3b24bac1,0xb737384a,0x3b9abbcf,0x34ffb2f7,
  0x3bb5bb76,0xb44b35c8,0x3af7bb52,0x37ddb676,0x3bfabbe1,0xacce3185,0x3a11ba8c,0x3937b899,0x3c00bb1e,0x2452374e,0xb9903b9e,0xb9c034e7,
  0x3855bafe,0x3abab7c8,0x32c63463,0xbbd23bb2,0xb65fad33,0x3b57bbf9,0x3b71b92e,0xb5df3a19,0xbbdf3a45,0x31b6b8f8,0x3a93bbf2,0x388eaf59,
  0x3a21bbdd,0x392431e8,0x2d97ba9b,0x3bf8b884,0xba3d217f,0x3902bc00,0xbbf439b8,0xaef5b999,0xb7643bd4,0xbb183294,0x34cf385f,0xbba13ab3,
  0x3baeb648,0xb47b3b5c,0x3b04bb6c,0x37b235f7,0x3219bbf5,0x3bdaae91,0x387a390c,0xbaa23a35,0xb9a13b13,0xb9afb77a,0x9cb6bba5,0x3c00b4b7,
  0x3bd7b79b,0x32633b0a,0xb86a3bab,0xbaacb493,0xbb68adfb,0x360ebbf7,0x3b60b91b,0x36313a29,0xb785bb65,0x3b10b61a,0xbba7b625,0x34abbb63,
  0x39113aa9,0xba31386f,0x3bf6324b,0xae5f3bd8,0xba2db9aa,0x3916b9a6,0xbbf69648,0xae2dbc00,0x3b0d3874,0xb7903aa5,0x3ba9b232,0x349f3bd9,
  0xbb5eba39,0x363cb907,0x3b6a2ec3,0x36023bf5,0x3ab0adc9,0x38653bf8,0xb27c3a25,0xbbd6b91f,0x9fdb3b07,0xbc00b7a6,0xb99dbbac,0x39b3b487,
  0xba9ebb16,0x387fb76f,0x3bdc34c3,0x32013ba3,0xbbb0b889,0xb46fba97,0xb7bd31cf,0xbb01bbde,0xb759bb59,0x3b1b3654,0xbb9fbb6f,0x34dbb5eb,
  0x3a4132ad,0x38fd3bd3,0x2f27b85a,0x3bf33ab6,0x3a1d3c00,0xb929a311,0x3bf939bc,0x2d653994,0xb894b4f3,0xba90bb9c,0xb19eb742,0x3be03b21,
  0xbb73ba49,0xb5d4b8f3,0x366b2f8b,0x3b543bf2,0xbbd0bbfa,0x32dead00,0x3abd3933,0x38503a15,0xb98bbafb,0x39c537d2,0x3c003bb3,0xa51b3457,
  0xb43eb16c,0x3bb73be2,0xbaf4ba89,0x37e8389e,0xb72cb5bc,0x3b273b78,0xbb98bb4f,0x350b3682,0xb8eab845,0x3a503ac4,0xbbf0bbce,0x2fef330f,
  0xba0db982,0x393c39cd,0xbbfbbbff,0xac9c26ad,0xba81b715,0x38a83b2c,0x3be43b94,0x313bb523,0xbb7cbbef,0xb5a53029,0x36993a58,0x3b4a38e0,
  0xb340b946,0xbbcbba04,0xb83aac38,0x3acb3bfc,0x39793426,0xb9d6bbba,0xbbffbaee,0x281f37fe,0xbbfcb970,0xaba739df,0xb94fbbfe,0xb9fc28e8,
  0x340eb8b2,0xbbbdba7a,0x3ae83109,0xb80abbe6,0x3b323b45,0x36ffb6af,0x353a3b81,0x3b90358d,0xb8d63371,0x3a603bc8,0xbbedb830,0x305b3ad1,
  0xb9e7bae1,0xb9663815,0x29b13bc0,0x3bfe33eb,0x3be836e8,0x30d7bb37,0xb8bcbb8b,0xba733552,0xbb3f308d,0x36c63beb,0x3b8538cc,0x3576ba67,
  0x3825b958,0xbad8b9f4,0xbbc5aade,0x33a23bfd,0xb0bebbc2,0xbbe933d3,0x38c1bade,0xba6fb81a,0xaa163bfd,0x3bfeaa7a,0xb9eb39f0,0x3962395d,
  0x33babbea,0xbbc3b0a6,0x3adbb8c7,0xb820ba6b,0xb6d23b89,0x3b3d355e,0xbb8736dd,0x356a3b3a,0x380fbbfe,0xbae5a94d,0xbbbf396b,0x340239e3,
  0xbbfd382a,0x2b433ad5,0x39f83389,0x3954bbc6,0x38d136bb,0x3a64bb42,0x3074bb83,0xbbec3581,0x3546bbe7,0xbb8e30f0,0xbb353a76,0x36f438b7,
  0x3b7fbb92,0xb599b52f,0x3b47b70a,0x36a4bb2f,0xb122b805,0xbbe53aeb,0x38adbbbc,0xba7e341a,0xbbff3a00,0xa884394a,0xb9742c06,0xb9da3bfc,
  0xb3593a5c,0x3bc9b8db,0xbace3bee,0x38353042,0x3b96ba85,0x3517b8a3,0xb7213153,0xbb2a3be3,0x3bb8bbff,0xb432a776,0xbaf1397d,0xb7f339d2,
  0x3941bac7,0xba093840,0xbbfb3bcc,0x2c6a3328,0x3010b68d,0xbbef3b4c,0xba543b7a,0x38e5b5b1,0x384ab8ee,0x3ac1ba4d,0xb2f72fbd,0x3bcfbbf1,
  0x35c8b737,0x3b76bb24,0xb67634ff,0x3b52bb9a,0x3185b44b,0x3be1bbb5,0xb89937dd,0x3a8cbaf7,0xa5e4acce,0x3bffbbfa,0xb9c93937,0x3986ba11,
  0xaf59b5df,0x3bf2bb71,0x3a45b65f,0xb8f83b57,0xbb1e388e,0x374eba93,0x3b9ebbdf,0x34e731b6,0xbafe3c00,0xb7c82452,0x3463b990,0x3bb2b9c0,
  0xad333855,0xbbf93aba,0xb92e32c6,0x3a19bbd2,0xb9b8ad97,0x3999bbf8,0xbc003924,0xa17fba21,0xb85f3bf4,0xbab32ef5,0x32943902,0xbbd43a3d,
  0x3b6cb4cf,0xb5f73ba1,0x3b5cbb18,0x36483764,0x31e8bb04,0x3bddb7b2,0xb884b47b,0x3a9bbbae,0xbbf73263,0x2dfbbbd7,0x3a29baac,0x391b386a,
  0x3a35360e,0xb90c3b68,0xbbf53631,0xae91bb60,0xb4b7baa2,0x3ba5b87a,0x3b133219,0xb77a3bda,0xb4933c00,0xbbab1cb6,0xb79bb9a1,0x3b0ab9af,
  0xbaa93785,0xb86fbb10,0xb24b3ba7,0xbbd8b4ab,0x39aab911,0x39a63a31,0x1648bbf6,0x3c002e5f,0xb8743a2d,0xbaa5b916,0x32323bf6,0xbbd92e2d,
  0x3625bb0d,0x3b633790,0xb61abba9,0x3b65b49f,0xb4c3399d,0xbba3b9b3,0xb76fbc00,0x3b161fdb,0xb907bbdc,0x3a39b201,0x3bf5387f,0xaec33a9e,
  0x3bf8363c,0x2dc93b5e,0xb91f3602,0xba25bb6a,0xb7a63865,0xbb07bab0,0xb487bbd6,0x3bac327c,0x35eb3b01,0xbb6fb7bd,0x3b593bb0,0xb654346f,
  0xbab6b4db,0xb85abb9f,0xb2ad3759,0xbbd3bb1b,0xb994bbf3,0x39bc2f27,0xbc00ba41,0x2311b8fd,0x3889ad65,0x3a973bf9,0xb1cfba1d,0x3bde3929,
  0x3afb3bd0,0xb7d2b2de,0xbbb3babd,0xb457b850,0x3742398b,0xbb21b9c5,0xbb9cbc00,0x34f3251b,0xaf8b319e,0xbbf2bbe0,0xb8f3ba90,0x3a493894,
  0xb933b66b,0xba15bb54,0xad00b5d4,0x3bfa3b73,0x211b21e4,0xa51ba5e4,0x98b69248,0x1cb61648,0x1f122052,0xa311a452,0x9d7f9bdb,0x217f1fdb,
  0x1bdb1d7f,0x9fdba17f,0xa0529f12,0x24522311,0x124818b6,0x96489cb6,0xa1e4a11b,0x25e4251b,0x2a632b5f,0xae5faf59,0xa1e49bdb,0x25e41fdb,
  0x286b2967,0xac6aad65,0xa6e0a4e9,0x2ade28e8,0x24e926e0,0xa8e8aade,0xa967a86b,0x2d652c6a,0x1bdb21e4,0x9fdba5e4,0xab5faa63,0x2f592e5f,
  0x2dc22ea7,0xb1b6b294,0xa54d9f12,0x294d2311,0x2bf62cde,0xafefb0d7,0xaa31a86b,0x2e2d2c6a,0x286b2a31,0xac6aae2d,0xacdeabf6,0x30d72fef,
  0x1f12254d,0xa311a94d,0xaea7adc2,0x329431b6,0x302c30d2,0xb41ab4b7,0xa7a9a11b,0x2ba7251b,0x2dc22f0c,0xb1b6b2f7,0xac79aa63,0x30742e5f,
  0x2a632c79,0xae5fb074,0xaf0cadc2,0x32f731b6,0x211b27a9,0xa51baba7,0xb0d2b02c,0x34b7341a,0x317a3257,0xb552b61a,0xa902a2ad,0x2d0026ad,
  0x2f8c309f,0xb371b487,0xaddcac2e,0x31cf3029,0x2c2e2ddc,0xb029b1cf,0xb09faf8c,0x34873371,0x22ad2902,0xa6adad00,0xb257b17a,0x361a3552,
  0x32cd33e3,0xb682b76f,0xaa31a420,0x2e2d281f,0x30ac31bb,0xb493b58d,0xaf3fad2a,0x33283122,0x2d2a2f3f,0xb122b328,0xb1bbb0ac,0x358d3493,
  0x24202a31,0xa81fae2d,0xb3e3b2cd,0x376f3682,0x341334bc,0xb7a6b85a,0xab5fa4e9,0x2f5928e8,0x319432da,0xb56ab68d,0xb052ae28,0x343e3219,
  0x2e283052,0xb219b43e,0xb2dab194,0x368d356a,0x24e92b5f,0xa8e8af59,0xb4bcb413,0x385a37a6,0x34c3358c,0xb85fb8f3,0xac47a5b2,0x304229b1,
  0x327e33fd,0xb63cb785,0xb106af26,0x34e7330f,0x2f263106,0xb30fb4e7,0xb3fdb27e,0x3785363c,0x25b22c47,0xa9b1b042,0xb58cb4c3,0x38f3385f,
  0x35773662,0xb8e5b982,0xacdea67b,0x30d72a7a,0x336b3493,0xb70ab83a,0xb1bbb012,0x358d3402,0x301231bb,0xb402b58d,0xb493b36b,0x383a370a,
  0x267b2cde,0xaa7ab0d7,0xb662b577,0x398238e5,0x36303741,0xb962ba04,0xad76a744,0x316c2b43,0x342e352a,0xb7d2b8ad,0xb271b092,0x3631347b,
  0x30923271,0xb47bb631,0xb52ab42e,0x38ad37d2,0x27442d76,0xab43b16c,0xb741b630,0x3a043962,0x36ee3815,0xb9d6ba7a,0xae0ea807,0x32012c06,
  0x34a735c4,0xb84ab91b,0xb329b113,0x36d234f3,0x31133329,0xb4f3b6d2,0xb5c4b4a7,0x391b384a,0x28072e0e,0xac06b201,0xb815b6ee,0x3a7a39d6,
  0x37b4388e,0xba41bae1,0xaea7a86b,0x32942c6a,0x35233662,0xb8a8b982,0xb3e3b194,0x376f356a,0x319433e3,0xb56ab76f,0xb662b523,0x398238a8,
  0x286b2ea7,0xac6ab294,0xb88eb7b4,0x3ae13a41,0x3841390f,0xbaa2bb3a,0xaf3fa8d0,0x33282cce,0x35a13705,0xb902b9e3,0xb44fb216,0x380535df,
  0x3216344f,0xb5dfb805,0xb705b5a1,0x39e33902,0x28d02f3f,0xacceb328,0xb90fb841,0x3b3a3aa2,0x38ac3997,0xbaf7bb83,0xafd8a935,0x33ba2d33,
  0x362137ac,0xb958ba3d,0xb4aeb298,0x38503654,0x329834ae,0xb654b850,0xb7acb621,0x3a3d3958,0x29352fd8,0xad33b3ba,0xb997b8ac,0x3b833af7,
  0x391c3a28,0xbb42bbbc,0xb039a999,0x34262d97,0x36a4382d,0xb9aaba90,0xb50eb31c,0x389936c6,0x331c350e,0xb6c6b899,0xb82db6a4,0x3a9039aa,
  0x29993039,0xad97b426,0xba28b91c,0x3bbc3b42,0x39923ac3,0xbb81bbe3,0xb085a9fe,0x346f2dfb,0x372a3886,0xb9f8badb,0xb570b3a0,0x38e03737,
  0x33a03570,0xb737b8e0,0xb886b72a,0x3adb39f8,0x29fe3085,0xadfbb46f,0xbac3b992,0x3be33b81,0xb9cfbb16,0x3b9c3bf1,0x30ac2a31,0xb493ae2d,
  0xb76fb8b4,0x3a1d3afe,0x35a133e3,0xb902b76f,0xb3e3b5a1,0x376f3902,0x38b4376f,0xbafeba1d,0xaa31b0ac,0x2e2d3493,0x3b1639cf,0xbbf1bb9c,
  0xb956ba74,0x3b633bd2,0x305f29cc,0xb44badc9,0xb6e7b859,0x39d23ab6,0x353f335e,0xb8bcb6ff,0xb35eb53f,0x36ff38bc,0x385936e7,0xbab6b9d2,
  0xa9ccb05f,0x2dc9344b,0x3a743956,0xbbd2bb63,0xb8e3b9de,0x3b1e3ba1,0x30122967,0xb402ad65,0xb662b801,0x39823a67,0x34de32da,0xb874b68d,
  0xb2dab4de,0x368d3874,0x38013662,0xba67b982,0xa967b012,0x2d653402,0x39de38e3,0xbba1bb1e,0xb876b952,0x3ace3b60,0x2f8c2902,0xb371ad00,
  0xb5e1b758,0x392e3a11,0x347e3257,0xb82ab61a,0xb257b47e,0x361a382a,0x375835e1,0xba11b92e,0xa902af8c,0x2d003371,0x39523876,0xbb60bace,
  0xb80db8ce,0x3a733b10,0x2ef3289e,0xb2deac9c,0xb562b6b3,0x38d639b3,0x342031d5,0xb7bdb5a5,0xb1d5b420,0x35a537bd,0x36b33562,0xb9b3b8d6,
  0xa89eaef3,0x2c9c32de,0x38ce380d,0xbb10ba73,0xb750b851,0x3a0d3ab0,0x2e5a2839,0xb24bac38,0xb4e5b613,0x387a394f,0x33863153,0xb721b52f,
  0xb153b386,0x352f3721,0x361334e5,0xb94fb87a,0xa839ae5a,0x2c38324b,0x38513750,0xbab0ba0d,0xb68eb7b4,0x399d3a41,0x2dc227a9,0xb1b6aba7,
  0xb46ab577,0x381a38e5,0x32cd30d2,0xb682b4b7,0xb0d2b2cd,0x34b73682,0x3577346a,0xb8e5b81a,0xa7a9adc2,0x2ba731b6,0x37b4368e,0xba41b99d,
  0xb5d2b6d1,0x392439c5,0x2d2a26e0,0xb122aade,0xb3e3b4de,0x376f3874,0x32163052,0xb5dfb43e,0xb052b216,0x343e35df,0x34de33e3,0xb874b76f,
  0xa6e0ad2a,0x2ade3122,0x36d135d2,0xb9c5b924,0xb51cb5f6,0x38a3393c,0x2c932617,0xb08daa16,0xb2f4b448,0x36a437fe,0x31602fa5,0xb53ab389,
  0xafa5b160,0x3389353a,0x344832f4,0xb7feb6a4,0xa617ac93,0x2a16308d,0x35f6351c,0xb93cb8a3,0xb46ab523,0x381a38a8,0x2bf6254d,0xafefa94d,
  0xb209b36b,0x35d4370a,0x30ac2ea7,0xb493b294,0xaea7b0ac,0x32943493,0x336b3209,0xb70ab5d4,0xa54dabf6,0x294d2fef,0x3523346a,0xb8a8b81a,
  0xb378b456,0x3715380a,0x2ac82484,0xaec3a884,0xb120b24a,0x34ff360e,0x2ff22da9,0xb3d3b19e,0xada9aff2,0x319e33d3,0x324a3120,0xb60eb4ff,
  0xa484aac8,0x28842ec3,0x34563378,0xb80ab715,0xb223b31c,0x35eb36c6,0x29992376,0xad97a776,0xb039b12d,0x3426350b,0x2e8d2cac,0xb27cb0a6,
  0xacacae8d,0x30a6327c,0x312d3039,0xb50bb426,0xa376a999,0x27762d97,0x331c3223,0xb6c6b5eb,0xb0d2b194,0x34b7356a,0x286b21e4,0xac6aa5e4,
  0xaea7b012,0x32943402,0x2d2a2b5f,0xb122af59,0xab5fad2a,0x2f593122,0x30122ea7,0xb402b294,0xa1e4a86b,0x25e42c6a,0x319430d2,0xb56ab4b7,
  0xaf0cb012,0x32f73402,0x267b2052,0xaa7aa452,0xacdeadf5,0x30d731e8,0x2b912967,0xaf8bad65,0xa967ab91,0x2d652f8b,0x2df52cde,0xb1e8b0d7,
  0xa052a67b,0x24522a7a,0x30122f0c,0xb402b2f7,0xac79ad2a,0x30743122,0x24201d7f,0xa81fa17f,0xaa31ab91,0x2e2d2f8b,0x28d026e0,0xacceaade,
  0xa6e0a8d0,0x2ade2cce,0x2b912a31,0xaf8bae2d,0x9d7fa420,0x217f281f,0x2d2a2c79,0xb122b074,0xa7a9a86b,0x2ba72c6a,0x1f1218b6,0xa3119cb6,
  0xa54da67b,0x294d2a7a,0x242021e4,0xa81fa5e4,0xa1e4a420,0x25e4281f,0x267b254d,0xaa7aa94d,0x98b69f12,0x1cb62311,0x286b27a9,0xac6aaba7,
  0xa5e43bff,0xb61a3b65,0xb98239cd,0xbb3a36dd,0xaf593bf2,0xb76f3b16,0xba043946,0xbb833581,0xb2943bd4,0xb85a3ab6,0xba7a38b2,0xbbbc341a,
  0xb4b73ba5,0xb8f33a49,0xbae13815,0xbbe33153,0xac9c3bfb,0xbb87356a,0xb986b9c9,0x361abb65,0xb5a53b7c,0xbbfd2b43,0xb74ebb1e,0x3907ba39,
  0xb8d63a60,0xbbc9b359,0xb1e8bbdd,0x3a97b889,0xba7338bc,0xbaf1b7f3,0x2e91bbf5,0x3b9cb4f3,0xafbd3bf1,0xbb10b785,0x3a0db93c,0x356a3b87,
  0xb88e3a93,0xb87fba9e,0x3bcbb340,0xb0743bec,0xbb183764,0xaf27bbf3,0x3bbd340e,0xb8ad3a7e,0xbc009cb6,0x35d4bb73,0x39e73966,0xbb2a3721,
  0xb16c3be2,0xb3d3bbc2,0x38ee3a4d,0xbb10b785,0xba043946,0x36bbbb42,0xa4523c00,0xb63cbb5e,0xbbfe28e8,0x3b2fb70a,0xb9243a21,0x346fbbb0,
  0xba67b8cc,0x3bcc3328,0xbbda3219,0x3a90b894,0xb2f73bcf,0x386fbaa9,0xba89389e,0x3bc2b3d3,0xbb1e374e,0x3bf5aec3,0xbbbab426,0x3a7638b7,
  0xbb5cb648,0x39bc3994,0xb6afbb45,0x2c063bfc,0xb493bbab,0xad003bfa,0x36e8bb37,0xb9d2397d,0xb43e3bb7,0x3be9b0be,0xb84abac1,0xb86f3aa9,
  0xbbcb3340,0x38d13a64,0x37c8bafe,0xbbf8adc9,0xb94fb9fc,0xb6a43b47,0x3c00217f,0xb654bb59,0x3576bb85,0xbbfb2c6a,0x377a3b13,0x38f3ba49,
  0xb4ff3b9a,0x3a313911,0x3af4b7e8,0xb0bebbe9,0xbc00a452,0xb6023b6a,0x39d63979,0x3b35b6f4,0xb47bbbae,0xbbf9ad65,0xb6ff3b32,0x397439da,
  0x3aacb86a,0xb2debbd0,0xbbe8b0d7,0xb7f33af1,0xb5bc3b78,0x2a7a3bfd,0x37373b24,0x3a313911,0xbbbab426,0xbbe730f0,0xbaba3855,0xb8653ab0,
  0x3109bbe6,0xb41abbbc,0xb902ba3d,0xbb1bb759,0x3bfd2ade,0x3b7ab5b1,0x39afb9a1,0x35d4bb73,0xb6763b52,0xb9a639aa,0xbb4f3682,0xbbfd2a7a,
  0xbafeb7c8,0xb91fba25,0xb523bb94,0x294dbbfe,0x3884ba9b,0x3a97b889,0x3bc8b371,0x3bee3042,0x3a29391b,0x37d23afb,0x308d3beb,0xb3283bcc,
  0xb72c3b27,0xbbfeaa16,0xb5c8bb76,0x39a6b9aa,0xb9d6b979,0x3546bb8e,0x3bf9ad33,0x37a63b07,0x3ae8b80a,0x3a7e38ad,0xb2943bd4,0xbbd332ad,
  0x33a23bc5,0xba5438e5,0xbb0ab79b,0x2d00bbfa,0xb7dd3af7,0xb916ba2d,0x3b98b50b,0xaa163bfe,0xb855baba,0x3bd6b27c,0xb13b3be4,0xbae5b80f,
  0x3bf8ad97,0xb46f3bb0,0xba60b8d6,0x3aceb835,0xb6313b60,0xb9c5b98b,0x3b3fb6c6,0x2c6a3bfb,0xb8453ac4,0x30a6bbea,0x344b3bb5,0xb916ba2d,
  0xb523bb94,0x396b39e3,0xbb57b65f,0x3c009fdb,0x3b81358d,0xbbfc2c06,0x3b18b764,0xb8fd3a41,0xbae13815,0x38a3ba85,0xb2633bd7,0xb2debbd0,
  0xb8993a8c,0x3aa5b874,0xbbce330f,0x3bea30a6,0xad33bbf9,0xb4873bac,0x38e0ba58,0xbad5382a,0x399939b8,0xb654bb59,0x28e83bfe,0x352fbb92,
  0xbbf5ae91,0x3b213742,0xb958b9f4,0x35b13b7a,0xb8ea3a50,0x3bc333ba,0xb185bbe1,0xbaa53874,0x313bbbe4,0xbbbf3402,0x38f83a45,0x376fbb16,
  0x353a3b90,0x39dab974,0xbb5cb648,0x23113c00,0xb9e7b966,0xb5173b96,0x3bf7adfb,0xb7d2bafb,0xb9373a11,0x37903b0d,0x3bf0afef,0x33babbc3,
  0x365fbb57,0xb9b3b99d,0xbb4a3699,0x2b433bfd,0xaef53bf4,0x3b1b3759,0x39fcb94f,0xb599bb7f,0xb219bbda,0xbbe0b19e,0xb8253ad8,0x38e53a54,
  0xb98239cd,0xb55e3b89,0x2cce3bfa,0x37903b0d,0x38e0ba58,0x3389bbc6,0xb1b6bbdf,0xb87fba9e,0xb8303ad1,0xb0423bee,0x347b3bae,0x39293a1d,
  0x36e8bb37,0x2776bbff,0xb60ebb68,0xb9c5b98b,0xb9c93986,0xbb633625,0xbbff26ad,0xbb89b55e,0x3a45b8f8,0x3ba3b4c3,0x3bfc2c38,0x3b4236bb,
  0xbab3385f,0xbbd332ad,0xbbe6b109,0xbaebb805,0x3b13b77a,0x3bf2af8b,0x3bc033eb,0x3a8538a3,0xba0d393c,0xbb3db6d2,0x25e4bbff,0x3b63b625,
  0x3b4ab699,0x39f83954,0xb4e73b9e,0xbbf52ec3,0xbbed305b,0xb835bace,0x3884ba9b,0x3bde31cf,0x3be830d7,0x34323bb8,0xba35390c,0xbb21b742,
  0xba4d38ee,0xb4abbba7,0x3bfb2c9c,0xb6d23b3d,0x3bdfb1b6,0xb2013bdc,0xbacbb83a,0x3a64b8d1,0xbba1b4cf,0x38fdba41,0x380a3ae8,0xbbe53122,
  0x39a139af,0xbb54366b,0xa9b1bbfe,0x3b963517,0xba89389e,0x381abade,0xafbd3bf1,0xb4abbba7,0x3bfc2c38,0xbb833581,0x39c0b990,0xb6023b6a,
  0xb9dfb970,0x3b92352f,0xbbf82d97,0x3b01b7bd,0x308d3beb,0xb840bac7,0x3aa2387a,0xbbe0b19e,0xbac1384a,0x3bd8b24b,0xbbe2b16c,0x3ade381a,
  0x3b9e34e7,0xba39b907,0x37fe3aee,0xb0f0bbe7,0xb5f7bb6c,0x23113c00,0x358dbb81,0xb94a3a00,0xb79b3b0a,0x3a15b933,0xbb8b3552,0x3bff2776,
  0xbaf437e8,0x3a6f38c1,0x32f7bbcf,0xbbd8324b,0x3acb383a,0x3074bbec,0xbbb23463,0x391f3a25,0x2ba7bbfc,0xbb7f3599,0x399939b8,0x35ebbb6f,
  0xbb3f36c6,0x3a093941,0x34b7bba5,0xbbf22f8b,0xbb243737,0x2e5f3bf6,0x3bb7343e,0x38c1ba6f,0x399039c0,0x3b5eb63c,0xa81fbbff,0xbb8eb546,
  0x37b2bb04,0xb929ba1d,0xbb90353a,0xa8843bff,0xbbd7b263,0xb8503abd,0x38bc3a73,0x3bb8b432,0xbb4f3682,0xb95d39f0,0xb4ff3b9a,0x2e5f3bf6,
  0x37fe3aee,0x3a7638b7,0x3bd232c6,0x3bd6b27c,0x3a7ab8b2,0x3805baeb,0x2ef5bbf4,0xb4dbbb9f,0xb958b9f4,0xbb4cb68d,0xbc009cb6,0xbb54366b,
  0xbb7635c8,0xbc001648,0xbb78b5bc,0xb9f0b95d,0x34633bb2,0xadc93bf8,0xb7153b2c,0xb9e3396b,0x3bddb1e8,0x3bde31cf,0x3ad13830,0x38db3a5c,
  0xadfbbbf7,0x3457bbb3,0x38ccba67,0x3ac7b840,0xbb98350b,0xb962b9eb,0x3676bb52,0x3c009648,0x281f3bff,0xbb3536f4,0xba19b92e,0x3487bbac,
  0x3bbd340e,0x31223be5,0xbab3385f,0xbab6b85a,0x3825bad8,0x3bef3010,0x34933bab,0xba153933,0xbbb5344b,0x2e2dbbf6,0x3b27372c,0xb9eb3962,
  0xb2c63bd2,0xbab0b865,0x3a81b8a8,0x34023bbf,0x3a213924,0xbb0137bd,0xb05bbbed,0x3bc93359,0x3b68b60e,0x251b3c00,0xbb85b576,0x3941ba09,
  0xbbce330f,0x3a6bb8c7,0xb7dd3af7,0x2e2dbbf6,0xb7153b2c,0x294dbbfe,0x35df3b71,0xb9b3b99d,0x36af3b45,0xba00b94a,0x3ba134cf,0xbbf32f27,
  0x3bc033eb,0xbbe33153,0x3aacb86a,0xb8503abd,0xbbe13185,0x3bd93232,0xbac4b845,0x38c73a6b,0xb92e3a19,0x3b07b7a6,0xbbef3029,0x3bc63389,
  0xa17f3c00,0x35ebbb6f,0xb97039df,0x3b2fb70a,0x390c3a35,0xb4f3bb9c,0xaade3bfd,0x368dbb4c,0xbbf02fef,0x38203adb,0x3899ba8c,0xbbd9b232,
  0xba8138a8,0x3ae5380f,0x2f59bbf2,0xbba334c3,0xb6ff3b32,0x3bff2884,0xb5f7bb6c,0xb99439bc,0x29b13bfe,0x3b2ab721,0xba29b91b,0xb4573bb3,
  0xbbfa2cce,0xb49f3ba9,0x3a5038ea,0x3adbb820,0xbb7135df,0x1fdb3c00,0x3b7c35a5,0x3954b9f8,0xba3d3902,0x34db3b9f,0x3bfc2ba7,0x36a4bb47,
  0xb87a3aa2,0x38943a90,0x3bc5b3a2,0x3010bbef,0xbbff26ad,0xbb3a36dd,0xb9373a11,0xb49f3ba9,0xbbef3029,0xbad5382a,0xb88e3a93,0xb2013bdc,
  0xbbc83371,0xba5c38db,0xb7b23b04,0xad653bf9,0xbb8b3552,0xb9d2397d,0xb6313b60,0x251b3c00,0x3bf12fbd,0x3b103785,0x393c3a0d,0x356a3b87,
  0x3bd232c6,0x3ab03865,0x38a83a81,0x34023bbf,0x3ba134cf,0x3a4138fd,0x380a3ae8,0x31223be5,0x3b603631,0x39c5398b,0x36c63b3f,0x2c6a3bfb,
  0xbbe2b16c,0xb3d3bbc2,0x3a4db8ee,0x3b103785,0xbb2cb715,0x294dbbfe,0x3b71b5df,0x39b3399d,0xb9dfb970,0x352fbb92,0x3bf8ad97,0x37bd3b01,
  0xb815bae1,0x38a3ba85,0x3bd73263,0x32de3bd0,0x3bcf32f7,0xb86f3aa9,0xb89eba89,0x3bc2b3d3,0x3a19392e,0xbb0737a6,0xb029bbef,0x3bc63389,
  0x35f73b6c,0xbc002311,0x358dbb81,0x3a00394a,0xae913bf5,0xbb21b742,0x39f4b958,0x35b13b7a,0xbbb7b43e,0x3be9b0be,0xbac1384a,0x386fbaa9,
  0xb8a8ba81,0x3ae5380f,0xbbf2af59,0x3ba3b4c3,0x2ba7bbfc,0x35993b7f,0xb999b9b8,0x3b6f35eb,0x3966b9e7,0xb5173b96,0xadfbbbf7,0x37d23afb,
  0x3b9a34ff,0xba31b911,0x37e83af4,0xb0bebbe9,0x35df3b71,0x9fdbbc00,0xb5a53b7c,0x3954b9f8,0xb7b23b04,0x3a1db929,0xbb90353a,0x3bff2884,
  0xbbda3219,0x3be0319e,0xbad8b825,0x38e53a54,0xbb78b5bc,0x2a7a3bfd,0x3b24b737,0xba31b911,0xb029bbef,0xbad5382a,0x3a93388e,0x3201bbdc,
  0x3a7ab8b2,0xbaebb805,0xaef53bf4,0x3b9fb4db,0x3b3736e8,0x2776bbff,0xbb68360e,0x39c5398b,0x3b523676,0x39a6b9aa,0xb682bb4f,0xbbfd2a7a,
  0xaf593bf2,0x3b16376f,0x3a04b946,0xb581bb83,0xbbdd31e8,0xb1cf3bde,0x3ad13830,0x3a5cb8db,0xb77abb13,0xbbf22f8b,0xb3eb3bc0,0x3a8538a3,
  0xbb27b72c,0xbbfeaa16,0xbb7635c8,0xb9a639aa,0x35a5bb7c,0xab43bbfd,0xb74ebb1e,0xba39b907,0x3bbd340e,0x3be5b122,0x3ab3b85f,0x385abab6,
  0xb0d73be8,0x34323bb8,0x390c3a35,0x3b213742,0x3af737dd,0x39163a2d,0x350b3b98,0xaa163bfe,0xb88e3a93,0xba9e387f,0xbbcb3340,0xbbecb074,
  0xba21b924,0xb7bdbb01,0xb05bbbed,0x3359bbc9,0x39afb9a1,0x3b54b66b,0x3bfea9b1,0x3b963517,0xbac4b845,0x30a6bbea,0x3bb5b44b,0x39163a2d,
  0x3a04b946,0x3b4236bb,0xa4523c00,0xbb5e363c,0x36af3b45,0xb94a3a00,0xbba1b4cf,0xaf27bbf3,0xbbeb308d,0xb840bac7,0x387abaa2,0x3be0319e,
  0x3a8c3899,0xbaa53874,0xb30fbbce,0x3bea30a6,0xbb1e374e,0xaec3bbf5,0x3bba3426,0xb8b73a76,0x217fbc00,0x3b6f35eb,0xb97039df,0xb70abb2f,
  0x3b0a379b,0xba153933,0xb552bb8b,0x3bff2776,0xba50b8ea,0x3bc333ba,0xbbe13185,0x3aa5b874,0x3bcbb340,0xba6438d1,0x37c8bafe,0xadc93bf8,
  0xb6ff3b32,0x2884bbff,0x35f73b6c,0xb9bcb994,0xb6c6bb3f,0x3a093941,0xbba5b4b7,0x3bf2af8b,0x3a113937,0xb790bb0d,0x2fef3bf0,0x33babbc3,
  0xbc00a452,0x3b6a3602,0xb9d6b979,0x36f43b35,0x3a3db902,0xbb9f34db,0x3bfc2ba7,0xbb47b6a4,0xb2633bd7,0x3850babd,0xba7338bc,0x3bb8b432,
  0xb9cdb982,0xb55e3b89,0x3bfaacce,0xb790bb0d,0x3bba3426,0xb0f0bbe7,0xbaba3855,0x3ab03865,0xbbc83371,0x38db3a5c,0x37b2bb04,0xbbf9ad65,
  0x39f4b958,0xbb4cb68d,0x9cb63c00,0x3b54b66b,0x398639c9,0x3b63b625,0xa6adbbff,0xbb89b55e,0xbafeb7c8,0xba25391f,0x35233b94,0x3bfe294d,
  0x3bd43294,0x385abab6,0xb8b2ba7a,0xbbbc341a,0xbbf72dfb,0xb4573bb3,0x3a6738cc,0x3ac7b840,0xb93cba0d,0xbb3db6d2,0xbbffa5e4,0xbb633625,
  0x39d63979,0x3b8e3546,0x3bf9ad33,0x3b07b7a6,0xba60b8d6,0xbbc9b359,0xbbdd31e8,0xba973889,0x3ad83825,0x3bef3010,0x3babb493,0x3a15b933,
  0x38ee3a4d,0x34ab3ba7,0xac9c3bfb,0xb6d23b3d,0xb855baba,0xb27cbbd6,0x313bbbe4,0x380fbae5,0x37643b18,0x2f273bf3,0xb40e3bbd,0xb8ad3a7e,
  0xb60ebb68,0xa51bbc00,0x3576bb85,0x3941ba09,0xb89eba89,0x381abade,0x3bf12fbd,0x34ab3ba7,0x35233b94,0xb9e3396b,0xbb57b65f,0x9fdbbc00,
  0xa8e8bbfe,0x3b2fb70a,0x3a213924,0xb46f3bb0,0xb3eb3bc0,0xbbe33153,0xb86abaac,0x3850babd,0x384a3ac1,0xbbd8324b,0x316cbbe2,0x3ade381a,
  0xad33bbf9,0x3bac3487,0xb8e03a58,0xb82abad5,0xb6483b5c,0xb9bcb994,0x3b45b6af,0x2c063bfc,0x3a35b90c,0x34f33b9c,0xbbfdaade,0x368dbb4c,
  0xb7e8baf4,0x3a6f38c1,0xbbcfb2f7,0x3bd8b24b,0xb13b3be4,0xb402bbbf,0x38f83a45,0xbb16b76f,0x39fcb94f,0xb6a43b47,0x217fbc00,0x36543b59,
  0xbbfe29b1,0x3b2ab721,0xb91b3a29,0x3457bbb3,0x37373b24,0xae5fbbf6,0xb43e3bb7,0x38c1ba6f,0x365fbb57,0xb99d39b3,0x3b4ab699,0xbbfd2b43,
  0xbbae347b,0x3bf92d65,0xbb32b6ff,0x397439da,0x3aa2387a,0xb894ba90,0x33a23bc5,0x3010bbef,0xb682bb4f,0xb95d39f0,0x3b9a34ff,0xae5fbbf6,
  0xb8e03a58,0x3bc63389,0xb1b6bbdf,0xba9e387f,0x3be63109,0xb41abbbc,0xba3d3902,0x3b1b3759,0xb552bb8b,0xb9d2397d,0x3b603631,0xa51bbc00,
  0x35c83b76,0x3c009648,0x35bcbb78,0xb9f0b95d,0x3a45b8f8,0xb4c3bba3,0xbbfcac38,0xb6bb3b42,0xba9bb884,0xba973889,0x33713bc8,0x3bee3042,
  0xb4b73ba5,0x3a4938f3,0x3ae1b815,0xb153bbe3,0xb50bbb98,0xb962b9eb,0xbb52b676,0xbc001648,0xbb4a3699,0xb95439f8,0xb4e73b9e,0x2ec33bf5,
  0x380a3ae8,0x3a7e38ad,0x3bd43294,0x3bd3b2ad,0x3a73b8bc,0x37f3baf1,0x2e91bbf5,0xb4f3bb9c,0x344b3bb5,0xae2d3bf6,0xb72c3b27,0xb9eb3962,
  0x3bdfb1b6,0x3bdc3201,0x3acb383a,0x38d13a64,0xad97bbf8,0x346fbbb0,0x38d6ba60,0x3aceb835,0xbc009cb6,0xbb73b5d4,0xb9e7b966,0xb721bb2a,
  0xb30fbbce,0x3a6bb8c7,0x3af737dd,0xae2d3bf6,0xbbfcac38,0xb581bb83,0x39c0b990,0x3b6a3602,0xb58d3b81,0xbbfc2c06,0xb764bb18,0x38fdba41,
  0x3a6738cc,0xb3283bcc,0xbbda3219,0xb894ba90,0x31853be1,0xbbd9b232,0x3845bac4,0x38c73a6b,0x3b9e34e7,0xb9073a39,0xb7febaee,0x3be7b0f0,
  0x39b8b999,0x36543b59,0xbbfe28e8,0x352fbb92,0xb493bbab,0x3bfa2d00,0xb6e83b37,0xb97db9d2,0xafefbbf0,0x38203adb,0xba8cb899,0x3bd93232,
  0xbacbb83a,0x3bec3074,0xbbb23463,0x3a25b91f,0xbb90353a,0x39dab974,0xb6483b5c,0xa311bc00,0xb5763b85,0xac6abbfb,0x377a3b13,0xba49b8f3,
  0x2cce3bfa,0x349fbba9,0xb8ea3a50,0x3adbb820,0x399039c0,0xb63cbb5e,0x281f3bff,0x3546bb8e,0x3bf42ef5,0xbb1bb759,0x394f39fc,0xb599bb7f,
  0x3aacb86a,0xbbd032de,0x3be830d7,0xbaf1b7f3,0xa6adbbff,0xbb3a36dd,0x3a113937,0x349fbba9,0xb7febaee,0xb8b73a76,0x3bd232c6,0xb27cbbd6,
  0xbad1b830,0xb0423bee,0x3baeb47b,0xb929ba1d,0xbbfdaade,0x35b13b7a,0x39afb9a1,0xbb73b5d4,0xa5e43bff,0x3b65361a,0x3982b9cd,0xb6ddbb3a,
  0x34633bb2,0x3bf82dc9,0x3715bb2c,0xb96bb9e3,0x385f3ab3,0x3bd3b2ad,0x3109bbe6,0xbaebb805,0x3a29391b,0x3afbb7d2,0xb08dbbeb,0xbbccb328,
  0x2c9cbbfb,0xb56abb87,0xb986b9c9,0xbb65b61a,0xa81fbbff,0xb6f4bb35,0xba19b92e,0xbbacb487,0xb05bbbed,0xb835bace,0xba9bb884,0xbbdeb1cf,
  0xb3a2bbc5,0xb8e5ba54,0xbb0ab79b,0xbbfaad00,0x00000000,0x00000000,0x00000000,0x00000000,0xaa1f0000,0xaf64ada8,0xaf64b000,0xaa1fada8,
  0xada80000,0xada8b000,0x2da88000,0x2da83000,0xaf640000,0x2a1fada8,0x2a1f3000,0xaf64ada8,0xb0000000,0x30008000,0xb0000000,0x30008000,
  0xaf640000,0x2a1f2da8,0x2a1fb000,0xaf642da8,0xada80000,0xada83000,0x2da88000,0x2da8b000,0xaa1f0000,0xaf642da8,0xaf643000,0xaa1f2da8,
  0x00000000,0x00000000,0x00000000,0x00000000,0x2a1f8000,0x2f642da8,0x2f643000,0x2a1f2da8,0xada80000,0xada8b000,0x2da88000,0x2da83000,
  0x2f648000,0xaa1f2da8,0xaa1fb000,0x2f642da8,0xb0000000,0x30008000,0xb0000000,0x30008000,0x2f648000,0xaa1fada8,0xaa1f3000,0x2f64ada8,
  0xada80000,0xada83000,0x2da88000,0x2da8b000,0x2a1f8000,0x2f64ada8,0x2f64b000,0x2a1fada8,0x80000000,0x80000000,0x80000000,0x80000000,
  0x2a1f0000,0x2f64ada8,0x2f64b000,0x2a1fada8,0x2da80000,0x2da8b000,0xada88000,0xada83000,0x2f640000,0xaa1fada8,0xaa1f3000,0x2f64ada8,
  0x30000000,0xb0008000,0x30000000,0xb0008000,0x2f640000,0xaa1f2da8,0xaa1fb000,0x2f642da8,0x2da80000,0x2da83000,0xada88000,0xada8b000,
  0x2a1f0000,0x2f642da8,0x2f643000,0x2a1f2da8,0x80000000,0x80000000,0x80000000,0x80000000,0xaa1f8000,0xaf642da8,0xaf643000,0xaa1f2da8,
  0x2da80000,0x2da8b000,0xada88000,0xada83000,0xaf648000,0x2a1f2da8,0x2a1fb000,0xaf642da8,0x30000000,0xb0008000,0x30000000,0xb0008000,
  0xaf648000,0x2a1fada8,0x2a1f3000,0xaf64ada8,0x2da80000,0x2da83000,0xada88000,0xada8b000,0xaa1f8000,0xaf64ada8,0xaf64b000,0xaa1fada8,
  0x30003000,0x30003000,0x30003000,0x30003000,0x2f643000,0x2a1f2da8,0xaa1f0000,0xaf64ada8,0x2da83000,0xada80000,0xada8b000,0x2da88000,
  0x2a1f3000,0xaf64ada8,0x2f648000,0xaa1f2da8,0x00003000,0x8000b000,0x00003000,0x8000b000,0xaa1f3000,0x2f64ada8,0xaf640000,0x2a1f2da8,
  0xada83000,0x2da88000,0x2da8b000,0xada80000,0xaf643000,0xaa1f2da8,0x2a1f8000,0x2f64ada8,0x30003000,0x30003000,0x30003000,0x30003000,
  0xaf64b000,0xaa1fada8,0x2a1f8000,0x2f642da8,0x2da83000,0xada80000,0xada8b000,0x2da88000,0xaa1fb000,0x2f642da8,0xaf640000,0x2a1fada8,
  0x00003000,0x8000b000,0x00003000,0x8000b000,0x2a1fb000,0xaf642da8,0x2f648000,0xaa1fada8,0xada83000,0x2da88000,0x2da8b000,0xada80000,
  0x2f64b000,0x2a1fada8,0xaa1f0000,0xaf642da8,0xb0003000,0xb0003000,0xb0003000,0xb0003000,0xaf643000,0xaa1f2da8,0x2a1f0000,0x2f64ada8,
  0xada83000,0x2da80000,0x2da8b000,0xada88000,0xaa1f3000,0x2f64ada8,0xaf648000,0x2a1f2da8,0x80003000,0x0000b000,0x80003000,0x0000b000,
  0x2a1f3000,0xaf64ada8,0x2f640000,0xaa1f2da8,0x2da83000,0xada88000,0xada8b000,0x2da80000,0x2f643000,0x2a1f2da8,0xaa1f8000,0xaf64ada8,
  0xb0003000,0xb0003000,0xb0003000,0xb0003000,0x2f64b000,0x2a1fada8,0xaa1f8000,0xaf642da8,0xada83000,0x2da80000,0x2da8b000,0xada88000,
  0x2a1fb000,0xaf642da8,0x2f640000,0xaa1fada8,0x80003000,0x0000b000,0x80003000,0x0000b000,0xaa1fb000,0x2f642da8,0xaf648000,0x2a1fada8,
  0x2da83000,0xada88000,0xada8b000,0x2da80000,0xaf64b000,0xaa1fada8,0x2a1f0000,0x2f642da8,0x80008000,0x80008000,0x80008000,0x80008000,
  0x2a1f8000,0x2f642da8,0x2f643000,0x2a1f2da8,0x2da88000,0x2da83000,0xada80000,0xada8b000,0x2f648000,0xaa1f2da8,0xaa1fb000,0x2f642da8,
  0x30008000,0xb0000000,0x30008000,0xb0000000,0x2f648000,0xaa1fada8,0xaa1f3000,0x2f64ada8,0x2da88000,0x2da8b000,0xada80000,0xada83000,
  0x2a1f8000,0x2f64ada8,0x2f64b000,0x2a1fada8,0x80008000,0x80008000,0x80008000,0x80008000,0xaa1f0000,0xaf64ada8,0xaf64b000,0xaa1fada8,
  0x2da88000,0x2da83000,0xada80000,0xada8b000,0xaf640000,0x2a1fada8,0x2a1f3000,0xaf64ada8,0x30008000,0xb0000000,0x30008000,0xb0000000,
  0xaf640000,0x2a1f2da8,0x2a1fb000,0xaf642da8,0x2da88000,0x2da8b000,0xada80000,0xada83000,0xaa1f0000,0xaf642da8,0xaf643000,0xaa1f2da8,
  0x00008000,0x00008000,0x00008000,0x00008000,0xaa1f8000,0xaf642da8,0xaf643000,0xaa1f2da8,0xada88000,0xada83000,0x2da80000,0x2da8b000,
  0xaf648000,0x2a1f2da8,0x2a1fb000,0xaf642da8,0xb0008000,0x30000000,0xb0008000,0x30000000,0xaf648000,0x2a1fada8,0x2a1f3000,0xaf64ada8,
  0xada88000,0xada8b000,0x2da80000,0x2da83000,0xaa1f8000,0xaf64ada8,0xaf64b000,0xaa1fada8,0x00008000,0x00008000,0x00008000,0x00008000,
  0x2a1f0000,0x2f64ada8,0x2f64b000,0x2a1fada8,0xada88000,0xada83000,0x2da80000,0x2da8b000,0x2f640000,0xaa1fada8,0xaa1f3000,0x2f64ada8,
  0xb0008000,0x30000000,0xb0008000,0x30000000,0x2f640000,0xaa1f2da8,0xaa1fb000,0x2f642da8,0xada88000,0xada8b000,0x2da80000,0x2da83000,
  0x2a1f0000,0x2f642da8,0x2f643000,0x2a1f2da8,
};

constexpr int kThreads = 384;
constexpr int kCtas = 128;

#define EARLY 2
#define HT0 13800
#define HGAP 500
#define PREP0 1200
#define PREPGAP 700
#define U0 5
#define UNUM 11
#define UDEN 4
#define UCV 28
#define UPRE 0
#define WQT 11800
#define QGAP 400
#define QT 17800
#define PSEQ 0
#define S18 0
#define ROT 1
#define CE 11
#define OSEQ 0
#define TAIL 3
#define TAILE 0
#define ENDS 0
#define PUB 1
#define PSW 6
#define YV 4
#define PU 2
#define POSTGAP 1000
#define SAFE 1
#define EXP 0

constexpr int NS1 = 6;
__host__ __device__ constexpr int slot1(int it) { return (it + 4) % NS1; }
__host__ __device__ constexpr uint32_t w1_off(int s) { return (1 + s + (s >> 1)) * 16384; }
__host__ __device__ constexpr uint32_t x1_off(int it) { return ((it >> 1) & 3) * 49152; }
constexpr uint32_t ST2 = 32768;
constexpr uint32_t RA = 131072;
constexpr uint32_t RB = 163840;
constexpr uint32_t RU = 196608;
constexpr uint32_t Y_IN = RU;
constexpr uint32_t SM_ONES = 229376;
constexpr uint32_t SM_F2 = SM_ONES + 128;
constexpr uint32_t SM_BAR = 231424;
constexpr uint32_t SM_SCALE = SM_ONES + 1792;
constexpr uint32_t SM_MAX = SM_BAR + 512;
constexpr uint32_t SM_TOTAL = 232448;
constexpr uint32_t SM_BASE = 1024;
__host__ __device__ constexpr uint32_t kv_off(int h) { return RB + (h >> 1) * 16384 + (h & 1) * 2560; }

enum Bar { B_F1 = 0, B_F2 = 6, B_H = B_F2 + 4, B_KVL = 12, B_RDY = 16, B_Q = 30, B_MAX, B_ZERO, B_U, B_KV,
           B_E1 = 35, B_E2 = 41, B_I2 = B_E2 + 4,
           B_KVE = 47, B_VST = 51, B_KVM, B_KVP, B_KVI, B_OW, B_S1 = 57, B_ZST,
           B_OFREE = 59, B_F2M, B_STG, B_Y, B_COUNT = 64, B_U2 = B_KVL };
__host__ __device__ constexpr int slot2(int n) { return n < 22 ? n & 3 : (0x1032510325ull >> (4 * (n - 22))) & 7; }
__host__ __device__ constexpr int par2(int n) { return n < 22 ? (n >> 2) & 1 : (0x326 >> (n - 22)) & 1; }

constexpr int KV_WORDS = 4096 + 128;
struct Scratch {
  float kv[8][KV_WORDS];
  unsigned kvflag[8 * 32], zflag[8 * 32], oflag[16 * 32], epoch[kCtas];
};
struct Params {
  CUtensorMap w1, x, k, v, w2, wo, o, outa, q, outb;
  const __nv_bfloat16* shift_k;
  const __nv_bfloat16* ssm_k;
  const __nv_bfloat16* ssm_d;
  const __nv_bfloat16* q_ptr;
  const __nv_bfloat16* k_ptr;
  const __nv_bfloat16* w_ptr;
  const __nv_bfloat16* wo_ptr;
  uint64_t zero;
  Scratch* g;
  const uint32_t* tab;
};

__device__ __align__(128) Scratch g_scratch;
__device__ __align__(128) __nv_bfloat16 g_o[2048 * 1024];

#define TSTAMP(cond, i) do { } while (0)
#define GSTAMP(cond, i) do { } while (0)
#define KSTAMP(n) do { } while (0)
#define QSTAMP(n) do { } while (0)

constexpr int kSpinLimit = 1 << 17;

DEVI void mbar_init(uint32_t a, uint32_t c) { asm volatile("mbarrier.init.shared::cta.b64 [%0], %1;" :: "r"(a), "r"(c) : "memory"); }
DEVI void mbar_expect(uint32_t a, uint32_t b) { asm volatile("mbarrier.arrive.expect_tx.shared::cta.b64 _, [%0], %1;" :: "r"(a), "r"(b) : "memory"); }
DEVI void mbar_arrive(uint32_t a) { asm volatile("mbarrier.arrive.shared::cta.b64 _, [%0];" :: "r"(a) : "memory"); }
DEVI void mbar_arrive_if(uint32_t a, bool pred) {
  asm volatile("{\n.reg .pred p;\nsetp.ne.b32 p, %1, 0;\n@p mbarrier.arrive.shared::cta.b64 _, [%0];\n}" :: "r"(a), "r"((int)pred) : "memory");
}
DEVI void mbar_wait(uint32_t a, uint32_t parity) {
  asm volatile("{\n.reg .pred p;\n.reg .u32 n;\nmov.u32 n, 0;\nW_LOOP:\n"
               "mbarrier.try_wait.parity.shared::cta.b64 p, [%0], %1;\n@p bra W_DONE;\n"
               "add.u32 n, n, 1;\nsetp.lt.u32 p, n, %2;\n@p bra W_LOOP;\nW_DONE:\n}"
               :: "r"(a), "r"(parity), "n"(kSpinLimit) : "memory");
}
DEVI void mbar_wait_long(uint32_t a, uint32_t parity) {
  asm volatile("{\n.reg .pred p;\n.reg .u32 n;\nmov.u32 n, 0;\nW_LOOP:\n"
               "mbarrier.try_wait.parity.shared::cta.b64 p, [%0], %1, %3;\n@p bra W_DONE;\n"
               "add.u32 n, n, 1;\nsetp.lt.u32 p, n, %2;\n@p bra W_LOOP;\nW_DONE:\n}"
               :: "r"(a), "r"(parity), "n"(kSpinLimit), "r"(4000) : "memory");
}
DEVI void flag_wait(const unsigned* p, unsigned target) {
  int n = 0; unsigned v;
  do {
    asm volatile("ld.relaxed.gpu.global.u32 %0, [%1];" : "=r"(v) : "l"(p) : "memory");
  } while ((int)(v - target) < 0 && ++n < kSpinLimit);
  asm volatile("fence.acquire.gpu;" ::: "memory");
}
DEVI unsigned ld_relaxed(const unsigned* p) { unsigned v; asm volatile("ld.relaxed.gpu.global.u32 %0, [%1];" : "=r"(v) : "l"(p) : "memory"); return v; }
DEVI uint32_t clock32() { uint32_t t; asm volatile("mov.u32 %0, %%clock;" : "=r"(t)); return t; }
DEVI void pace(uint32_t t0, uint32_t n) { while (clock32() - t0 < n) __nanosleep(20); }
DEVI bool elect() { uint32_t p; asm volatile("{\n.reg .pred p;\nelect.sync _|p, 0xffffffff;\nselp.u32 %0, 1, 0, p;\n}" : "=r"(p)); return p; }
DEVI void fence_async_smem() { asm volatile("fence.proxy.async.shared::cta;" ::: "memory"); }
DEVI void bar_sync(int id, int n) { asm volatile("bar.sync %0, %1;" :: "r"(id), "r"(n) : "memory"); }
DEVI void cluster_sync() { asm volatile("barrier.cluster.arrive.relaxed.aligned;\nbarrier.cluster.wait.aligned;" ::: "memory"); }
DEVI void wg_fence() { asm volatile("wgmma.fence.sync.aligned;" ::: "memory"); }
DEVI void wg_commit() { asm volatile("wgmma.commit_group.sync.aligned;" ::: "memory"); }
template <int N> DEVI void wg_wait() { asm volatile("wgmma.wait_group.sync.aligned %0;" :: "n"(N) : "memory"); }
template <int N> DEVI void pin(uint32_t* r) {
#pragma unroll
  for (int i = 0; i < N; i++) asm volatile("" : "+r"(r[i]));
}
template <int N> DEVI void pin(float* r) {
#pragma unroll
  for (int i = 0; i < N; i++) asm volatile("" : "+f"(r[i]));
}

DEVI void tma2d(uint32_t dst, const CUtensorMap* m, int c0, int c1, uint32_t bar) {
  asm volatile("cp.async.bulk.tensor.2d.shared::cluster.global.mbarrier::complete_tx::bytes [%0], [%1, {%3, %4}], [%2];"
               :: "r"(dst), "l"(m), "r"(bar), "r"(c0), "r"(c1) : "memory");
}
DEVI void tma2d_mc(uint32_t dst, const CUtensorMap* m, int c0, int c1, uint32_t bar) {
  asm volatile("cp.async.bulk.tensor.2d.shared::cluster.global.mbarrier::complete_tx::bytes.multicast::cluster [%0], [%1, {%3, %4}], [%2], %5;"
               :: "r"(dst), "l"(m), "r"(bar), "r"(c0), "r"(c1), "h"((uint16_t)3) : "memory");
}
DEVI void tma3d(uint32_t dst, const CUtensorMap* m, int c0, int c1, int c2, uint32_t bar) {
  asm volatile("cp.async.bulk.tensor.3d.shared::cluster.global.mbarrier::complete_tx::bytes [%0], [%1, {%3, %4, %5}], [%2];"
               :: "r"(dst), "l"(m), "r"(bar), "r"(c0), "r"(c1), "r"(c2) : "memory");
}
DEVI void tma4d(uint32_t dst, const CUtensorMap* m, int c1, int c2, int c3, uint32_t bar) {
  asm volatile("cp.async.bulk.tensor.4d.shared::cluster.global.mbarrier::complete_tx::bytes [%0], [%1, {%3, %4, %5, %6}], [%2];"
               :: "r"(dst), "l"(m), "r"(bar), "r"(0), "r"(c1), "r"(c2), "r"(c3) : "memory");
}
DEVI void tma5d(uint32_t dst, const CUtensorMap* m, int c0, int c1, int c3, int c4, uint32_t bar) {
  asm volatile("cp.async.bulk.tensor.5d.shared::cluster.global.mbarrier::complete_tx::bytes [%0], [%1, {%3, %4, %5, %6, %7}], [%2];"
               :: "r"(dst), "l"(m), "r"(bar), "r"(c0), "r"(c1), "r"(0), "r"(c3), "r"(c4) : "memory");
}
DEVI void tma2d_store(const CUtensorMap* m, uint32_t src, int c0, int c1) {
  asm volatile("cp.async.bulk.tensor.2d.global.shared::cta.bulk_group [%0, {%2, %3}], [%1];" :: "l"(m), "r"(src), "r"(c0), "r"(c1) : "memory");
}
DEVI void tma2d_store_e(const CUtensorMap* m, uint32_t src, int c0, int c1) {
  asm volatile("{\n.reg .pred e;\nelect.sync _|e, 0xffffffff;\n@e cp.async.bulk.tensor.2d.global.shared::cta.bulk_group [%0, {%2, %3}], [%1];\n"
               "@e cp.async.bulk.commit_group;\n}" :: "l"(m), "r"(src), "r"(c0), "r"(c1) : "memory");
}
DEVI void tma5d_store(const CUtensorMap* m, uint32_t src, int c0, int c1, int c3, int c4) {
  asm volatile("cp.async.bulk.tensor.5d.global.shared::cta.bulk_group [%0, {%2, %3, %4, %5, %6}], [%1];\ncp.async.bulk.commit_group;"
               :: "l"(m), "r"(src), "r"(c0), "r"(c1), "r"(0), "r"(c3), "r"(c4) : "memory");
}
DEVI void bulk_load(uint32_t dst, const void* src, uint32_t bytes, uint32_t bar) {
  asm volatile("cp.async.bulk.shared::cluster.global.mbarrier::complete_tx::bytes [%0], [%1], %2, [%3];" :: "r"(dst), "l"(src), "r"(bytes), "r"(bar) : "memory");
}
DEVI uint32_t mapa(uint32_t a, int rank) { uint32_t r; asm("mapa.shared::cluster.u32 %0, %1, %2;" : "=r"(r) : "r"(a), "r"(rank)); return r; }
DEVI void st_async4(uint32_t dst, uint32_t a, uint32_t b, uint32_t c, uint32_t d, uint32_t bar) {
  asm volatile("st.async.weak.shared::cluster.mbarrier::complete_tx::bytes.v4.b32 [%0], {%1,%2,%3,%4}, [%5];"
               :: "r"(dst), "r"(a), "r"(b), "r"(c), "r"(d), "r"(bar) : "memory");
}
DEVI void st_either4(bool local, uint32_t dst, uint32_t a, uint32_t b, uint32_t c, uint32_t d, uint32_t bar) {
  asm volatile("{\n.reg .pred p;\nsetp.ne.b32 p, %6, 0;\n@p st.shared.v4.b32 [%0], {%1,%2,%3,%4};\n"
               "@!p st.async.weak.shared::cluster.mbarrier::complete_tx::bytes.v4.b32 [%0], {%1,%2,%3,%4}, [%5];\n}"
               :: "r"(dst), "r"(a), "r"(b), "r"(c), "r"(d), "r"(bar), "r"((int)local) : "memory");
}
DEVI void red_async_max(uint32_t dst, uint32_t a, uint32_t bar) {
  asm volatile("red.async.relaxed.cluster.shared::cluster.mbarrier::complete_tx::bytes.max.u32 [%0], %1, [%2];" :: "r"(dst), "r"(a), "r"(bar) : "memory");
}
DEVI void pf_line(const void* p) { asm volatile("prefetch.global.L2 [%0];" :: "l"(p) : "memory"); }
DEVI void bulk_commit() { asm volatile("cp.async.bulk.commit_group;" ::: "memory"); }
DEVI void bulk_wait_all() { asm volatile("cp.async.bulk.wait_group 0;" ::: "memory"); }
DEVI void bulk_wait_read() { asm volatile("cp.async.bulk.wait_group.read 0;" ::: "memory"); }
DEVI void prefetch_map(const CUtensorMap* m) { asm volatile("prefetch.tensormap [%0];" :: "l"(m) : "memory"); }

__host__ __device__ constexpr uint32_t dlo(uint32_t off, uint32_t lbo) { return (off >> 4) + ((lbo >> 4) << 16); }
struct Desc {
  uint64_t v;
  DEVI Desc(uint64_t z, uint32_t base, uint32_t sbo, uint32_t mode) : v(z + (base | (uint64_t)((sbo >> 4) | (mode << 30)) << 32)) { asm volatile("" : "+l"(v)); }
  DEVI void renew(uint64_t z) { asm volatile("add.s64 %0, %0, %1;" : "+l"(v) : "l"(z)); }
  DEVI uint64_t at(uint32_t lo) const { uint64_t r; asm volatile("add.s64 %0, %1, %2;" : "=l"(r) : "l"(v), "l"((int64_t)(int32_t)lo)); return r; }
};
DEVI uint32_t pack_bf16(float lo, float hi) { uint32_t r; asm("cvt.rn.bf16x2.f32 %0, %1, %2;" : "=r"(r) : "f"(hi), "f"(lo)); return r; }
DEVI uint32_t pack_f16(float lo, float hi) { uint32_t r; asm("cvt.rn.f16x2.f32 %0, %1, %2;" : "=r"(r) : "f"(hi), "f"(lo)); return r; }
DEVI void stsm4(uint32_t addr, uint32_t r0, uint32_t r1, uint32_t r2, uint32_t r3) {
  asm volatile("stmatrix.sync.aligned.m8n8.x4.shared.b16 [%0], {%1,%2,%3,%4};" :: "r"(addr), "r"(r0), "r"(r1), "r"(r2), "r"(r3) : "memory");
}
DEVI void sts128(uint32_t addr, uint32_t a, uint32_t b, uint32_t c, uint32_t d) {
  asm volatile("st.shared.v4.b32 [%0], {%1,%2,%3,%4};" :: "r"(addr), "r"(a), "r"(b), "r"(c), "r"(d) : "memory");
}
DEVI void sts32(uint32_t addr, uint32_t v) { asm volatile("st.shared.b32 [%0], %1;" :: "r"(addr), "r"(v) : "memory"); }
DEVI uint32_t lds32(uint32_t a) { uint32_t v; asm volatile("ld.shared.b32 %0, [%1];" : "=r"(v) : "r"(a)); return v; }
DEVI void lds128(uint32_t* v, uint32_t a) {
  asm volatile("ld.shared.v4.b32 {%0,%1,%2,%3}, [%4];" : "=r"(v[0]), "=r"(v[1]), "=r"(v[2]), "=r"(v[3]) : "r"(a));
}
DEVI void ldg128(uint32_t* v, const void* p) {
  asm volatile("ld.global.nc.L1::no_allocate.v4.b32 {%0,%1,%2,%3}, [%4];" : "=r"(v[0]), "=r"(v[1]), "=r"(v[2]), "=r"(v[3]) : "l"(p));
}
DEVI uint32_t ldg32(const void* p) { uint32_t v; asm volatile("ld.global.nc.L1::no_allocate.b32 %0, [%1];" : "=r"(v) : "l"(p)); return v; }
DEVI float rcp(float x) { float r; asm("rcp.approx.ftz.f32 %0, %1;" : "=f"(r) : "f"(x)); return r; }
DEVI float exp_sat(float t) {
  float e, s;
  asm("ex2.approx.ftz.f32 %0, %1;" : "=f"(e) : "f"(t * 1.4426950408889634f));
  asm("add.sat.f32 %0, %1, 0f358637BD;" : "=f"(s) : "f"(e));
  return s;
}
DEVI uint32_t phi2(float a, float b) {
  uint32_t r, o;
  asm("cvt.rn.relu.bf16x2.f32 %0, %1, %2;" : "=r"(r) : "f"(b), "f"(a));
  asm("add.rn.bf16x2 %0, %1, %2;" : "=r"(o) : "r"(r), "r"(pack_bf16(exp_sat(a), exp_sat(b))));
  return o;
}
DEVI void arrive_both(uint32_t bar, int lane, bool pred = true) {
  asm volatile("{\n.reg .pred p;\n.reg .b32 r;\nsetp.ne.b32 p, %2, 0;\nmapa.shared::cluster.u32 r, %0, %1;\n@p mbarrier.arrive.shared::cluster.b64 _, [r];\n}"
               :: "r"(bar), "r"(lane & 1), "r"((int)(pred && lane < 2)) : "memory");
}
DEVI uint32_t bmul2(uint32_t a, uint32_t b) { uint32_t r; asm("mul.rn.bf16x2 %0, %1, %2;" : "=r"(r) : "r"(a), "r"(b)); return r; }
DEVI uint32_t bfma2(uint32_t a, uint32_t b, uint32_t c) { uint32_t r; asm("fma.rn.bf16x2 %0, %1, %2, %3;" : "=r"(r) : "r"(a), "r"(b), "r"(c)); return r; }
DEVI uint32_t bamax2(uint32_t a, uint32_t b) { uint32_t r; asm("max.NaN.xorsign.abs.bf16x2 %0, %1, %2;" : "=r"(r) : "r"(a), "r"(b)); return r; }
DEVI uint32_t hmul2(uint32_t a, uint32_t b) { uint32_t r; asm("mul.rn.f16x2 %0, %1, %2;" : "=r"(r) : "r"(a), "r"(b)); return r; }
DEVI uint32_t hadd2(uint32_t a, uint32_t b) { uint32_t r; asm("add.rn.f16x2 %0, %1, %2;" : "=r"(r) : "r"(a), "r"(b)); return r; }
DEVI uint32_t hsub2(uint32_t a, uint32_t b) { uint32_t r; asm("sub.rn.f16x2 %0, %1, %2;" : "=r"(r) : "r"(a), "r"(b)); return r; }
DEVI uint32_t hfma2(uint32_t a, uint32_t b, uint32_t c) { uint32_t r; asm("fma.rn.f16x2 %0, %1, %2, %3;" : "=r"(r) : "r"(a), "r"(b), "r"(c)); return r; }
DEVI uint32_t hfnma2(uint32_t a, uint32_t b, uint32_t c) {
  uint32_t r; asm("{\n.reg .b32 n;\nneg.f16x2 n, %1;\nfma.rn.f16x2 %0, n, %2, %3;\n}" : "=r"(r) : "r"(a), "r"(b), "r"(c)); return r;
}
DEVI float bf_lo(uint32_t w) { return __uint_as_float(w << 16); }
DEVI float bf_hi(uint32_t w) { return __uint_as_float(w & 0xffff0000u); }

DEVI uint32_t chan_exponent(const uint32_t* w) {
  uint32_t m[4];
#pragma unroll
  for (int i = 0; i < 4; i++) m[i] = bamax2(w[i], w[i + 4]);
#pragma unroll
  for (int i = 8; i < 32; i++) m[i & 3] = bamax2(m[i & 3], w[i]);
  uint32_t x = bamax2(bamax2(m[0], m[1]), bamax2(m[2], m[3])) & 0x7fff7fffu;
  x = max(x >> 16, x & 0xffffu);
  x = __reduce_max_sync(0xffffffffu, x);
  return min(x >> 7, 251u);
}
DEVI uint32_t to_f16(uint32_t w, uint32_t mul) { const uint32_t y = bmul2(w, mul); return pack_f16(bf_lo(y), bf_hi(y)); }

struct Tile { int j, r; };
DEVI Tile tile_of() {
  int cta; asm volatile("mov.u32 %0, %%ctaid.x;" : "=r"(cta));
  const int cl = cta >> 1, lo = (cl - 4) >> 31, hi = (35 - cl) >> 31;
  const int p = cl - 4 + (lo & (36 + 7 * cl)) + (hi & ((((cl - 36) * 37) >> 8) + 1)), g = p & 7, rr = p >> 3;
  return Tile{(g & 6) | (cta & 1), 2 * rr + (g & 1)};
}

__host__ __device__ constexpr int upiece(int it) {
  for (int m = 0; m < 8; m++) if (U0 + m * UNUM / UDEN == it) return m;
  return -1;
}
static_assert(TAIL <= 3, "stage 27 is released inside the loop");
__host__ __device__ constexpr bool prew(int it) { return it >= UCV && it < UCV + 4 && it < 31; }

DEVI void twiddle(uint32_t& ore, uint32_t& oim, uint32_t re, uint32_t im, uint32_t t, uint32_t s) {
  re = hfma2(t, im, re);
  oim = hfma2(s, re, im);
  ore = hfma2(t, oim, re);
}

__global__ void __cluster_dims__(2, 1, 1) __launch_bounds__(kThreads, 1)
fused_kernel(const __grid_constant__ Params P) {
  extern __shared__ __align__(1024) uint8_t smem[];
  const int tid = threadIdx.x, lane = tid & 31;
  const int warp = tid >> 5, warpu = __shfl_sync(0xffffffffu, tid >> 5, 0);
  const int cta = blockIdx.x, rho = cta & 1, cl = cta >> 1;
  const uint32_t sb = SM_BASE + (rho << 24);
  const uint32_t tstart = clock32();
  auto bar = [&](int i) INL { return sb + SM_BAR + 8u * i; };
  auto load1 = [&](int it, int s, int j, int r, bool mc) INL {
    const uint32_t fb = bar(B_F1 + s), xs = sb + x1_off(it);
    mbar_expect(fb, (it & 1) ? 16384 : 32768);
    tma4d(sb + w1_off(s), &P.w1, 32 * it, 2 * j, 1, fb);
    if (!(it & 1)) {
      if (mc) tma2d_mc(xs + rho * 8192, &P.x, 32 * it, 128 * r + 64 * rho, fb);
      else { tma2d(xs, &P.x, 32 * it, 128 * r, fb); tma2d(xs + 8192, &P.x, 32 * it, 128 * r + 64, fb); }
    }
  };
  TSTAMP(tid == 0, 0); GSTAMP(tid == 0, 62);

  if (warpu == 8 && elect()) {
    prefetch_map(&P.w1); prefetch_map(&P.x);
    for (int i = 0; i < EARLY; i++) mbar_init(bar(B_F1 + slot1(i)), 1);
    const Tile T = tile_of();
    for (int i = 0; i < EARLY; i++) load1(i, slot1(i), T.j, T.r, false);
    TSTAMP(true, 18);
    for (int i = EARLY; i < NS1; i++) mbar_init(bar(B_F1 + slot1(i)), 1);
    asm volatile("fence.mbarrier_init.release.cluster;" ::: "memory");
  }
  if (warpu == 9 && elect()) {
    if (sb != (uint32_t)__cvta_generic_to_shared(smem)) __trap();
#pragma unroll
    for (int i = B_F2; i < B_Q; i++) mbar_init(bar(i), 1);
    mbar_expect(bar(B_H), 32768);
    asm volatile("fence.mbarrier_init.release.cluster;" ::: "memory");
  }
  if (warpu == 10 && elect()) {
#pragma unroll
    for (int i = B_Q; i < B_KVE; i++) mbar_init(bar(i), i < B_E1 ? 1 : 16);
    mbar_expect(bar(B_Q), 32768); mbar_expect(bar(B_U), 16384); mbar_expect(bar(B_MAX), 1024);
    asm volatile("fence.mbarrier_init.release.cluster;" ::: "memory");
  }
  if (warpu == 11 && elect()) {
#pragma unroll
    for (int i = B_KVE; i < B_COUNT; i++) mbar_init(bar(i), i < B_OFREE ? 8 : i == B_F2M ? 3 : i < B_Y ? 4 : 9);
    mbar_expect(bar(B_Y), 8192); mbar_expect(bar(B_Y + 1), 8192);
    asm volatile("fence.mbarrier_init.release.cluster;" ::: "memory");
  }
  __syncwarp();
  cluster_sync();

  if (warpu < 8) {
    asm volatile("setmaxnreg.inc.sync.aligned.u32 %0;" :: "n"(232));
    const int wg = warp >> 2, wq = warp & 3, g = lane >> 2, q = lane & 3;
    constexpr uint32_t sbq = SM_BASE >> 4;
    const uint32_t wgu = warpu >> 2;
    const uint64_t z64 = P.zero;
    Desc dA(z64, sbq + wgu * 512, 1024, 1), dB(z64, sbq, 1024, 1);
    const int srow = wg * 64 + wq * 16 + (lane & 15);
    const uint32_t stm = srow * 128 + (((lane >> 4) ^ (srow & 7)) << 4);
    auto stage2 = [&](float* acc, int n, bool first, bool wait = true) INL {
      const int s = slot2(n);
      if (wait) mbar_wait(bar(B_F2 + s), par2(n));
      const uint32_t da = s * (ST2 >> 4) + dlo(0, 16), db = s * (ST2 >> 4) + dlo(16384, 8192);
      wg_fence();
      const uint64_t a0 = dA.at(da), b0 = dB.at(db);
      if (first) mma_n128_init(acc, a0, b0); else mma_n128(acc, a0, b0);
#pragma unroll
      for (int kk = 1; kk < 4; kk++) mma_n128(acc, a0 + 2 * kk, b0 + kk * (2048 >> 4));
      wg_commit();
    };
    auto release2 = [&](int n) INL { arrive_both(bar(B_E2 + slot2(n)), lane); };
    auto publish = [&](int b) INL { fence_async_smem(); __syncwarp(); mbar_arrive_if(bar(b), lane == 0); };

    float aq[64];
    uint32_t f1[8], tw[4];
    uint32_t su[2][32], sh[2][32];
    uint32_t x0[4][8], x1[4][8], p0[2][8], p1[2][8], z0[2][8], z1[2][8];
    auto s1 = [&](uint32_t* d, uint32_t base) INL {
      Desc db(z64, sbq + wgu * 1024 + dlo(base, 128), 512, 0);
      mma_s1_init(d, f1, db.v);
      mma_s1(d, f1 + 4, db.at(256 >> 4));
      wg_commit();
    };
    const uint64_t dre = Desc(z64, sbq + dlo(SM_F2 + 512, 128), 256, 0).v, dim = Desc(z64, sbq + dlo(SM_F2, 128), 256, 0).v;
    auto fwd2 = [&](uint32_t (*x)[8], int c) INL {
      uint32_t a[4][8];
#pragma unroll
      for (int t = 0; t < 4; t++) {
        uint32_t* s = (t < 2 ? sh[c >> 1] : su[c >> 1]) + 16 * (c & 1) + 8 * (t & 1);
        pin<8>(s);
#pragma unroll
        for (int i = 0; i < 4; i++) twiddle(a[t][i], a[t][4 + i], s[4 * (i & 1) + (i & 2)], s[4 * (i & 1) + (i & 2) + 1], tw[i & 2], tw[(i & 2) + 1]);
      }
      wg_fence();
#pragma unroll
      for (int t = 0; t < 4; t++) { mma_s2_init(x[t], a[t], dre); mma_s2(x[t], a[t] + 4, dim); }
      wg_commit();
    };
    auto half2 = [&](uint32_t (*x)[8], uint32_t* s) INL {
      uint32_t a[2][8];
      pin<16>(s);
#pragma unroll
      for (int t = 0; t < 2; t++)
#pragma unroll
        for (int i = 0; i < 4; i++) twiddle(a[t][i], a[t][4 + i], s[8 * t + 4 * (i & 1) + (i & 2)], s[8 * t + 4 * (i & 1) + (i & 2) + 1], tw[i & 2], tw[(i & 2) + 1]);
      wg_fence();
#pragma unroll
      for (int t = 0; t < 2; t++) { mma_s2_init(x[t], a[t], dre); mma_s2(x[t], a[t] + 4, dim); }
      wg_commit();
    };
    auto product = [&](uint32_t (*a)[8], uint32_t (*x)[8], int i) INL {
#pragma unroll
      for (int t = 0; t < 4; t++) { pin<2>(x[t] + i); pin<2>(x[t] + 4 + i); }
      auto hr = [&](int l) INL { return x[l >> 1][i + (l & 1)]; };
      auto hi = [&](int l) INL { return x[l >> 1][4 + i + (l & 1)]; };
      auto ur = [&](int l) INL { return x[2 + (l >> 1)][i + (l & 1)]; };
      auto ui = [&](int l) INL { return x[2 + (l >> 1)][4 + i + (l & 1)]; };
      uint32_t gr[4], gi[4];
      gr[0] = hr(0); gi[0] = hi(0);
#pragma unroll
      for (int l = 1; l < 4; l++) { gr[l] = hadd2(hr(l), hi(l - 1)); gi[l] = hsub2(hi(l), hr(l - 1)); }
#pragma unroll
      for (int p = 0; p < 4; p++) {
        uint32_t re = hfnma2(gi[0], ui(p), hmul2(gr[0], ur(p))), im = hfma2(gi[0], ur(p), hmul2(gr[0], ui(p)));
#pragma unroll
        for (int l = 1; l <= p; l++) {
          re = hfnma2(gi[l], ui(p - l), hfma2(gr[l], ur(p - l), re));
          im = hfma2(gi[l], ur(p - l), hfma2(gr[l], ui(p - l), im));
        }
        a[p >> 1][i + (p & 1)] = re; a[p >> 1][4 + i + (p & 1)] = im;
      }
#pragma unroll
      for (int t = 0; t < 2; t++) { pin<2>(a[t] + i); pin<2>(a[t] + 4 + i); }
    };
    auto inv1 = [&](uint32_t (*z)[8], uint32_t (*a)[8]) INL {
      wg_fence();
#pragma unroll
      for (int t = 0; t < 2; t++) { mma_s2_init(z[t], a[t], dre); mma_s2_neg(z[t], a[t] + 4, dim); }
      wg_commit();
    };
    auto zstore = [&](uint32_t (*z)[8], int c) INL {
      const uint32_t zoff = sb + RB + (q >> 1) * (RU + 16 - RB) + (8 * rho + 4 * wg) * 2048 + (4 * (8 * wq + g) + 2 * (q & 1)) * 16;
#pragma unroll
      for (int t = 0; t < 2; t++) {
        uint32_t a[8];
        pin<8>(z[t]);
#pragma unroll
        for (int i = 0; i < 4; i++) twiddle(a[i], a[4 + i], z[t][i], z[t][4 + i], tw[i & 2], tw[(i & 2) + 1]);
        const uint32_t dst = zoff + t * (16384 - rho * 32768) + c * 2048;
        sts128(dst, a[0], a[1], a[2], a[3]);
        sts128(dst + 16, a[4], a[5], a[6], a[7]);
      }
    };
    float kvr[18];
    auto kvstore = [&]() INL {
      const uint32_t dst = sb + kv_off(warp >> 1) + (warp & 1) * 256 + lane * 4;
      pin<18>(kvr);
#pragma unroll
      for (int b = 0; b < 4; b++) { sts32(dst + b * 512, pack_bf16(kvr[4 * b], kvr[4 * b + 1])); sts32(dst + b * 512 + 128, pack_bf16(kvr[4 * b + 2], kvr[4 * b + 3])); }
      sts32(dst + 2048, pack_bf16(kvr[16], kvr[16])); sts32(dst + 2176, pack_bf16(kvr[17], kvr[17]));
      publish(B_KVI);
    };
    {
      float ak[64], av[64];
      Desc dK(z64, sbq + wgu * 256, 1024, 1);
      auto kstep = [&](int it) INL {
        const int s = slot1(it);
        if (!prew(it - 1)) mbar_wait(bar(B_F1 + s), (it / NS1) & 1);
        TSTAMP(tid == 0 && it == 0, 1);
        const uint32_t dx = dlo(x1_off(it) + (it & 1) * 64, 16), dk = dlo(w1_off(s), 16), dv = dlo(w1_off(s) + 8192, 4096);
        if (s == 0) { dK.renew(z64); dA.renew(z64); dB.renew(z64); }
        wg_fence();
        if (it == 0) { mma_kt_init(ak, dK.at(dk), dB.at(dx)); mma_n128_init(av, dA.at(dx), dB.at(dv)); }
        else { mma_kt(ak, dK.at(dk), dB.at(dx)); mma_n128(av, dA.at(dx), dB.at(dv)); }
        mma_kt(ak, dK.at(dk + (2048 >> 4)), dB.at(dx + 2));
        mma_n128(av, dA.at(dx + 2), dB.at(dv + (2048 >> 4)));
        wg_commit();
        wg_wait<1>();
        if (it > 0) arrive_both(bar(B_E1 + (s + NS1 - 1) % NS1), lane);
        if (prew(it)) mbar_wait(bar(B_F1 + slot1(it + 1)), ((it + 1) / NS1) & 1);
        KSTAMP(it);
      };
      uint32_t kk[35], u[32], sw[4], mx[2], um, umul, ud, eu;
      unsigned short dskip;
      float tap0;
      const bool local = (g >> 2) == rho;
      auto calcu = [&](int e0, int e1) INL {
#pragma unroll
        for (int e = e0; e < e1; e++) {
          pin<1>(kk + 3 + e); pin<1>(u + e);
          u[e] = bmul2(bfma2(kk[3 + e], sw[0], bfma2(kk[2 + e], sw[1], bfma2(kk[1 + e], sw[2], bmul2(kk[e], sw[3])))), u[e]);
          um = bamax2(um, u[e]);
          pin<1>(u + e);
        }
        pin<1>(&um);
      };
      sts32(sb + SM_MAX + (lane & 15) * 4, 0);
      ldg128(sw, P.shift_k + (cl * 16 + 2 * g) * 4);
#pragma unroll
      for (int e = 0; e < 3; e++) kk[e] = ldg32(P.k_ptr + (1021 + e) * 1024 + 16 * cl + 2 * g);
      asm volatile("ld.global.nc.b16 %0, [%1];" : "=h"(dskip) : "l"(P.ssm_d + 8 * cta + warp));
      auto side = [&](int it) INL {
        if (it == 1) {
          pin<4>(sw);
          const uint32_t t0 = __byte_perm(sw[0], sw[2], 0x5410), t1 = __byte_perm(sw[0], sw[2], 0x7632), t2 = __byte_perm(sw[1], sw[3], 0x5410);
          sw[3] = __byte_perm(sw[1], sw[3], 0x7632); sw[0] = t0; sw[1] = t1; sw[2] = t2;
          const bool halo = rho && warp + q == 0;
#pragma unroll
          for (int e = 0; e < 3; e++) kk[e] = halo ? kk[e] : 0u;
          tap0 = lane == 0 ? bf_lo(dskip) : 0.f;
          um = 0;
          pin<4>(sw); pin<3>(kk); pin<1>(&tap0);
        }
        if (CE && it == CE) { ldg128(f1, P.tab + (tid & 127) * 4); ldg128(f1 + 4, P.tab + 512 + (tid & 127) * 4); ldg128(tw, P.tab + 1024 + (tid & 127) * 4); }
        if (upiece(it - 1) >= 0) {
          const int m = upiece(it - 1);
          calcu(m == 0 ? 3 : 4 * m, 4 * m + 4);
          if (m < 4) mbar_arrive_if(bar(B_KVE + m), lane == 0);
          if (m == 7) {
            pin<3>(kk);
            calcu(0, 3);
            um = bamax2(um, __shfl_xor_sync(0xffffffffu, um, 1));
            um = bamax2(um, __shfl_xor_sync(0xffffffffu, um, 2));
            red_async_max(mapa(sb + SM_MAX + g * 8 + (q & 1) * 4, q >> 1), min((um >> (7 + 16 * (q & 1))) & 0xffu, 251u), mapa(bar(B_MAX), q >> 1));
          }
        }
        if (upiece(it) >= 0) {
          const int m = upiece(it);
          const uint32_t a = sb + RU + (m & 3) * 8192 + warp * 128 + q * 32 + g * 4;
          mbar_wait(bar(B_KVL + (m & 3)), m >> 2);
#pragma unroll
          for (int e = 0; e < 4; e++) { kk[3 + 4 * m + e] = lds32(a + e * 1024); u[4 * m + e] = lds32(a + 4096 + e * 1024); }
          if (m == 7) {
#pragma unroll
            for (int e = 0; e < 3; e++)
              asm volatile("{\n.reg .pred p;\nsetp.ne.b32 p, %2, 0;\n@p ld.shared.b32 %0, [%1];\n}" : "+r"(kk[e]) : "r"(a + (e + 1) * 1024 - 32), "r"(warp + q));
          }
        }
        if (it == UCV - 1 - UPRE) {
          mbar_wait(bar(B_MAX), 0);
          TSTAMP(tid == 0, 5);
          asm volatile("ld.shared.v2.b32 {%0,%1}, [%2];" : "=r"(mx[0]), "=r"(mx[1]) : "r"(sb + SM_MAX + g * 8));
          eu = lds32(sb + SM_MAX + (8 * rho + warp) * 4);
        }
        if (it == UCV - UPRE) {
          pin<2>(mx);
          umul = (0x00fd00fdu - (mx[0] | mx[1] << 16)) << 7;
          ud = mapa(sb + RU + (g & 3) * 8192 + (2 * rho + wg) * 1024 + (4 * wq + q) * 16, g >> 2);
        }
        if (it >= UCV && it < UCV + 4) {
          const int i = it - UCV;
          uint32_t* y = u + 8 * i;
          pin<8>(y);
#pragma unroll
          for (int e = 0; e < 8; e++) y[e] = bmul2(y[e], umul);
          const uint32_t dst = ud + (i & 1) * 512 + (i >> 1) * 256, ub = mapa(bar(B_U), rho ^ 1);
          st_either4(local, dst, pack_f16(bf_lo(y[0]), bf_lo(y[1])), pack_f16(bf_lo(y[2]), bf_lo(y[3])), pack_f16(bf_lo(y[4]), bf_lo(y[5])), pack_f16(bf_lo(y[6]), bf_lo(y[7])), ub);
          st_either4(local, dst + 4096, pack_f16(bf_hi(y[0]), bf_hi(y[1])), pack_f16(bf_hi(y[2]), bf_hi(y[3])), pack_f16(bf_hi(y[4]), bf_hi(y[5])), pack_f16(bf_hi(y[6]), bf_hi(y[7])), ub);
        }
      };
#pragma unroll
      for (int it = 0; it < 32; it++) { kstep(it); side(it); }
      auto qstep = [&](int n, bool wait = true) INL {
        if ((n & 3) == 0) { dA.renew(z64); dB.renew(z64); }
        stage2(aq, n, n == 0, wait);
        wg_wait<1>();
        if (n == 0) arrive_both(bar(B_E1 + NS1 - 1), lane); else release2(n - 1);
        QSTAMP(n);
      };
      uint32_t pk[32];
      auto phik = [&](int i0, int i1) INL {
#pragma unroll
        for (int i = i0; i < i1; i++) { pin<2>(ak + 2 * i); pk[i] = phi2(ak[2 * i], ak[2 * i + 1]); pin<1>(pk + i); }
      };
      const uint32_t rot = ROT == 0 ? 0 : ROT == 1 ? tile_of().r & 3 : (tile_of().r >> 1) & 3, stv = stm ^ (rot << 4);
      auto vst1 = [&](int kt) INL {
        float* a = av + 8 * kt;
        pin<8>(a);
        stsm4(sb + RA + (kt >> 2) * 16384 + (stv ^ ((kt & 3) << 5)), pack_bf16(a[0], a[1]), pack_bf16(a[2], a[3]), pack_bf16(a[4], a[5]), pack_bf16(a[6], a[7]));
      };
      auto vst = [&](int k0, int k1) INL {
#pragma unroll
        for (int kt = k0; kt < k1; kt++) vst1(kt);
      };
      float dkv[36];
      Desc dV(z64, sbq + wgu * (1024u - (1024u << 16)) + dlo(RA, SM_ONES - RA), 1024, 1);
      auto kvmma = [&](int k0, int k1) INL {
        wg_fence();
#pragma unroll
        for (int ks = k0; ks < k1; ks++) {
          const uint64_t db = dV.at(ks * (128u - (128u << 16)));
          if (ks == 0) mma_kv_init(dkv, pk, db); else mma_kv(dkv, pk + 4 * ks, db);
        }
        wg_commit();
      };
      float* gacc;
      auto kvred = [&](int b) INL {
        const bool hh = wq >> 1;
        asm volatile("red.relaxed.gpu.global.add.v4.f32 [%0], {%1,%2,%3,%4};" :: "l"(gacc + (b ^ rot) * 128), "f"(hh ? dkv[16 + 4 * b] : dkv[4 * b]),
                     "f"(hh ? dkv[17 + 4 * b] : dkv[1 + 4 * b]), "f"(hh ? dkv[18 + 4 * b] : dkv[2 + 4 * b]), "f"(hh ? dkv[19 + 4 * b] : dkv[3 + 4 * b]) : "memory");
        if (b == 3) {
          asm volatile("{\n.reg .pred p;\nsetp.eq.s32 p, %3, 0;\n@p red.relaxed.gpu.global.add.v2.f32 [%0], {%1,%2};\n}"
                       :: "l"(gacc + 4096 - warp * 496 - g * 14), "f"(dkv[32]), "f"(dkv[34]), "r"(q) : "memory");
          __syncwarp();
          mbar_arrive_if(bar(B_KVP), lane == 0);
          TSTAMP(tid == 0, 4);
        }
      };
      auto consts = [&]() INL {
        if (!CE) { ldg128(f1, P.tab + (tid & 127) * 4); ldg128(f1 + 4, P.tab + 512 + (tid & 127) * 4); ldg128(tw, P.tab + 1024 + (tid & 127) * 4); }
        gacc = &P.g->kv[tile_of().j][warp * 512 + lane * 4];
      };
      uint32_t w[32], hmul;
      auto hload = [&](int i0, int i1) INL {
        const uint32_t a = sb + RB + warp * 4096 + (((lane >> 2) & 1) + (lane & 2) + 4 * (lane & 1) + (((lane << 2) ^ lane) & 24)) * 16;
#pragma unroll
        for (int i = i0; i < i1; i++) lds128(w + 4 * i, a + i * 512);
      };
      auto hmax = [&]() INL {
        pin<32>(w);
        tap0 += bf_lo(w[0]);
        w[0] = pack_bf16(tap0, bf_hi(w[0]));
        hmul = (252u - chan_exponent(w)) * 0x00800080u;
        const int e = min(max((int)(eu + 128 - (hmul >> 23)), 0), 254);
        asm volatile("st.shared.b16 [%0], %1;" :: "r"(sb + SM_SCALE + 2 * warp), "h"((unsigned short)(e << 7)) : "memory");
      };
      auto hstore = [&](int i0, int i1) INL {
        const uint32_t dst = sb + RB + warp * 4096 + (lane & 6) * 128 + ((lane ^ ((lane >> 2) & 6)) & 7) * 16;
#pragma unroll
        for (int i = i0; i < i1; i++) {
          pin<4>(w + 4 * i);
          const uint32_t w0 = i == 0 ? pack_f16(tap0 * bf_lo(hmul), bf_hi(w[0]) * bf_lo(hmul)) : to_f16(w[4 * i], hmul);
          sts128(dst + (i >> 1) * 1024 + (i & 1) * 128, w0, to_f16(w[4 * i + 1], hmul), to_f16(w[4 * i + 2], hmul), to_f16(w[4 * i + 3], hmul));
        }
      };
      auto kvload = [&]() INL {
        mbar_wait(bar(B_KV), 0);
        TSTAMP(tid == 0, 7);
#pragma unroll
        for (int b = 0; b < 4; b++)
          asm volatile("ld.global.cg.v4.f32 {%0,%1,%2,%3}, [%4];" : "=f"(kvr[4 * b]), "=f"(kvr[4 * b + 1]), "=f"(kvr[4 * b + 2]), "=f"(kvr[4 * b + 3]) : "l"(gacc + b * 128) : "memory");
        asm volatile("ld.global.cg.v2.f32 {%0,%1}, [%2];" : "=f"(kvr[16]), "=f"(kvr[17]) : "l"(gacc + 4096 - warp * 496 - g * 14 - q * 4) : "memory");
      };
      qstep(0);
      TSTAMP(tid == 0, 2);
#define WE1 mbar_wait(bar(B_E1 + NS1 - 1), 1)
#define PV publish(B_VST)
#define WV0 mbar_wait(bar(B_ZERO), 0); mbar_wait(bar(B_VST), 0)
#define WH mbar_wait(bar(B_H), 0)
#define KVD pin<36>(dkv); mbar_arrive_if(bar(B_KVM), lane == 0)
#define S1U0 mbar_wait(bar(B_U2), 0); wg_fence(); s1(su[0], RU)
#define S1H0 mbar_wait(bar(B_VST), 1); wg_fence(); s1(sh[0], RB)
#define WF mbar_wait(bar(B_F2M), 0)
#define HU(c) half2((c ? x1 : x0) + 2, su[0] + 16 * c)
#define HH(c) half2(c ? x1 : x0, sh[0] + 16 * c)
#define PD(n) product(n < 2 ? p0 : p1, n < 2 ? x0 : x1, 2 * (n & 1))
#define Q(n) qstep(n)
#define QL(n, code) mbar_wait(bar(B_F2 + slot2(n)), par2(n)); code; qstep(n, false)
      phik(0, 4); WE1; vst(0, 3); Q(1); vst(3, 6); phik(4, 8); Q(2); vst(6, 8); PV; phik(8, 14); Q(3); WV0; kvmma(0, 3); consts(); phik(14, 24); Q(4); kvmma(3, 6); WH; hload(0, 4); phik(24, 32); kvmma(6, 8); hload(4, 8); Q(5); KVD; hmax(); kvred(0); Q(6); S1U0; hstore(0, 4); kvred(1); Q(7); hstore(4, 6); kvred(2); Q(8); hstore(6, 8); PV; kvred(3); Q(9); S1H0; WF; HU(0); HU(1); Q(10); HH(0); HH(1); Q(11); PD(0); Q(12); PD(1); Q(13); kvload(); PD(2); Q(14); PD(3); Q(15);
    }

    float acc[64];
    {
      uint32_t pq[4][8];
      float dn[4][20];
      Desc dO(z64, sbq + dlo(0, 128), 512, 0);
      auto phiq = [&](int h) INL {
        pin<16>(aq + 16 * h);
#pragma unroll
        for (int i = 0; i < 8; i++) pq[h][i] = phi2(aq[16 * h + 2 * i], aq[16 * h + 2 * i + 1]);
        pin<8>(pq[h]);
      };
      auto omma = [&](int h) INL {
        wg_fence();
        mma_o_init(dn[h], pq[h], dO.at(kv_off(h) >> 4));
        mma_o(dn[h], pq[h] + 4, dO.at((kv_off(h) + 256) >> 4));
        wg_commit();
      };
      auto onorm = [&](int h) INL {
        pin<20>(dn[h]);
        const float i0 = rcp(dn[h][16] + 1e-6f), i1 = rcp(dn[h][18] + 1e-6f);
#pragma unroll
        for (int hf = 0; hf < 2; hf++) {
          const float* a = dn[h] + 8 * hf;
          stsm4(sb + (h >> 1) * ST2 + (stm ^ (((h & 1) * 2 + hf) << 5)), pack_bf16(a[0] * i0, a[1] * i0), pack_bf16(a[2] * i1, a[3] * i1),
                pack_bf16(a[4] * i0, a[5] * i0), pack_bf16(a[6] * i1, a[7] * i1));
        }
        if (h & 1) publish(B_OW + (h >> 1));
      };
      wg_fence();
      s1(su[1], RU + 8192);
      kvstore();
      wg_wait<1>();
      release2(15);
      TSTAMP(tid == 0, 6);
      auto own = [&](int c) INL { if (c == 0) { dA.renew(z64); dB.renew(z64); } mbar_wait(bar(B_OW + c), 0); stage2(acc, 16 + c, c == 0); };
      uint32_t gf[4][4];
#define WKV mbar_wait(bar(B_KVI), 0)
#define W(n) wg_wait<n>()
#define S1H wg_fence(); s1(sh[1], RB + 8192)
#define T8 TSTAMP(tid == 0, 8)
#define T9 TSTAMP(tid == 0, 9)
#define WS1 mbar_wait(bar(B_OW + 1), 0)
#define PR(p, x) product(p, x, 0); product(p, x, 2)
#define FIN PR(p0, x0); inv1(z0, p0); own(1); W(2); release2(16)
      phiq(0); phiq(1); WKV; omma(0); omma(1); W(1); onorm(0); W(0); onorm(1); T8; S1H; phiq(2); omma(2); phiq(3); W(0); onorm(2); omma(3); inv1(z0, p0); W(1); onorm(3); T9; inv1(z1, p1); fwd2(x0, 2); W(1); WS1; zstore(z0, 0); zstore(z1, 1); W(0); own(0); fwd2(x1, 3); FIN;
      ldg128(gf[1], P.tab + 1536 + (tid & 127) * 4); ldg128(gf[3], P.tab + 2048 + (tid & 127) * 4);
      product(p1, x1, 0); product(p1, x1, 2);
      inv1(z1, p1);
      if (S18 == 3) { stage2(acc, 18, false); wg_wait<3>(); } else wg_wait<2>();
      zstore(z0, 2);
#pragma unroll
      for (int i = 0; i < 4; i += 2) {
        pin<4>(gf[i + 1]);
        gf[i][0] = gf[i][1] = gf[i + 1][0]; gf[i][2] = gf[i][3] = gf[i + 1][1];
        gf[i + 1][0] = gf[i + 1][1] = gf[i + 1][2]; gf[i + 1][2] = gf[i + 1][3];
        pin<4>(gf[i]); pin<4>(gf[i + 1]);
      }
      if (S18 == 1) { stage2(acc, 18, false); wg_wait<1>(); } else if (S18 == 3) wg_wait<1>(); else wg_wait<0>();
      release2(17);
      zstore(z1, 3);
      publish(B_ZST);
      TSTAMP(tid == 0, 10);
      if (S18 == 2) stage2(acc, 18, false);
      const uint32_t qa = sb + RA + warp * 4096 + lane * 32 + ((rho ^ g) & 1) * 16;
      uint32_t qv[4][4];
      mbar_wait(bar(B_Q), 0);
#pragma unroll
      for (int i = 0; i < 4; i++) lds128(qv[i], qa + i * 1024);
      mbar_wait(bar(B_ZST), 0);
      float y[64];
      {
        Desc db(z64, sbq + wgu * ((RU + 16 - RB) >> 4) + dlo(RB, 128), 2048, 0);
        wg_fence();
        mma_i2_init(y, gf[0], db.v, 0xEEEE4444u);
#pragma unroll
        for (int i = 1; i < 4; i++) mma_i2(y, gf[i], db.at(i * (512 >> 4)), 0xEEEE4444u);
        wg_commit();
      }
      uint32_t sc[4];
      lds128(sc, sb + SM_SCALE);
      TSTAMP(tid == 0, 11);
      constexpr int NY = S18 ? 19 : 18;
      stage2(acc, NY, false);
      TSTAMP(tid == 0, 13);
      wg_wait<1>();
      QSTAMP(NY);
      if (S18) release2(18);
      arrive_both(bar(B_I2), lane);
      pin<64>(y);
      uint32_t yv[8][4];
#pragma unroll
      for (int i = 0; i < 8; i++)
#pragma unroll
        for (int m = 0; m < 4; m++) yv[i][m] = bmul2(pack_bf16(y[32 * (i >> 2) + (i & 3) + 8 * m], y[32 * (i >> 2) + (i & 3) + 8 * m + 4]), sc[m]);
      pin<32>(&yv[0][0]);
      stage2(acc, NY + 1, false);
      wg_wait<1>();
      QSTAMP(NY + 1);
      release2(NY);
      mbar_wait(bar(B_I2), 0);
      const uint32_t yr = mapa(sb + Y_IN + tid * 16 + warp * 1536, rho ^ 1), yb = mapa(bar(B_Y), rho ^ 1);
      dA.renew(z64); dB.renew(z64);
#pragma unroll
      for (int i = 0; i < 4; i++) {
        if (i == 2 || (i && YV == 4) || (i == 1 && YV == 3)) {
          const int n = NY + 1 + (YV == 2 ? 1 : i);
          stage2(acc, n, false); wg_wait<1>(); QSTAMP(n); release2(n - 1);
        }
        pin<4>(qv[i]);
        sts128(qa + i * 1024, bmul2(yv[i][0], qv[i][0]), bmul2(yv[i][1], qv[i][1]), bmul2(yv[i][2], qv[i][2]), bmul2(yv[i][3], qv[i][3]));
        st_async4(yr + i * 512, yv[4 + i][0], yv[4 + i][1], yv[4 + i][2], yv[4 + i][3], yb + 8 * (i >> 1));
        if (i & 1) { __syncwarp(); mbar_arrive_if(bar(B_Y + (i >> 1)), lane == 0); }
      }
      TSTAMP(tid == 0, 12);
    }
#pragma unroll 1
    for (int n = (S18 ? 20 : 19) + YV; n < 32 - TAIL; n++) {
      stage2(acc, n, false);
      TSTAMP(tid == 0 && n == 26, 14);
      wg_wait<1>();
      release2(n - 1);
      QSTAMP(n);
    }
    {
      const Tile T = tile_of();
      dA.renew(z64); dB.renew(z64);
      if (TAIL > 1) mbar_wait(bar(B_STG), wgu ^ 1);
#pragma unroll
      for (int n = 32 - TAIL; n < 32; n++) {
        if (n == 31 && TAILE) mbar_arrive_if(bar(B_STG), wgu == 0 && lane == 0);
        stage2(acc, n, false);
      }
      if (!TAILE) mbar_arrive_if(bar(B_STG), wgu == 0 && lane == 0);
      mbar_wait(bar(B_E2 + 5), 1);
      wg_wait<0>();
      TSTAMP(tid == 0, 17); TSTAMP(tid == 128, 15);
      pin<64>(acc);
#pragma unroll
      for (int c = 0; c < 2; c++) {
#pragma unroll
        for (int t = 0; t < 4; t++) {
          const float* a = acc + 32 * c + 8 * t;
          stsm4(sb + RB + c * 16384 + (stm ^ (t << 5)), pack_bf16(a[0], a[1]), pack_bf16(a[2], a[3]), pack_bf16(a[4], a[5]), pack_bf16(a[6], a[7]));
        }
        fence_async_smem();
        __syncwarp();
        tma2d_store_e(&P.outa, sb + RB + c * 16384 + warpu * 2048, 128 * T.j + 64 * c, 128 * T.r + 16 * warpu);
      }
      bulk_wait_read();
      TSTAMP(tid == 128, 16);
    }
    if (ENDS) { __syncwarp(); cluster_sync(); }
  } else {
    asm volatile("setmaxnreg.dec.sync.aligned.u32 %0;" :: "n"(40));
    const Tile T = tile_of();
    const int j = T.j, r = T.r;
    auto kcol = [&](int n) INL {
      return n < 20 ? 128 * (j ^ ((n >> 1) & 1)) + 64 * (n & 1) : 128 * (((j & 6) + n - (n < 26 ? 18 : 24)) & 7) + (n < 26 ? 0 : 64);
    };
    if (warpu == 8) {
      uint32_t ph = 0;
      int s = slot1(EARLY);
#pragma unroll 1
      for (int it = EARLY; it < 32; ++it, s = s + 1 == NS1 ? 0 : s + 1) {
        if (it >= NS1) { mbar_wait(bar(B_E1 + s), (ph >> s) & 1); ph ^= 1u << s; }
        if (elect()) load1(it, s, j, r, true);
      }
#pragma unroll 1
      for (int n = 0; n < 16; ++n) {
        const int s = n & 3, i = n + (n >> 1);
        mbar_wait(bar(n < 4 ? B_E1 + i : B_E2 + s), n < 4 ? (ph >> i) & 1 : ((n >> 2) - 1) & 1);
        const uint32_t st = sb + s * ST2, fb = bar(B_F2 + s);
        if (elect()) {
          mbar_expect(fb, ST2);
          tma4d(st + 16384, &P.w2, 64 * n, 2 * j, 0, fb);
          tma2d_mc(st + rho * 8192, &P.x, 64 * n, 128 * r + 64 * rho, fb);
        }
      }
      auto loadw = [&](int n) INL {
        const int s = n & 3;
        mbar_wait(bar(B_E2 + s), ((n >> 2) - 1) & 1);
        if (elect()) { mbar_expect(bar(B_F2 + s), n < 18 ? 16384 : ST2); tma4d(sb + s * ST2 + 16384, &P.wo, kcol(n), 2 * j, 0, bar(B_F2 + s)); }
      };
#pragma unroll 1
      for (int n = 16; n < 20; ++n) {
        if (elect()) tma5d(sb + RA + (n - 16) * 8192, &P.q, 16 * cl, 2 * rho, 2 * (n & 2), 2 * (n & 1), bar(B_Q));
        loadw(n);
      }
#pragma unroll 1
      for (int n = 18; n < 20; ++n) {
        const uint32_t st = sb + (n & 3) * ST2, fb = bar(B_F2 + (n & 3));
        mbar_wait(bar(B_RDY + n - 18), 0);
        asm volatile("fence.proxy.async.global;" ::: "memory");
        if (elect()) { tma2d(st, &P.o, kcol(n), 128 * r, fb); tma2d(st + 8192, &P.o, kcol(n), 128 * r + 64, fb); }
      }
      mbar_wait(bar(B_OFREE), 0);
      uint64_t slots = 0x103251032510ull, frees = 0x103251032410ull;
      uint32_t pars = 0xc9f, kc = 128 * (j & 6) + 256;
#pragma unroll 1
      for (int n = 20; n < 32; ++n, slots >>= 4, frees >>= 4, pars >>= 1, kc += n == 26 ? 448 : 128) {
        const uint32_t s = slots & 7, st = sb + s * ST2, fb = bar(B_F2 + s);
        mbar_wait(bar(B_RDY + n - 18), 0);
        mbar_wait(bar(B_E2 + (frees & 7)), ~pars & 1);
        if (elect()) {
          mbar_expect(fb, ST2);
          tma4d(st + 16384, &P.wo, kc & 1023, 2 * j, 0, fb);
          tma2d_mc(st + rho * 8192, &P.o, kc & 1023, 128 * r + 64 * rho, fb);
        }
      }
    } else {
      const int at = tid - 288, aw = warpu - 9;
      if (at < KV_WORDS / 64) reinterpret_cast<float4*>(&P.g->kv[j][r * (KV_WORDS / 16)])[at] = make_float4(0.f, 0.f, 0.f, 0.f);
      else if (at >= 80) sts128(sb + SM_ONES + (at & 15) * 128 + (at & 7) * 16, 0x3f803f80u, 0x3f803f80u, 0x3f803f80u, 0x3f803f80u);
      fence_async_smem();
      bar_sync(4, 96);
      if (at == 64) asm volatile("fence.release.gpu;\nred.relaxed.gpu.global.add.u32 [%0], 1;" :: "l"(&P.g->zflag[j * 32]) : "memory");
      const unsigned epoch = ld_relaxed(&P.g->epoch[cta]);
      if (aw == 1) {
#pragma unroll 1
        for (int m = 0; m < 16; m++) {
          const int s = (m >> 1) & 3;
          pace(tstart, PREP0 + m * PREPGAP);
          if (m >= 8) mbar_wait(bar(B_KVE + s), 0);
          if (elect()) {
            if (!(m & 1)) mbar_expect(bar(B_KVL + s), 8192);
            tma3d(sb + RU + (m & 7) * 4096, (m & 1) ? &P.v : &P.k, 16 * cl, 32 * rho, 2 * (m & 14), bar(B_KVL + s));
          }
        }
#pragma unroll 1
        for (int m = 0; m < 8; m++) {
          pace(tstart, HT0 + m * HGAP);
          if (elect()) bulk_load(sb + RB + m * 4096, P.ssm_k + (size_t)(8 * cta + m) * 2048, 4096, bar(B_H));
        }
      }
      if (at == 0) { flag_wait(&P.g->zflag[j * 32], 16u * (epoch + 1)); mbar_arrive(bar(B_ZERO)); }
      __syncwarp();
      if (at < 80) pf_line(P.tab + at * 32);
      if (aw == 2) {
        if (elect()) { prefetch_map(&P.w2); prefetch_map(&P.wo); prefetch_map(&P.o); prefetch_map(&P.q); prefetch_map(&P.outb); prefetch_map(&P.outa); }
#pragma unroll 1
        for (int m = 0; m < 16; m++) {
          pace(tstart, m < 4 ? WQT + m * 500 : QT + (m - 4) * QGAP);
          pf_line(m < 4 ? P.w_ptr + (size_t)(cta + (2 * m + (lane >> 4)) * 128) * 3072 + (lane & 15) * 64
                        : (m < 12 ? P.q_ptr + cta * 16384 - 8192 : P.wo_ptr + cta * 8192 - 24576) + m * 2048 + lane * 64);
        }
      }
      uint32_t f2[4];
      ldg128(f2, P.tab + 2560 + at * 4);
      if (at == 0) { mbar_wait_long(bar(B_U), 0); fence_async_smem(); mbar_arrive(bar(B_U2)); }
      mbar_wait_long(bar(B_KVM), 0);
      sts128(sb + SM_F2 + at * 16, f2[0], f2[1], f2[2], f2[3]);
      fence_async_smem();
      __syncwarp();
      mbar_arrive_if(bar(B_F2M), lane == 0);
      if (aw == 2 && elect()) {
        mbar_wait(bar(B_KVP), 0);
        asm volatile("fence.release.gpu;\nred.relaxed.gpu.global.add.u32 [%0], 1;" :: "l"(&P.g->kvflag[j * 32]) : "memory");
        flag_wait(&P.g->kvflag[j * 32], 16u * (epoch + 1));
        mbar_arrive(bar(B_KV));
        TSTAMP(true, 19);
      }
      __syncwarp();
      if (aw < 2) {
        {
          const int c = aw;
          mbar_wait_long(bar(B_OW + c), 0);
          if (c == 1 && PUB) mbar_wait(bar(B_ZERO), 1);
          if (elect()) {
            const uint32_t src = sb + c * ST2;
            tma2d_store(&P.o, src, 128 * j + 64 * c, 128 * r);
            tma2d_store(&P.o, src + 8192, 128 * j + 64 * c, 128 * r + 64);
            bulk_commit();
            bulk_wait_all();
            TSTAMP(c == 0, 21); TSTAMP(c == 1, 26);
            if (c == 0) mbar_arrive(bar(B_ZERO));
            asm volatile("mbarrier.arrive.shared::cluster.b64 _, [%0];\nmbarrier.arrive.shared::cluster.b64 _, [%1];"
                         :: "r"(mapa(bar(B_OFREE), 0)), "r"(mapa(bar(B_OFREE), 1)) : "memory");
            asm volatile("fence.release.gpu;\nst.relaxed.gpu.global.u32 [%0], %1;\nmbarrier.arrive.shared::cluster.b64 _, [%2];"
                         :: "l"(&P.g->oflag[r * 32 + 2 * j + c]), "r"(epoch + 1), "r"(mapa(bar(B_RDY + c), rho ^ 1)) : "memory");
            TSTAMP(c == 0, 22); TSTAMP(c == 1, 23);
          }
          __syncwarp();
        }
      } else {
        const unsigned* fp = &P.g->oflag[r * 32 + (kcol(18 + min(lane, 13)) >> 6)];
        bool done = lane > 13 || lane < 2;
        mbar_wait_long(bar(B_OW), 0);
        for (int i = 0; !__all_sync(0xffffffffu, done) && i < kSpinLimit; i++) {
          const bool now = !done && (int)(ld_relaxed(fp) - epoch) > 0;
          if (__any_sync(0xffffffffu, now)) {
            asm volatile("fence.acquire.gpu;\nfence.proxy.async.global;" ::: "memory");
            mbar_arrive_if(bar(B_RDY + lane), now);
            TSTAMP(lane == 2 && now, 24);
          }
          done |= now;
        }
        if (lane == 0) P.g->epoch[cta] = epoch + 1;
        TSTAMP(lane == 0, 25);
      }
#pragma unroll 1
      for (int m = aw; m < ((EXP & 64) ? 0 : 16); m += 3) {
        const int u = 4 * (m & 7) + 2 * (m >> 3);
        mbar_wait_long(bar(B_Y + (m >> 3)), 0);
        TSTAMP(at == 0 && m == 0, 20);
        const uint32_t t0 = clock32();
        const uint32_t qa = sb + RA + u * 1024 + lane * 32 + ((rho ^ 1 ^ (lane >> 2)) & 1) * 16, ya = sb + Y_IN + u * 512 + lane * 16;
        uint32_t qv[PU][4], yv[PU][4];
#pragma unroll
        for (int h = 0; h < PU; h++) { lds128(qv[h], qa + h * 1024); lds128(yv[h], ya + h * 512); }
#pragma unroll
        for (int h = 0; h < PU; h++) sts128(qa + h * 1024, bmul2(qv[h][0], yv[h][0]), bmul2(qv[h][1], yv[h][1]), bmul2(qv[h][2], yv[h][2]), bmul2(qv[h][3], yv[h][3]));
        fence_async_smem();
        __syncwarp();
        if (elect()) tma5d_store(&P.outb, sb + RA + u * 1024, 1024 + 16 * cl, 2 * rho, (u >> 4) * 4 + (u & 3), (u >> 2) & 3);
        if (m < PSW) pace(t0, POSTGAP);
      }
      bulk_wait_read();
      TSTAMP(at == 0, 27);
    }
    if (ENDS) { __syncwarp(); cluster_sync(); }
  }
  TSTAMP(tid == 128, 61); GSTAMP(tid == 128, 63);
}

typedef CUresult (*EncodeFn)(CUtensorMap*, CUtensorMapDataType, cuuint32_t, void*, const cuuint64_t*, const cuuint64_t*,
                             const cuuint32_t*, const cuuint32_t*, CUtensorMapInterleave, CUtensorMapSwizzle,
                             CUtensorMapL2promotion, CUtensorMapFloatOOBfill);

void encode(EncodeFn fn, CUtensorMap* m, const void* p, int rank, const cuuint64_t* dims, const cuuint64_t* strides,
            const cuuint32_t* box, CUtensorMapSwizzle sw, int prom = 0) {
  const cuuint32_t es[5] = {1, 1, 1, 1, 1};
  fn(m, CU_TENSOR_MAP_DATA_TYPE_BFLOAT16, rank, const_cast<void*>(p), dims, strides, box, es, CU_TENSOR_MAP_INTERLEAVE_NONE, sw,
     (CUtensorMapL2promotion)prom, CU_TENSOR_MAP_FLOAT_OOB_FILL_NONE);
}
void encode2d(EncodeFn fn, CUtensorMap* m, const void* p, uint64_t cols, uint64_t rows, uint32_t bc, uint32_t br, CUtensorMapSwizzle sw, int prom = 0) {
  const cuuint64_t dims[2] = {cols, rows}, strides[1] = {cols * 2};
  const cuuint32_t box[2] = {bc, br};
  encode(fn, m, p, 2, dims, strides, box, sw, prom);
}
void encode3d(EncodeFn fn, CUtensorMap* m, const void* p) {
  const cuuint64_t dims[3] = {1024, 64, 32}, strides[2] = {2048 * 32, 2048};
  const cuuint32_t box[3] = {16, 32, 4};
  encode(fn, m, p, 3, dims, strides, box, CU_TENSOR_MAP_SWIZZLE_NONE);
}
void encode4d(EncodeFn fn, CUtensorMap* m, const void* p, uint64_t cols, uint32_t rows, uint32_t nmat) {
  const cuuint64_t dims[4] = {64, 1024, 16, cols / 1024}, strides[3] = {cols * 2, 128, 2048};
  const cuuint32_t box[4] = {64, rows, 2, nmat};
  encode(fn, m, p, 4, dims, strides, box, CU_TENSOR_MAP_SWIZZLE_128B);
}
void encode5d(EncodeFn fn, CUtensorMap* m, const void* p, uint64_t cols, uint32_t n, uint32_t nw) {
  const cuuint64_t dims[5] = {cols, 4, 16, 8, 4}, strides[4] = {cols * 2 * 512, cols * 2 * 8, cols * 2, cols * 2 * 128};
  const cuuint32_t box[5] = {16, 2, 16, n, nw};
  encode(fn, m, p, 5, dims, strides, box, CU_TENSOR_MAP_SWIZZLE_32B);
}

}

extern "C" void kernel_launch(void* const* d_in, const int* in_sizes, int n_in, void* d_out, int out_size) {
  static EncodeFn fn = nullptr;
  static void *o_ptr = nullptr, *g_ptr = nullptr, *tab_ptr = nullptr;
  if (!fn) {
    cudaDriverEntryPointQueryResult qr;
    cudaGetDriverEntryPoint("cuTensorMapEncodeTiled", (void**)&fn, cudaEnableDefault, &qr);
    cudaGetSymbolAddress(&o_ptr, g_o);
    cudaGetSymbolAddress(&g_ptr, g_scratch);
    cudaGetSymbolAddress(&tab_ptr, d_tab);
    cudaFuncSetAttribute(fused_kernel, cudaFuncAttributeMaxDynamicSharedMemorySize, SM_TOTAL);
  }
  Params P;
  encode4d(fn, &P.w1, d_in[1], 3072, 32, 2);
  encode2d(fn, &P.x, d_in[0], 1024, 2048, 64, 64, CU_TENSOR_MAP_SWIZZLE_128B);
  encode4d(fn, &P.w2, d_in[1], 3072, 64, 1);
  encode4d(fn, &P.wo, d_in[2], 1024, 64, 1);
  encode2d(fn, &P.o, o_ptr, 1024, 2048, 64, 64, CU_TENSOR_MAP_SWIZZLE_128B);
  encode2d(fn, &P.outa, d_out, 2048, 2048, 64, 16, CU_TENSOR_MAP_SWIZZLE_128B);
  encode3d(fn, &P.k, d_in[4]);
  encode3d(fn, &P.v, d_in[5]);
  encode5d(fn, &P.q, d_in[3], 1024, 4, 2);
  encode5d(fn, &P.outb, d_out, 2048, PU, 1);
  P.shift_k = (const __nv_bfloat16*)d_in[6];
  P.ssm_k = (const __nv_bfloat16*)d_in[7];
  P.ssm_d = (const __nv_bfloat16*)d_in[8];
  P.q_ptr = (const __nv_bfloat16*)d_in[3];
  P.k_ptr = (const __nv_bfloat16*)d_in[4];
  P.w_ptr = (const __nv_bfloat16*)d_in[1];
  P.wo_ptr = (const __nv_bfloat16*)d_in[2];
  P.zero = 0;
  P.g = (Scratch*)g_ptr;
  P.tab = (const uint32_t*)tab_ptr;
  fused_kernel<<<kCtas, kThreads, SM_TOTAL>>>(P);
}
```

```cpp
#include <cuda.h>
#include <cuda_runtime.h>
#include <cuda_bf16.h>
#include <stdint.h>

#define DEVI __device__ __forceinline__
#define INL __attribute__((always_inline))

namespace {

DEVI void mma_kt_init(float* d, uint64_t da, uint64_t db) {
  asm volatile("{\nwgmma.mma_async.sync.aligned.m64n128k16.f32.bf16.bf16 {%0, %1, %2, %3, %4, %5, %6, %7, %8, %9, %10, %11, %12, %13, %14, %15, %16, %17, %18, %19, %20, %21, %22, %23, %24, %25, %26, %27, %28, %29, %30, %31, %32, %33, %34, %35, %36, %37, %38, %39, %40, %41, %42, %43, %44, %45, %46, %47, %48, %49, %50, %51, %52, %53, %54, %55, %56, %57, %58, %59, %60, %61, %62, %63}, %64, %65, 0, 1, 1, 1, 0;\n}\n"
    : "=f"(d[0]), "=f"(d[1]), "=f"(d[2]), "=f"(d[3]), "=f"(d[4]), "=f"(d[5]), "=f"(d[6]), "=f"(d[7]), "=f"(d[8]), "=f"(d[9]), "=f"(d[10]), "=f"(d[11]), "=f"(d[12]), "=f"(d[13]), "=f"(d[14]), "=f"(d[15]), "=f"(d[16]), "=f"(d[17]), "=f"(d[18]), "=f"(d[19]), "=f"(d[20]), "=f"(d[21]), "=f"(d[22]), "=f"(d[23]), "=f"(d[24]), "=f"(d[25]), "=f"(d[26]), "=f"(d[27]), "=f"(d[28]), "=f"(d[29]), "=f"(d[30]), "=f"(d[31]), "=f"(d[32]), "=f"(d[33]), "=f"(d[34]), "=f"(d[35]), "=f"(d[36]), "=f"(d[37]), "=f"(d[38]), "=f"(d[39]), "=f"(d[40]), "=f"(d[41]), "=f"(d[42]), "=f"(d[43]), "=f"(d[44]), "=f"(d[45]), "=f"(d[46]), "=f"(d[47]), "=f"(d[48]), "=f"(d[49]), "=f"(d[50]), "=f"(d[51]), "=f"(d[52]), "=f"(d[53]), "=f"(d[54]), "=f"(d[55]), "=f"(d[56]), "=f"(d[57]), "=f"(d[58]), "=f"(d[59]), "=f"(d[60]), "=f"(d[61]), "=f"(d[62]), "=f"(d[63])
    : "l"(da), "l"(db));
}
DEVI void mma_kt(float* d, uint64_t da, uint64_t db) {
  asm volatile("{\nwgmma.mma_async.sync.aligned.m64n128k16.f32.bf16.bf16 {%0, %1, %2, %3, %4, %5, %6, %7, %8, %9, %10, %11, %12, %13, %14, %15, %16, %17, %18, %19, %20, %21, %22, %23, %24, %25, %26, %27, %28, %29, %30, %31, %32, %33, %34, %35, %36, %37, %38, %39, %40, %41, %42, %43, %44, %45, %46, %47, %48, %49, %50, %51, %52, %53, %54, %55, %56, %57, %58, %59, %60, %61, %62, %63}, %64, %65, 1, 1, 1, 1, 0;\n}\n"
    : "+f"(d[0]), "+f"(d[1]), "+f"(d[2]), "+f"(d[3]), "+f"(d[4]), "+f"(d[5]), "+f"(d[6]), "+f"(d[7]), "+f"(d[8]), "+f"(d[9]), "+f"(d[10]), "+f"(d[11]), "+f"(d[12]), "+f"(d[13]), "+f"(d[14]), "+f"(d[15]), "+f"(d[16]), "+f"(d[17]), "+f"(d[18]), "+f"(d[19]), "+f"(d[20]), "+f"(d[21]), "+f"(d[22]), "+f"(d[23]), "+f"(d[24]), "+f"(d[25]), "+f"(d[26]), "+f"(d[27]), "+f"(d[28]), "+f"(d[29]), "+f"(d[30]), "+f"(d[31]), "+f"(d[32]), "+f"(d[33]), "+f"(d[34]), "+f"(d[35]), "+f"(d[36]), "+f"(d[37]), "+f"(d[38]), "+f"(d[39]), "+f"(d[40]), "+f"(d[41]), "+f"(d[42]), "+f"(d[43]), "+f"(d[44]), "+f"(d[45]), "+f"(d[46]), "+f"(d[47]), "+f"(d[48]), "+f"(d[49]), "+f"(d[50]), "+f"(d[51]), "+f"(d[52]), "+f"(d[53]), "+f"(d[54]), "+f"(d[55]), "+f"(d[56]), "+f"(d[57]), "+f"(d[58]), "+f"(d[59]), "+f"(d[60]), "+f"(d[61]), "+f"(d[62]), "+f"(d[63])
    : "l"(da), "l"(db));
}
DEVI void mma_n128_init(float* d, uint64_t da, uint64_t db) {
  asm volatile("{\nwgmma.mma_async.sync.aligned.m64n128k16.f32.bf16.bf16 {%0, %1, %2, %3, %4, %5, %6, %7, %8, %9, %10, %11, %12, %13, %14, %15, %16, %17, %18, %19, %20, %21, %22, %23, %24, %25, %26, %27, %28, %29, %30, %31, %32, %33, %34, %35, %36, %37, %38, %39, %40, %41, %42, %43, %44, %45, %46, %47, %48, %49, %50, %51, %52, %53, %54, %55, %56, %57, %58, %59, %60, %61, %62, %63}, %64, %65, 0, 1, 1, 0, 1;\n}\n"
    : "=f"(d[0]), "=f"(d[1]), "=f"(d[2]), "=f"(d[3]), "=f"(d[4]), "=f"(d[5]), "=f"(d[6]), "=f"(d[7]), "=f"(d[8]), "=f"(d[9]), "=f"(d[10]), "=f"(d[11]), "=f"(d[12]), "=f"(d[13]), "=f"(d[14]), "=f"(d[15]), "=f"(d[16]), "=f"(d[17]), "=f"(d[18]), "=f"(d[19]), "=f"(d[20]), "=f"(d[21]), "=f"(d[22]), "=f"(d[23]), "=f"(d[24]), "=f"(d[25]), "=f"(d[26]), "=f"(d[27]), "=f"(d[28]), "=f"(d[29]), "=f"(d[30]), "=f"(d[31]), "=f"(d[32]), "=f"(d[33]), "=f"(d[34]), "=f"(d[35]), "=f"(d[36]), "=f"(d[37]), "=f"(d[38]), "=f"(d[39]), "=f"(d[40]), "=f"(d[41]), "=f"(d[42]), "=f"(d[43]), "=f"(d[44]), "=f"(d[45]), "=f"(d[46]), "=f"(d[47]), "=f"(d[48]), "=f"(d[49]), "=f"(d[50]), "=f"(d[51]), "=f"(d[52]), "=f"(d[53]), "=f"(d[54]), "=f"(d[55]), "=f"(d[56]), "=f"(d[57]), "=f"(d[58]), "=f"(d[59]), "=f"(d[60]), "=f"(d[61]), "=f"(d[62]), "=f"(d[63])
    : "l"(da), "l"(db));
}
DEVI void mma_n128(float* d, uint64_t da, uint64_t db) {
  asm volatile("{\nwgmma.mma_async.sync.aligned.m64n128k16.f32.bf16.bf16 {%0, %1, %2, %3, %4, %5, %6, %7, %8, %9, %10, %11, %12, %13, %14, %15, %16, %17, %18, %19, %20, %21, %22, %23, %24, %25, %26, %27, %28, %29, %30, %31, %32, %33, %34, %35, %36, %37, %38, %39, %40, %41, %42, %43, %44, %45, %46, %47, %48, %49, %50, %51, %52, %53, %54, %55, %56, %57, %58, %59, %60, %61, %62, %63}, %64, %65, 1, 1, 1, 0, 1;\n}\n"
    : "+f"(d[0]), "+f"(d[1]), "+f"(d[2]), "+f"(d[3]), "+f"(d[4]), "+f"(d[5]), "+f"(d[6]), "+f"(d[7]), "+f"(d[8]), "+f"(d[9]), "+f"(d[10]), "+f"(d[11]), "+f"(d[12]), "+f"(d[13]), "+f"(d[14]), "+f"(d[15]), "+f"(d[16]), "+f"(d[17]), "+f"(d[18]), "+f"(d[19]), "+f"(d[20]), "+f"(d[21]), "+f"(d[22]), "+f"(d[23]), "+f"(d[24]), "+f"(d[25]), "+f"(d[26]), "+f"(d[27]), "+f"(d[28]), "+f"(d[29]), "+f"(d[30]), "+f"(d[31]), "+f"(d[32]), "+f"(d[33]), "+f"(d[34]), "+f"(d[35]), "+f"(d[36]), "+f"(d[37]), "+f"(d[38]), "+f"(d[39]), "+f"(d[40]), "+f"(d[41]), "+f"(d[42]), "+f"(d[43]), "+f"(d[44]), "+f"(d[45]), "+f"(d[46]), "+f"(d[47]), "+f"(d[48]), "+f"(d[49]), "+f"(d[50]), "+f"(d[51]), "+f"(d[52]), "+f"(d[53]), "+f"(d[54]), "+f"(d[55]), "+f"(d[56]), "+f"(d[57]), "+f"(d[58]), "+f"(d[59]), "+f"(d[60]), "+f"(d[61]), "+f"(d[62]), "+f"(d[63])
    : "l"(da), "l"(db));
}
DEVI void mma_kv_init(float* d, const uint32_t* a, uint64_t db) {
  asm volatile("{\nwgmma.mma_async.sync.aligned.m64n72k16.f32.bf16.bf16 {%0, %1, %2, %3, %4, %5, %6, %7, %8, %9, %10, %11, %12, %13, %14, %15, %16, %17, %18, %19, %20, %21, %22, %23, %24, %25, %26, %27, %28, %29, %30, %31, %32, %33, %34, %35}, {%36,%37,%38,%39}, %40, 0, 1, 1, 1;\n}\n"
    : "=f"(d[0]), "=f"(d[1]), "=f"(d[2]), "=f"(d[3]), "=f"(d[4]), "=f"(d[5]), "=f"(d[6]), "=f"(d[7]), "=f"(d[8]), "=f"(d[9]), "=f"(d[10]), "=f"(d[11]), "=f"(d[12]), "=f"(d[13]), "=f"(d[14]), "=f"(d[15]), "=f"(d[16]), "=f"(d[17]), "=f"(d[18]), "=f"(d[19]), "=f"(d[20]), "=f"(d[21]), "=f"(d[22]), "=f"(d[23]), "=f"(d[24]), "=f"(d[25]), "=f"(d[26]), "=f"(d[27]), "=f"(d[28]), "=f"(d[29]), "=f"(d[30]), "=f"(d[31]), "=f"(d[32]), "=f"(d[33]), "=f"(d[34]), "=f"(d[35])
    : "r"(a[0]), "r"(a[1]), "r"(a[2]), "r"(a[3]), "l"(db));
}
DEVI void mma_kv(float* d, const uint32_t* a, uint64_t db) {
  asm volatile("{\nwgmma.mma_async.sync.aligned.m64n72k16.f32.bf16.bf16 {%0, %1, %2, %3, %4, %5, %6, %7, %8, %9, %10, %11, %12, %13, %14, %15, %16, %17, %18, %19, %20, %21, %22, %23, %24, %25, %26, %27, %28, %29, %30, %31, %32, %33, %34, %35}, {%36,%37,%38,%39}, %40, 1, 1, 1, 1;\n}\n"
    : "+f"(d[0]), "+f"(d[1]), "+f"(d[2]), "+f"(d[3]), "+f"(d[4]), "+f"(d[5]), "+f"(d[6]), "+f"(d[7]), "+f"(d[8]), "+f"(d[9]), "+f"(d[10]), "+f"(d[11]), "+f"(d[12]), "+f"(d[13]), "+f"(d[14]), "+f"(d[15]), "+f"(d[16]), "+f"(d[17]), "+f"(d[18]), "+f"(d[19]), "+f"(d[20]), "+f"(d[21]), "+f"(d[22]), "+f"(d[23]), "+f"(d[24]), "+f"(d[25]), "+f"(d[26]), "+f"(d[27]), "+f"(d[28]), "+f"(d[29]), "+f"(d[30]), "+f"(d[31]), "+f"(d[32]), "+f"(d[33]), "+f"(d[34]), "+f"(d[35])
    : "r"(a[0]), "r"(a[1]), "r"(a[2]), "r"(a[3]), "l"(db));
}
DEVI void mma_o_init(float* d, const uint32_t* a, uint64_t db) {
  asm volatile("{\nwgmma.mma_async.sync.aligned.m64n40k16.f32.bf16.bf16 {%0, %1, %2, %3, %4, %5, %6, %7, %8, %9, %10, %11, %12, %13, %14, %15, %16, %17, %18, %19}, {%20,%21,%22,%23}, %24, 0, 1, 1, 1;\n}\n"
    : "=f"(d[0]), "=f"(d[1]), "=f"(d[2]), "=f"(d[3]), "=f"(d[4]), "=f"(d[5]), "=f"(d[6]), "=f"(d[7]), "=f"(d[8]), "=f"(d[9]), "=f"(d[10]), "=f"(d[11]), "=f"(d[12]), "=f"(d[13]), "=f"(d[14]), "=f"(d[15]), "=f"(d[16]), "=f"(d[17]), "=f"(d[18]), "=f"(d[19])
    : "r"(a[0]), "r"(a[1]), "r"(a[2]), "r"(a[3]), "l"(db));
}
DEVI void mma_o(float* d, const uint32_t* a, uint64_t db) {
  asm volatile("{\nwgmma.mma_async.sync.aligned.m64n40k16.f32.bf16.bf16 {%0, %1, %2, %3, %4, %5, %6, %7, %8, %9, %10, %11, %12, %13, %14, %15, %16, %17, %18, %19}, {%20,%21,%22,%23}, %24, 1, 1, 1, 1;\n}\n"
    : "+f"(d[0]), "+f"(d[1]), "+f"(d[2]), "+f"(d[3]), "+f"(d[4]), "+f"(d[5]), "+f"(d[6]), "+f"(d[7]), "+f"(d[8]), "+f"(d[9]), "+f"(d[10]), "+f"(d[11]), "+f"(d[12]), "+f"(d[13]), "+f"(d[14]), "+f"(d[15]), "+f"(d[16]), "+f"(d[17]), "+f"(d[18]), "+f"(d[19])
    : "r"(a[0]), "r"(a[1]), "r"(a[2]), "r"(a[3]), "l"(db));
}
DEVI void mma_s1_init(uint32_t* d, const uint32_t* a, uint64_t db) {
  asm volatile("{\nwgmma.mma_async.sync.aligned.m64n128k16.f16.f16.f16 {%0, %1, %2, %3, %4, %5, %6, %7, %8, %9, %10, %11, %12, %13, %14, %15, %16, %17, %18, %19, %20, %21, %22, %23, %24, %25, %26, %27, %28, %29, %30, %31}, {%32,%33,%34,%35}, %36, 0, 1, 1, 1;\n}\n"
    : "=r"(d[0]), "=r"(d[1]), "=r"(d[2]), "=r"(d[3]), "=r"(d[4]), "=r"(d[5]), "=r"(d[6]), "=r"(d[7]), "=r"(d[8]), "=r"(d[9]), "=r"(d[10]), "=r"(d[11]), "=r"(d[12]), "=r"(d[13]), "=r"(d[14]), "=r"(d[15]), "=r"(d[16]), "=r"(d[17]), "=r"(d[18]), "=r"(d[19]), "=r"(d[20]), "=r"(d[21]), "=r"(d[22]), "=r"(d[23]), "=r"(d[24]), "=r"(d[25]), "=r"(d[26]), "=r"(d[27]), "=r"(d[28]), "=r"(d[29]), "=r"(d[30]), "=r"(d[31])
    : "r"(a[0]), "r"(a[1]), "r"(a[2]), "r"(a[3]), "l"(db));
}
DEVI void mma_s1(uint32_t* d, const uint32_t* a, uint64_t db) {
  asm volatile("{\nwgmma.mma_async.sync.aligned.m64n128k16.f16.f16.f16 {%0, %1, %2, %3, %4, %5, %6, %7, %8, %9, %10, %11, %12, %13, %14, %15, %16, %17, %18, %19, %20, %21, %22, %23, %24, %25, %26, %27, %28, %29, %30, %31}, {%32,%33,%34,%35}, %36, 1, 1, 1, 1;\n}\n"
    : "+r"(d[0]), "+r"(d[1]), "+r"(d[2]), "+r"(d[3]), "+r"(d[4]), "+r"(d[5]), "+r"(d[6]), "+r"(d[7]), "+r"(d[8]), "+r"(d[9]), "+r"(d[10]), "+r"(d[11]), "+r"(d[12]), "+r"(d[13]), "+r"(d[14]), "+r"(d[15]), "+r"(d[16]), "+r"(d[17]), "+r"(d[18]), "+r"(d[19]), "+r"(d[20]), "+r"(d[21]), "+r"(d[22]), "+r"(d[23]), "+r"(d[24]), "+r"(d[25]), "+r"(d[26]), "+r"(d[27]), "+r"(d[28]), "+r"(d[29]), "+r"(d[30]), "+r"(d[31])
    : "r"(a[0]), "r"(a[1]), "r"(a[2]), "r"(a[3]), "l"(db));
}
DEVI void mma_s2_init(uint32_t* d, const uint32_t* a, uint64_t db) {
  asm volatile("{\nwgmma.mma_async.sync.aligned.m64n32k16.f16.f16.f16 {%0, %1, %2, %3, %4, %5, %6, %7}, {%8,%9,%10,%11}, %12, 0, 1, 1, 0;\n}\n"
    : "=r"(d[0]), "=r"(d[1]), "=r"(d[2]), "=r"(d[3]), "=r"(d[4]), "=r"(d[5]), "=r"(d[6]), "=r"(d[7])
    : "r"(a[0]), "r"(a[1]), "r"(a[2]), "r"(a[3]), "l"(db));
}
DEVI void mma_s2(uint32_t* d, const uint32_t* a, uint64_t db) {
  asm volatile("{\nwgmma.mma_async.sync.aligned.m64n32k16.f16.f16.f16 {%0, %1, %2, %3, %4, %5, %6, %7}, {%8,%9,%10,%11}, %12, 1, 1, 1, 0;\n}\n"
    : "+r"(d[0]), "+r"(d[1]), "+r"(d[2]), "+r"(d[3]), "+r"(d[4]), "+r"(d[5]), "+r"(d[6]), "+r"(d[7])
    : "r"(a[0]), "r"(a[1]), "r"(a[2]), "r"(a[3]), "l"(db));
}
DEVI void mma_s2_neg(uint32_t* d, const uint32_t* a, uint64_t db) {
  asm volatile("{\nwgmma.mma_async.sync.aligned.m64n32k16.f16.f16.f16 {%0, %1, %2, %3, %4, %5, %6, %7}, {%8,%9,%10,%11}, %12, 1, -1, 1, 0;\n}\n"
    : "+r"(d[0]), "+r"(d[1]), "+r"(d[2]), "+r"(d[3]), "+r"(d[4]), "+r"(d[5]), "+r"(d[6]), "+r"(d[7])
    : "r"(a[0]), "r"(a[1]), "r"(a[2]), "r"(a[3]), "l"(db));
}
DEVI void mma_i2_init(float* d, const uint32_t* a, uint64_t db, uint32_t meta) {
  asm volatile("{\nwgmma.mma_async.sp.sync.aligned.m64n128k32.f32.f16.f16 {%0, %1, %2, %3, %4, %5, %6, %7, %8, %9, %10, %11, %12, %13, %14, %15, %16, %17, %18, %19, %20, %21, %22, %23, %24, %25, %26, %27, %28, %29, %30, %31, %32, %33, %34, %35, %36, %37, %38, %39, %40, %41, %42, %43, %44, %45, %46, %47, %48, %49, %50, %51, %52, %53, %54, %55, %56, %57, %58, %59, %60, %61, %62, %63}, {%64,%65,%66,%67}, %68, %69, 0, 0, 1, 1, 1;\n}\n"
    : "=f"(d[0]), "=f"(d[1]), "=f"(d[2]), "=f"(d[3]), "=f"(d[4]), "=f"(d[5]), "=f"(d[6]), "=f"(d[7]), "=f"(d[8]), "=f"(d[9]), "=f"(d[10]), "=f"(d[11]), "=f"(d[12]), "=f"(d[13]), "=f"(d[14]), "=f"(d[15]), "=f"(d[16]), "=f"(d[17]), "=f"(d[18]), "=f"(d[19]), "=f"(d[20]), "=f"(d[21]), "=f"(d[22]), "=f"(d[23]), "=f"(d[24]), "=f"(d[25]), "=f"(d[26]), "=f"(d[27]), "=f"(d[28]), "=f"(d[29]), "=f"(d[30]), "=f"(d[31]), "=f"(d[32]), "=f"(d[33]), "=f"(d[34]), "=f"(d[35]), "=f"(d[36]), "=f"(d[37]), "=f"(d[38]), "=f"(d[39]), "=f"(d[40]), "=f"(d[41]), "=f"(d[42]), "=f"(d[43]), "=f"(d[44]), "=f"(d[45]), "=f"(d[46]), "=f"(d[47]), "=f"(d[48]), "=f"(d[49]), "=f"(d[50]), "=f"(d[51]), "=f"(d[52]), "=f"(d[53]), "=f"(d[54]), "=f"(d[55]), "=f"(d[56]), "=f"(d[57]), "=f"(d[58]), "=f"(d[59]), "=f"(d[60]), "=f"(d[61]), "=f"(d[62]), "=f"(d[63])
    : "r"(a[0]), "r"(a[1]), "r"(a[2]), "r"(a[3]), "l"(db), "r"(meta));
}
DEVI void mma_i2(float* d, const uint32_t* a, uint64_t db, uint32_t meta) {
  asm volatile("{\nwgmma.mma_async.sp.sync.aligned.m64n128k32.f32.f16.f16 {%0, %1, %2, %3, %4, %5, %6, %7, %8, %9, %10, %11, %12, %13, %14, %15, %16, %17, %18, %19, %20, %21, %22, %23, %24, %25, %26, %27, %28, %29, %30, %31, %32, %33, %34, %35, %36, %37, %38, %39, %40, %41, %42, %43, %44, %45, %46, %47, %48, %49, %50, %51, %52, %53, %54, %55, %56, %57, %58, %59, %60, %61, %62, %63}, {%64,%65,%66,%67}, %68, %69, 0, 1, 1, 1, 1;\n}\n"
    : "+f"(d[0]), "+f"(d[1]), "+f"(d[2]), "+f"(d[3]), "+f"(d[4]), "+f"(d[5]), "+f"(d[6]), "+f"(d[7]), "+f"(d[8]), "+f"(d[9]), "+f"(d[10]), "+f"(d[11]), "+f"(d[12]), "+f"(d[13]), "+f"(d[14]), "+f"(d[15]), "+f"(d[16]), "+f"(d[17]), "+f"(d[18]), "+f"(d[19]), "+f"(d[20]), "+f"(d[21]), "+f"(d[22]), "+f"(d[23]), "+f"(d[24]), "+f"(d[25]), "+f"(d[26]), "+f"(d[27]), "+f"(d[28]), "+f"(d[29]), "+f"(d[30]), "+f"(d[31]), "+f"(d[32]), "+f"(d[33]), "+f"(d[34]), "+f"(d[35]), "+f"(d[36]), "+f"(d[37]), "+f"(d[38]), "+f"(d[39]), "+f"(d[40]), "+f"(d[41]), "+f"(d[42]), "+f"(d[43]), "+f"(d[44]), "+f"(d[45]), "+f"(d[46]), "+f"(d[47]), "+f"(d[48]), "+f"(d[49]), "+f"(d[50]), "+f"(d[51]), "+f"(d[52]), "+f"(d[53]), "+f"(d[54]), "+f"(d[55]), "+f"(d[56]), "+f"(d[57]), "+f"(d[58]), "+f"(d[59]), "+f"(d[60]), "+f"(d[61]), "+f"(d[62]), "+f"(d[63])
    : "r"(a[0]), "r"(a[1]), "r"(a[2]), "r"(a[3]), "l"(db), "r"(meta));
}
__device__ const __align__(128) uint32_t d_tab[2944] = {
  0x3bf13bff,0x2fbd25e4,0x38ee3986,0x3a4d39c9,0x3b9a3bcf,0x34ff32f7,0x3737384a,0x3b243ac1,0x3af73b52,0x37dd3676,0x344b35c8,0x3bb53b76,
  0x3a113a8c,0x39373899,0x2cce3185,0x3bfa3be1,0x3a933bf2,0x388e2f59,0xb1b6b8f8,0xbbdfba45,0xa452374e,0x3c003b1e,0x39c034e7,0xb990bb9e,
  0xbabab7c8,0x38553afe,0x3bd23bb2,0x32c6b463,0xbb57bbf9,0xb65f2d33,0x35df3a19,0x3b71392e,0x37643bd4,0x3b183294,0xb4cf385f,0x3ba13ab3,
  0xbbaeb648,0x347b3b5c,0xbb04bb6c,0xb7b235f7,0xad97ba9b,0xbbf8b884,0x3924b1e8,0xba21bbdd,0x3bf439b8,0x2ef5b999,0x39023c00,0x3a3d217f,
  0x9cb63ba5,0x3c0034b7,0x39afb77a,0xb9a1bb13,0xb86abbab,0xbaac3493,0xb2633b0a,0x3bd7379b,0x3b60391b,0x3631ba29,0xb60ebbf7,0xbb682dfb,
  0xbbdaae91,0x32193bf5,0x3aa23a35,0x387ab90c,0xb7853b65,0x3b10361a,0xbba73625,0x34ab3b63,0x3911baa9,0xba31b86f,0x3bf6b24b,0xae5fbbd8,
  0xba2d39aa,0x391639a6,0xbbf61648,0xae2d3c00,0x3b0db874,0xb790baa5,0x3ba93232,0x349fbbd9,0xba9e3b16,0x387f376f,0x3bdcb4c3,0x3201bba3,
  0x3b6aaec3,0x3602bbf5,0xb63cb907,0xbb5e3a39,0xb27cba25,0xbbd6391f,0xb8653bf8,0x3ab02dc9,0xb99d3bac,0x39b33487,0x3c00b7a6,0x9fdbbb07,
  0xbbf33ab6,0x2f27385a,0xba4132ad,0xb8fd3bd3,0xad653994,0x3bf9b9bc,0xba1d3c00,0x3929a311,0x3bb0b889,0x346fba97,0x37bd31cf,0x3b01bbde,
  0x3759bb59,0xbb1b3654,0x3b9fbb6f,0xb4dbb5eb,0xbb733a49,0xb5d438f3,0x366baf8b,0x3b54bbf2,0xbbd03bfa,0x32de2d00,0x3abdb933,0x3850ba15,
  0xb98b3afb,0x39c5b7d2,0x3c00bbb3,0xa51bb457,0xb19e3742,0x3be0bb21,0x3a90bb9c,0xb89434f3,0xb93c39cd,0xba0d3982,0x2c9c26ad,0xbbfb3bff,
  0xb7e8389e,0xbaf43a89,0x343eb16c,0xbbb73be2,0xb50b3682,0xbb983b4f,0x372cb5bc,0xbb273b78,0xafef330f,0xbbf03bce,0x38eab845,0xba503ac4,
  0xb3403946,0xbbcb3a04,0xb83a2c38,0x3acbbbfc,0x3979b426,0xb9d63bba,0xbbff3aee,0x281fb7fe,0x3be4bb94,0x313b3523,0xb8a83b2c,0xba813715,
  0x3699ba58,0x3b4ab8e0,0x35a53029,0xbb7c3bef,0x340e38b2,0xbbbd3a7a,0x3ae8b109,0xb80a3be6,0x3b32bb45,0x36ff36af,0x353abb81,0x3b90b58d,
  0xb8d6b371,0x3a60bbc8,0xbbed3830,0x305bbad1,0xb94f3bfe,0xb9fca8e8,0x2ba739df,0xbbfc3970,0x39663815,0xb9e73ae1,0xbbfe33eb,0x29b1bbc0,
  0xb0d7bb37,0x3be8b6e8,0x3a733552,0xb8bc3b8b,0xb6c63beb,0xbb3fb08d,0xb576ba67,0x3b85b8cc,0x3ad8b9f4,0x38253958,0xb3a23bfd,0xbbc52ade,
  0x3b8736dd,0xb56a3b3a,0x3b3db55e,0x36d23b89,0xbbe9b3d3,0x30bebbc2,0xba6f381a,0xb8c1bade,0x3bfe2a7a,0x2a163bfd,0x3962b95d,0x39eb39f0,
  0xbbc330a6,0xb3babbea,0xb8203a6b,0xbadbb8c7,0x3bec3581,0x30743b83,0xb8d136bb,0xba64bb42,0xb6f438b7,0xbb35ba76,0xb546bbe7,0x3b8e30f0,
  0xb80fbbfe,0x3ae5a94d,0x3bbf396b,0xb40239e3,0x3bfd382a,0xab433ad5,0xb9f83389,0xb954bbc6,0x3a7e341a,0x38ad3bbc,0x3122b805,0x3be53aeb,
  0x39da3bfc,0xb974ac06,0x3bff3a00,0x2884394a,0xb8353042,0xbacebbee,0x33593a5c,0xbbc9b8db,0xbb7fbb92,0x3599b52f,0xbb47b70a,0xb6a4bb2f,
  0x37213153,0x3b2a3be3,0x351738a3,0xbb96ba85,0x3af1397d,0x37f339d2,0xb4322776,0xbbb8bbff,0x3bfb3bcc,0xac6a3328,0xba09b840,0xb941bac7,
  0x3a543b7a,0xb8e5b5b1,0xbbefbb4c,0xb010b68d,0x32f72fbd,0xbbcfbbf1,0x3ac13a4d,0xb84ab8ee,0x367634ff,0xbb52bb9a,0x3b763b24,0xb5c8b737,
  0x389937dd,0xba8cbaf7,0x3be13bb5,0xb185b44b,0x39c93937,0xb986ba11,0x3bff3bfa,0x25e4acce,0x392e32c6,0xba19bbd2,0xbbf9baba,0x2d333855,
  0x3bf23b71,0x2f59b5df,0xb8f8bb57,0xba45b65f,0x374e3a93,0x3b1e388e,0x34e7b1b6,0xbb9ebbdf,0xb7c8a452,0x3afe3c00,0x3bb239c0,0xb463b990,
  0x3b6c34cf,0xb5f7bba1,0x3b5c3b18,0x3648b764,0x31e83b04,0x3bdd37b2,0xb884347b,0x3a9b3bae,0xbc00b924,0xa17f3a21,0xb999bbf8,0xb9b82d97,
  0x3294b902,0xbbd4ba3d,0x3ab32ef5,0xb85fbbf4,0x3bf53631,0x2e91bb60,0xb90cbb68,0xba35360e,0xbb133219,0x377a3bda,0x3ba5387a,0x34b7baa2,
  0x379bb9a1,0xbb0ab9af,0xbbab9cb6,0x34933c00,0x2dfb3bd7,0x3bf73263,0x391bb86a,0xba29baac,0x3aa93785,0x386fbb10,0x324b3ba7,0x3bd8b4ab,
  0xb9aab911,0xb9a63a31,0x9648bbf6,0xbc002e5f,0x38743a2d,0x3aa5b916,0xb2323bf6,0x3bd92e2d,0xb625bb0d,0xbb633790,0x361abba9,0xbb65b49f,
  0x37a63865,0x3b07bab0,0x3487bbd6,0xbbac327c,0x376fbc00,0xbb161fdb,0xbba339b3,0x34c3399d,0xbbf5387f,0x2ec33a9e,0x3a393201,0x3907bbdc,
  0x391f3602,0x3a25bb6a,0x2dc9bb5e,0xbbf8363c,0x231138fd,0x3c00ba41,0xb9943bf3,0x39bcaf27,0x3bdeb929,0x31cfba1d,0x38892d65,0x3a97bbf9,
  0x35ebbb01,0xbb6f37bd,0x3b59bbb0,0xb654b46f,0xbab634db,0xb85a3b9f,0xb2adb759,0xbbd33b1b,0xb742398b,0x3b21b9c5,0x3b9cbc00,0xb4f3251b,
  0x2f8b319e,0x3bf2bbe0,0x38f3ba90,0xba493894,0x3933b66b,0x3a15bb54,0x2d00b5d4,0xbbfa3b73,0x3bb3babd,0x3457b850,0xb7d232de,0xbafb3bd0,
  0xba893a0d,0x389eb93c,0xbbe23bfb,0xb16c2c9c,0xbb4f3af4,0x3682b7e8,0xbb783bb7,0xb5bc343e,0xbbce3b98,0x330fb50b,0xbac43b27,0xb845372c,
  0xbbff3bf0,0x26adafef,0xb9cd3a50,0xb98238ea,0xbbef3a81,0x3029b8a8,0x3a58bbe4,0x38e0b13b,0xb9463b7c,0xba0435a5,0xac38b699,0x3bfcbb4a,
  0x34263340,0xbbba3bcb,0xbaee383a,0x37febacb,0x3b94b979,0xb52339d6,0xbb2c3bff,0xb715a81f,0xbb813ae8,0xb58db80a,0xb6af3bbd,0xbb45340e,
  0x3830353a,0xbad13b90,0x3bc8b6ff,0xb3713b32,0x39dfbbed,0x3970305b,0x28e8ba60,0x3bfeb8d6,0xba7a2ba7,0x38b2bbfc,0xbbe639fc,0xb109b94f,
  0xb9583b3f,0xb9f4b6c6,0xaadebb85,0x3bfdb576,0x3bc0b825,0x33eb3ad8,0xb8153bc5,0xbae1b3a2,0xbb8ba9b1,0x3552bbfe,0x3b37b966,0x36e839e7,
  0x38cc38bc,0xba673a73,0xbbeb30d7,0x308dbbe8,0xb3d33b87,0xbbc2b56a,0x381a3b3d,0xbade36d2,0x2a7abbe9,0x3bfd30be,0xb95dba6f,0x39f0b8c1,
  0x30a63bfe,0xbbea2a16,0x3a6b3962,0xb8c739eb,0xb55ebbc3,0x3b89b3ba,0xbb3ab820,0x36ddbadb,0x33893bbf,0xbbc6b402,0xbad5bae5,0x382ab80f,
  0xbb83b9f8,0x3581b954,0x3b422b43,0x36bb3bfd,0x3a76b074,0x38b73bec,0xb0f03a64,0xbbe7b8d1,0x294d3b35,0xbbfeb6f4,0xb9e3bb8e,0x396bb546,
  0x394a3be5,0xba00b122,0x3bfc3a7e,0xac0638ad,0xb8db2884,0xba5cbbff,0x304239da,0xbbeeb974,0xbb2fbbc9,0x370ab359,0xbb92b835,0xb52fbace,
  0x341ab6a4,0x3bbc3b47,0xb805bb7f,0x3aeb3599,0x3b7a3bfb,0xb5b1ac6a,0xbb4cba09,0xb68db941,0x38a33a54,0xba85b8e5,0xbbe3bbef,0x3153b010,
  0x27763517,0xbbffbb96,0xb9d2bb2a,0x397d3721,0xb840b432,0xbac7bbb8,0xb328b7f3,0x3bcc3af1,0x3be23bfb,0x316c2c9c,0x389e393c,0x3a893a0d,
  0x3b783bb7,0x35bc343e,0x368237e8,0x3b4f3af4,0x3ac43b27,0x3845372c,0x330f350b,0x3bce3b98,0x39cd3a50,0x398238ea,0x26ad2fef,0x3bff3bf0,
  0x39463b7c,0x3a0435a5,0x2c38b699,0xbbfcbb4a,0xb4263340,0x3bba3bcb,0x3aee383a,0xb7febacb,0xbb94b979,0x352339d6,0x3b2c3bff,0x3715a81f,
  0xba58bbe4,0xb8e0b13b,0x302938a8,0x3bef3a81,0x28e83a60,0x3bfe38d6,0xb970305b,0x39df3bed,0xbbe6b9fc,0xb109394f,0xb8b2bbfc,0xba7aaba7,
  0x358db80a,0xbb81bae8,0x3b45340e,0xb6afbbbd,0x3ad13b90,0x3830b53a,0x33713b32,0x3bc836ff,0xb8cc38bc,0x3a673a73,0x3beb30d7,0xb08dbbe8,
  0x2adebb85,0xbbfdb576,0xb9f436c6,0x39583b3f,0x38153bc5,0x3ae1b3a2,0x33ebbad8,0xbbc0b825,0xbb37b966,0xb6e839e7,0x35523bfe,0x3b8ba9b1,
  0xbbc2356a,0x33d33b87,0xbadeb6d2,0xb81a3b3d,0x3bfdb0be,0xaa7abbe9,0x39f038c1,0x395dba6f,0xbbeaaa16,0xb0a63bfe,0xb8c7b9eb,0xba6b3962,
  0x3b8933ba,0x355ebbc3,0x36dd3adb,0x3b3ab820,0xbb422b43,0xb6bb3bfd,0x35813954,0x3b83b9f8,0x30f03a64,0x3be7b8d1,0x38b7bbec,0xba76b074,
  0x39e3bb8e,0xb96bb546,0xbbfe36f4,0xa94d3b35,0xbbc63402,0xb3893bbf,0x382a380f,0x3ad5bae5,0xb70ab359,0xbb2f3bc9,0x352fbace,0xbb923835,
  0xbbbc3b47,0x341a36a4,0xbaeb3599,0xb8053b7f,0x2c0638ad,0x3bfcba7e,0xb94a3be5,0x3a00b122,0x3beeb974,0x3042b9da,0x38db2884,0x3a5cbbff,
  0x3328b7f3,0xbbcc3af1,0xbac73bb8,0x3840b432,0xb5b12c6a,0xbb7a3bfb,0xb68d3941,0x3b4cba09,0xba8538e5,0xb8a33a54,0x31533010,0x3be3bbef,
  0xbbff3b96,0xa7763517,0x397db721,0x39d2bb2a,0x3a4db9c9,0xb8ee3986,0x3bf1bbff,0x2fbda5e4,0x3b24bac1,0xb737384a,0x3b9abbcf,0x34ffb2f7,
  0x3bb5bb76,0xb44b35c8,0x3af7bb52,0x37ddb676,0x3bfabbe1,0xacce3185,0x3a11ba8c,0x3937b899,0x3c00bb1e,0x2452374e,0xb9903b9e,0xb9c034e7,
  0x3855bafe,0x3abab7c8,0x32c63463,0xbbd23bb2,0xb65fad33,0x3b57bbf9,0x3b71b92e,0xb5df3a19,0xbbdf3a45,0x31b6b8f8,0x3a93bbf2,0x388eaf59,
  0x3a21bbdd,0x392431e8,0x2d97ba9b,0x3bf8b884,0xba3d217f,0x3902bc00,0xbbf439b8,0xaef5b999,0xb7643bd4,0xbb183294,0x34cf385f,0xbba13ab3,
  0x3baeb648,0xb47b3b5c,0x3b04bb6c,0x37b235f7,0x3219bbf5,0x3bdaae91,0x387a390c,0xbaa23a35,0xb9a13b13,0xb9afb77a,0x9cb6bba5,0x3c00b4b7,
  0x3bd7b79b,0x32633b0a,0xb86a3bab,0xbaacb493,0xbb68adfb,0x360ebbf7,0x3b60b91b,0x36313a29,0xb785bb65,0x3b10b61a,0xbba7b625,0x34abbb63,
  0x39113aa9,0xba31386f,0x3bf6324b,0xae5f3bd8,0xba2db9aa,0x3916b9a6,0xbbf69648,0xae2dbc00,0x3b0d3874,0xb7903aa5,0x3ba9b232,0x349f3bd9,
  0xbb5eba39,0x363cb907,0x3b6a2ec3,0x36023bf5,0x3ab0adc9,0x38653bf8,0xb27c3a25,0xbbd6b91f,0x9fdb3b07,0xbc00b7a6,0xb99dbbac,0x39b3b487,
  0xba9ebb16,0x387fb76f,0x3bdc34c3,0x32013ba3,0xbbb0b889,0xb46fba97,0xb7bd31cf,0xbb01bbde,0xb759bb59,0x3b1b3654,0xbb9fbb6f,0x34dbb5eb,
  0x3a4132ad,0x38fd3bd3,0x2f27b85a,0x3bf33ab6,0x3a1d3c00,0xb929a311,0x3bf939bc,0x2d653994,0xb894b4f3,0xba90bb9c,0xb19eb742,0x3be03b21,
  0xbb73ba49,0xb5d4b8f3,0x366b2f8b,0x3b543bf2,0xbbd0bbfa,0x32dead00,0x3abd3933,0x38503a15,0xb98bbafb,0x39c537d2,0x3c003bb3,0xa51b3457,
  0xb43eb16c,0x3bb73be2,0xbaf4ba89,0x37e8389e,0xb72cb5bc,0x3b273b78,0xbb98bb4f,0x350b3682,0xb8eab845,0x3a503ac4,0xbbf0bbce,0x2fef330f,
  0xba0db982,0x393c39cd,0xbbfbbbff,0xac9c26ad,0xba81b715,0x38a83b2c,0x3be43b94,0x313bb523,0xbb7cbbef,0xb5a53029,0x36993a58,0x3b4a38e0,
  0xb340b946,0xbbcbba04,0xb83aac38,0x3acb3bfc,0x39793426,0xb9d6bbba,0xbbffbaee,0x281f37fe,0xbbfcb970,0xaba739df,0xb94fbbfe,0xb9fc28e8,
  0x340eb8b2,0xbbbdba7a,0x3ae83109,0xb80abbe6,0x3b323b45,0x36ffb6af,0x353a3b81,0x3b90358d,0xb8d63371,0x3a603bc8,0xbbedb830,0x305b3ad1,
  0xb9e7bae1,0xb9663815,0x29b13bc0,0x3bfe33eb,0x3be836e8,0x30d7bb37,0xb8bcbb8b,0xba733552,0xbb3f308d,0x36c63beb,0x3b8538cc,0x3576ba67,
  0x3825b958,0xbad8b9f4,0xbbc5aade,0x33a23bfd,0xb0bebbc2,0xbbe933d3,0x38c1bade,0xba6fb81a,0xaa163bfd,0x3bfeaa7a,0xb9eb39f0,0x3962395d,
  0x33babbea,0xbbc3b0a6,0x3adbb8c7,0xb820ba6b,0xb6d23b89,0x3b3d355e,0xbb8736dd,0x356a3b3a,0x380fbbfe,0xbae5a94d,0xbbbf396b,0x340239e3,
  0xbbfd382a,0x2b433ad5,0x39f83389,0x3954bbc6,0x38d136bb,0x3a64bb42,0x3074bb83,0xbbec3581,0x3546bbe7,0xbb8e30f0,0xbb353a76,0x36f438b7,
  0x3b7fbb92,0xb599b52f,0x3b47b70a,0x36a4bb2f,0xb122b805,0xbbe53aeb,0x38adbbbc,0xba7e341a,0xbbff3a00,0xa884394a,0xb9742c06,0xb9da3bfc,
  0xb3593a5c,0x3bc9b8db,0xbace3bee,0x38353042,0x3b96ba85,0x3517b8a3,0xb7213153,0xbb2a3be3,0x3bb8bbff,0xb432a776,0xbaf1397d,0xb7f339d2,
  0x3941bac7,0xba093840,0xbbfb3bcc,0x2c6a3328,0x3010b68d,0xbbef3b4c,0xba543b7a,0x38e5b5b1,0x384ab8ee,0x3ac1ba4d,0xb2f72fbd,0x3bcfbbf1,
  0x35c8b737,0x3b76bb24,0xb67634ff,0x3b52bb9a,0x3185b44b,0x3be1bbb5,0xb89937dd,0x3a8cbaf7,0xa5e4acce,0x3bffbbfa,0xb9c93937,0x3986ba11,
  0xaf59b5df,0x3bf2bb71,0x3a45b65f,0xb8f83b57,0xbb1e388e,0x374eba93,0x3b9ebbdf,0x34e731b6,0xbafe3c00,0xb7c82452,0x3463b990,0x3bb2b9c0,
  0xad333855,0xbbf93aba,0xb92e32c6,0x3a19bbd2,0xb9b8ad97,0x3999bbf8,0xbc003924,0xa17fba21,0xb85f3bf4,0xbab32ef5,0x32943902,0xbbd43a3d,
  0x3b6cb4cf,0xb5f73ba1,0x3b5cbb18,0x36483764,0x31e8bb04,0x3bddb7b2,0xb884b47b,0x3a9bbbae,0xbbf73263,0x2dfbbbd7,0x3a29baac,0x391b386a,
  0x3a35360e,0xb90c3b68,0xbbf53631,0xae91bb60,0xb4b7baa2,0x3ba5b87a,0x3b133219,0xb77a3bda,0xb4933c00,0xbbab1cb6,0xb79bb9a1,0x3b0ab9af,
  0xbaa93785,0xb86fbb10,0xb24b3ba7,0xbbd8b4ab,0x39aab911,0x39a63a31,0x1648bbf6,0x3c002e5f,0xb8743a2d,0xbaa5b916,0x32323bf6,0xbbd92e2d,
  0x3625bb0d,0x3b633790,0xb61abba9,0x3b65b49f,0xb4c3399d,0xbba3b9b3,0xb76fbc00,0x3b161fdb,0xb907bbdc,0x3a39b201,0x3bf5387f,0xaec33a9e,
  0x3bf8363c,0x2dc93b5e,0xb91f3602,0xba25bb6a,0xb7a63865,0xbb07bab0,0xb487bbd6,0x3bac327c,0x35eb3b01,0xbb6fb7bd,0x3b593bb0,0xb654346f,
  0xbab6b4db,0xb85abb9f,0xb2ad3759,0xbbd3bb1b,0xb994bbf3,0x39bc2f27,0xbc00ba41,0x2311b8fd,0x3889ad65,0x3a973bf9,0xb1cfba1d,0x3bde3929,
  0x3afb3bd0,0xb7d2b2de,0xbbb3babd,0xb457b850,0x3742398b,0xbb21b9c5,0xbb9cbc00,0x34f3251b,0xaf8b319e,0xbbf2bbe0,0xb8f3ba90,0x3a493894,
  0xb933b66b,0xba15bb54,0xad00b5d4,0x3bfa3b73,0x211b21e4,0xa51ba5e4,0x98b69248,0x1cb61648,0x1f122052,0xa311a452,0x9d7f9bdb,0x217f1fdb,
  0x1bdb1d7f,0x9fdba17f,0xa0529f12,0x24522311,0x124818b6,0x96489cb6,0xa1e4a11b,0x25e4251b,0x2a632b5f,0xae5faf59,0xa1e49bdb,0x25e41fdb,
  0x286b2967,0xac6aad65,0xa6e0a4e9,0x2ade28e8,0x24e926e0,0xa8e8aade,0xa967a86b,0x2d652c6a,0x1bdb21e4,0x9fdba5e4,0xab5faa63,0x2f592e5f,
  0x2dc22ea7,0xb1b6b294,0xa54d9f12,0x294d2311,0x2bf62cde,0xafefb0d7,0xaa31a86b,0x2e2d2c6a,0x286b2a31,0xac6aae2d,0xacdeabf6,0x30d72fef,
  0x1f12254d,0xa311a94d,0xaea7adc2,0x329431b6,0x302c30d2,0xb41ab4b7,0xa7a9a11b,0x2ba7251b,0x2dc22f0c,0xb1b6b2f7,0xac79aa63,0x30742e5f,
  0x2a632c79,0xae5fb074,0xaf0cadc2,0x32f731b6,0x211b27a9,0xa51baba7,0xb0d2b02c,0x34b7341a,0x317a3257,0xb552b61a,0xa902a2ad,0x2d0026ad,
  0x2f8c309f,0xb371b487,0xaddcac2e,0x31cf3029,0x2c2e2ddc,0xb029b1cf,0xb09faf8c,0x34873371,0x22ad2902,0xa6adad00,0xb257b17a,0x361a3552,
  0x32cd33e3,0xb682b76f,0xaa31a420,0x2e2d281f,0x30ac31bb,0xb493b58d,0xaf3fad2a,0x33283122,0x2d2a2f3f,0xb122b328,0xb1bbb0ac,0x358d3493,
  0x24202a31,0xa81fae2d,0xb3e3b2cd,0x376f3682,0x341334bc,0xb7a6b85a,0xab5fa4e9,0x2f5928e8,0x319432da,0xb56ab68d,0xb052ae28,0x343e3219,
  0x2e283052,0xb219b43e,0xb2dab194,0x368d356a,0x24e92b5f,0xa8e8af59,0xb4bcb413,0x385a37a6,0x34c3358c,0xb85fb8f3,0xac47a5b2,0x304229b1,
  0x327e33fd,0xb63cb785,0xb106af26,0x34e7330f,0x2f263106,0xb30fb4e7,0xb3fdb27e,0x3785363c,0x25b22c47,0xa9b1b042,0xb58cb4c3,0x38f3385f,
  0x35773662,0xb8e5b982,0xacdea67b,0x30d72a7a,0x336b3493,0xb70ab83a,0xb1bbb012,0x358d3402,0x301231bb,0xb402b58d,0xb493b36b,0x383a370a,
  0x267b2cde,0xaa7ab0d7,0xb662b577,0x398238e5,0x36303741,0xb962ba04,0xad76a744,0x316c2b43,0x342e352a,0xb7d2b8ad,0xb271b092,0x3631347b,
  0x30923271,0xb47bb631,0xb52ab42e,0x38ad37d2,0x27442d76,0xab43b16c,0xb741b630,0x3a043962,0x36ee3815,0xb9d6ba7a,0xae0ea807,0x32012c06,
  0x34a735c4,0xb84ab91b,0xb329b113,0x36d234f3,0x31133329,0xb4f3b6d2,0xb5c4b4a7,0x391b384a,0x28072e0e,0xac06b201,0xb815b6ee,0x3a7a39d6,
  0x37b4388e,0xba41bae1,0xaea7a86b,0x32942c6a,0x35233662,0xb8a8b982,0xb3e3b194,0x376f356a,0x319433e3,0xb56ab76f,0xb662b523,0x398238a8,
  0x286b2ea7,0xac6ab294,0xb88eb7b4,0x3ae13a41,0x3841390f,0xbaa2bb3a,0xaf3fa8d0,0x33282cce,0x35a13705,0xb902b9e3,0xb44fb216,0x380535df,
  0x3216344f,0xb5dfb805,0xb705b5a1,0x39e33902,0x28d02f3f,0xacceb328,0xb90fb841,0x3b3a3aa2,0x38ac3997,0xbaf7bb83,0xafd8a935,0x33ba2d33,
  0x362137ac,0xb958ba3d,0xb4aeb298,0x38503654,0x329834ae,0xb654b850,0xb7acb621,0x3a3d3958,0x29352fd8,0xad33b3ba,0xb997b8ac,0x3b833af7,
  0x391c3a28,0xbb42bbbc,0xb039a999,0x34262d97,0x36a4382d,0xb9aaba90,0xb50eb31c,0x389936c6,0x331c350e,0xb6c6b899,0xb82db6a4,0x3a9039aa,
  0x29993039,0xad97b426,0xba28b91c,0x3bbc3b42,0x39923ac3,0xbb81bbe3,0xb085a9fe,0x346f2dfb,0x372a3886,0xb9f8badb,0xb570b3a0,0x38e03737,
  0x33a03570,0xb737b8e0,0xb886b72a,0x3adb39f8,0x29fe3085,0xadfbb46f,0xbac3b992,0x3be33b81,0xb9cfbb16,0x3b9c3bf1,0x30ac2a31,0xb493ae2d,
  0xb76fb8b4,0x3a1d3afe,0x35a133e3,0xb902b76f,0xb3e3b5a1,0x376f3902,0x38b4376f,0xbafeba1d,0xaa31b0ac,0x2e2d3493,0x3b1639cf,0xbbf1bb9c,
  0xb956ba74,0x3b633bd2,0x305f29cc,0xb44badc9,0xb6e7b859,0x39d23ab6,0x353f335e,0xb8bcb6ff,0xb35eb53f,0x36ff38bc,0x385936e7,0xbab6b9d2,
  0xa9ccb05f,0x2dc9344b,0x3a743956,0xbbd2bb63,0xb8e3b9de,0x3b1e3ba1,0x30122967,0xb402ad65,0xb662b801,0x39823a67,0x34de32da,0xb874b68d,
  0xb2dab4de,0x368d3874,0x38013662,0xba67b982,0xa967b012,0x2d653402,0x39de38e3,0xbba1bb1e,0xb876b952,0x3ace3b60,0x2f8c2902,0xb371ad00,
  0xb5e1b758,0x392e3a11,0x347e3257,0xb82ab61a,0xb257b47e,0x361a382a,0x375835e1,0xba11b92e,0xa902af8c,0x2d003371,0x39523876,0xbb60bace,
  0xb80db8ce,0x3a733b10,0x2ef3289e,0xb2deac9c,0xb562b6b3,0x38d639b3,0x342031d5,0xb7bdb5a5,0xb1d5b420,0x35a537bd,0x36b33562,0xb9b3b8d6,
  0xa89eaef3,0x2c9c32de,0x38ce380d,0xbb10ba73,0xb750b851,0x3a0d3ab0,0x2e5a2839,0xb24bac38,0xb4e5b613,0x387a394f,0x33863153,0xb721b52f,
  0xb153b386,0x352f3721,0x361334e5,0xb94fb87a,0xa839ae5a,0x2c38324b,0x38513750,0xbab0ba0d,0xb68eb7b4,0x399d3a41,0x2dc227a9,0xb1b6aba7,
  0xb46ab577,0x381a38e5,0x32cd30d2,0xb682b4b7,0xb0d2b2cd,0x34b73682,0x3577346a,0xb8e5b81a,0xa7a9adc2,0x2ba731b6,0x37b4368e,0xba41b99d,
  0xb5d2b6d1,0x392439c5,0x2d2a26e0,0xb122aade,0xb3e3b4de,0x376f3874,0x32163052,0xb5dfb43e,0xb052b216,0x343e35df,0x34de33e3,0xb874b76f,
  0xa6e0ad2a,0x2ade3122,0x36d135d2,0xb9c5b924,0xb51cb5f6,0x38a3393c,0x2c932617,0xb08daa16,0xb2f4b448,0x36a437fe,0x31602fa5,0xb53ab389,
  0xafa5b160,0x3389353a,0x344832f4,0xb7feb6a4,0xa617ac93,0x2a16308d,0x35f6351c,0xb93cb8a3,0xb46ab523,0x381a38a8,0x2bf6254d,0xafefa94d,
  0xb209b36b,0x35d4370a,0x30ac2ea7,0xb493b294,0xaea7b0ac,0x32943493,0x336b3209,0xb70ab5d4,0xa54dabf6,0x294d2fef,0x3523346a,0xb8a8b81a,
  0xb378b456,0x3715380a,0x2ac82484,0xaec3a884,0xb120b24a,0x34ff360e,0x2ff22da9,0xb3d3b19e,0xada9aff2,0x319e33d3,0x324a3120,0xb60eb4ff,
  0xa484aac8,0x28842ec3,0x34563378,0xb80ab715,0xb223b31c,0x35eb36c6,0x29992376,0xad97a776,0xb039b12d,0x3426350b,0x2e8d2cac,0xb27cb0a6,
  0xacacae8d,0x30a6327c,0x312d3039,0xb50bb426,0xa376a999,0x27762d97,0x331c3223,0xb6c6b5eb,0xb0d2b194,0x34b7356a,0x286b21e4,0xac6aa5e4,
  0xaea7b012,0x32943402,0x2d2a2b5f,0xb122af59,0xab5fad2a,0x2f593122,0x30122ea7,0xb402b294,0xa1e4a86b,0x25e42c6a,0x319430d2,0xb56ab4b7,
  0xaf0cb012,0x32f73402,0x267b2052,0xaa7aa452,0xacdeadf5,0x30d731e8,0x2b912967,0xaf8bad65,0xa967ab91,0x2d652f8b,0x2df52cde,0xb1e8b0d7,
  0xa052a67b,0x24522a7a,0x30122f0c,0xb402b2f7,0xac79ad2a,0x30743122,0x24201d7f,0xa81fa17f,0xaa31ab91,0x2e2d2f8b,0x28d026e0,0xacceaade,
  0xa6e0a8d0,0x2ade2cce,0x2b912a31,0xaf8bae2d,0x9d7fa420,0x217f281f,0x2d2a2c79,0xb122b074,0xa7a9a86b,0x2ba72c6a,0x1f1218b6,0xa3119cb6,
  0xa54da67b,0x294d2a7a,0x242021e4,0xa81fa5e4,0xa1e4a420,0x25e4281f,0x267b254d,0xaa7aa94d,0x98b69f12,0x1cb62311,0x286b27a9,0xac6aaba7,
  0xa5e43bff,0xb61a3b65,0xb98239cd,0xbb3a36dd,0xaf593bf2,0xb76f3b16,0xba043946,0xbb833581,0xb2943bd4,0xb85a3ab6,0xba7a38b2,0xbbbc341a,
  0xb4b73ba5,0xb8f33a49,0xbae13815,0xbbe33153,0xac9c3bfb,0xbb87356a,0xb986b9c9,0x361abb65,0xb5a53b7c,0xbbfd2b43,0xb74ebb1e,0x3907ba39,
  0xb8d63a60,0xbbc9b359,0xb1e8bbdd,0x3a97b889,0xba7338bc,0xbaf1b7f3,0x2e91bbf5,0x3b9cb4f3,0xafbd3bf1,0xbb10b785,0x3a0db93c,0x356a3b87,
  0xb88e3a93,0xb87fba9e,0x3bcbb340,0xb0743bec,0xbb183764,0xaf27bbf3,0x3bbd340e,0xb8ad3a7e,0xbc009cb6,0x35d4bb73,0x39e73966,0xbb2a3721,
  0xb16c3be2,0xb3d3bbc2,0x38ee3a4d,0xbb10b785,0xba043946,0x36bbbb42,0xa4523c00,0xb63cbb5e,0xbbfe28e8,0x3b2fb70a,0xb9243a21,0x346fbbb0,
  0xba67b8cc,0x3bcc3328,0xbbda3219,0x3a90b894,0xb2f73bcf,0x386fbaa9,0xba89389e,0x3bc2b3d3,0xbb1e374e,0x3bf5aec3,0xbbbab426,0x3a7638b7,
  0xbb5cb648,0x39bc3994,0xb6afbb45,0x2c063bfc,0xb493bbab,0xad003bfa,0x36e8bb37,0xb9d2397d,0xb43e3bb7,0x3be9b0be,0xb84abac1,0xb86f3aa9,
  0xbbcb3340,0x38d13a64,0x37c8bafe,0xbbf8adc9,0xb94fb9fc,0xb6a43b47,0x3c00217f,0xb654bb59,0x3576bb85,0xbbfb2c6a,0x377a3b13,0x38f3ba49,
  0xb4ff3b9a,0x3a313911,0x3af4b7e8,0xb0bebbe9,0xbc00a452,0xb6023b6a,0x39d63979,0x3b35b6f4,0xb47bbbae,0xbbf9ad65,0xb6ff3b32,0x397439da,
  0x3aacb86a,0xb2debbd0,0xbbe8b0d7,0xb7f33af1,0xb5bc3b78,0x2a7a3bfd,0x37373b24,0x3a313911,0xbbbab426,0xbbe730f0,0xbaba3855,0xb8653ab0,
  0x3109bbe6,0xb41abbbc,0xb902ba3d,0xbb1bb759,0x3bfd2ade,0x3b7ab5b1,0x39afb9a1,0x35d4bb73,0xb6763b52,0xb9a639aa,0xbb4f3682,0xbbfd2a7a,
  0xbafeb7c8,0xb91fba25,0xb523bb94,0x294dbbfe,0x3884ba9b,0x3a97b889,0x3bc8b371,0x3bee3042,0x3a29391b,0x37d23afb,0x308d3beb,0xb3283bcc,
  0xb72c3b27,0xbbfeaa16,0xb5c8bb76,0x39a6b9aa,0xb9d6b979,0x3546bb8e,0x3bf9ad33,0x37a63b07,0x3ae8b80a,0x3a7e38ad,0xb2943bd4,0xbbd332ad,
  0x33a23bc5,0xba5438e5,0xbb0ab79b,0x2d00bbfa,0xb7dd3af7,0xb916ba2d,0x3b98b50b,0xaa163bfe,0xb855baba,0x3bd6b27c,0xb13b3be4,0xbae5b80f,
  0x3bf8ad97,0xb46f3bb0,0xba60b8d6,0x3aceb835,0xb6313b60,0xb9c5b98b,0x3b3fb6c6,0x2c6a3bfb,0xb8453ac4,0x30a6bbea,0x344b3bb5,0xb916ba2d,
  0xb523bb94,0x396b39e3,0xbb57b65f,0x3c009fdb,0x3b81358d,0xbbfc2c06,0x3b18b764,0xb8fd3a41,0xbae13815,0x38a3ba85,0xb2633bd7,0xb2debbd0,
  0xb8993a8c,0x3aa5b874,0xbbce330f,0x3bea30a6,0xad33bbf9,0xb4873bac,0x38e0ba58,0xbad5382a,0x399939b8,0xb654bb59,0x28e83bfe,0x352fbb92,
  0xbbf5ae91,0x3b213742,0xb958b9f4,0x35b13b7a,0xb8ea3a50,0x3bc333ba,0xb185bbe1,0xbaa53874,0x313bbbe4,0xbbbf3402,0x38f83a45,0x376fbb16,
  0x353a3b90,0x39dab974,0xbb5cb648,0x23113c00,0xb9e7b966,0xb5173b96,0x3bf7adfb,0xb7d2bafb,0xb9373a11,0x37903b0d,0x3bf0afef,0x33babbc3,
  0x365fbb57,0xb9b3b99d,0xbb4a3699,0x2b433bfd,0xaef53bf4,0x3b1b3759,0x39fcb94f,0xb599bb7f,0xb219bbda,0xbbe0b19e,0xb8253ad8,0x38e53a54,
  0xb98239cd,0xb55e3b89,0x2cce3bfa,0x37903b0d,0x38e0ba58,0x3389bbc6,0xb1b6bbdf,0xb87fba9e,0xb8303ad1,0xb0423bee,0x347b3bae,0x39293a1d,
  0x36e8bb37,0x2776bbff,0xb60ebb68,0xb9c5b98b,0xb9c93986,0xbb633625,0xbbff26ad,0xbb89b55e,0x3a45b8f8,0x3ba3b4c3,0x3bfc2c38,0x3b4236bb,
  0xbab3385f,0xbbd332ad,0xbbe6b109,0xbaebb805,0x3b13b77a,0x3bf2af8b,0x3bc033eb,0x3a8538a3,0xba0d393c,0xbb3db6d2,0x25e4bbff,0x3b63b625,
  0x3b4ab699,0x39f83954,0xb4e73b9e,0xbbf52ec3,0xbbed305b,0xb835bace,0x3884ba9b,0x3bde31cf,0x3be830d7,0x34323bb8,0xba35390c,0xbb21b742,
  0xba4d38ee,0xb4abbba7,0x3bfb2c9c,0xb6d23b3d,0x3bdfb1b6,0xb2013bdc,0xbacbb83a,0x3a64b8d1,0xbba1b4cf,0x38fdba41,0x380a3ae8,0xbbe53122,
  0x39a139af,0xbb54366b,0xa9b1bbfe,0x3b963517,0xba89389e,0x381abade,0xafbd3bf1,0xb4abbba7,0x3bfc2c38,0xbb833581,0x39c0b990,0xb6023b6a,
  0xb9dfb970,0x3b92352f,0xbbf82d97,0x3b01b7bd,0x308d3beb,0xb840bac7,0x3aa2387a,0xbbe0b19e,0xbac1384a,0x3bd8b24b,0xbbe2b16c,0x3ade381a,
  0x3b9e34e7,0xba39b907,0x37fe3aee,0xb0f0bbe7,0xb5f7bb6c,0x23113c00,0x358dbb81,0xb94a3a00,0xb79b3b0a,0x3a15b933,0xbb8b3552,0x3bff2776,
  0xbaf437e8,0x3a6f38c1,0x32f7bbcf,0xbbd8324b,0x3acb383a,0x3074bbec,0xbbb23463,0x391f3a25,0x2ba7bbfc,0xbb7f3599,0x399939b8,0x35ebbb6f,
  0xbb3f36c6,0x3a093941,0x34b7bba5,0xbbf22f8b,0xbb243737,0x2e5f3bf6,0x3bb7343e,0x38c1ba6f,0x399039c0,0x3b5eb63c,0xa81fbbff,0xbb8eb546,
  0x37b2bb04,0xb929ba1d,0xbb90353a,0xa8843bff,0xbbd7b263,0xb8503abd,0x38bc3a73,0x3bb8b432,0xbb4f3682,0xb95d39f0,0xb4ff3b9a,0x2e5f3bf6,
  0x37fe3aee,0x3a7638b7,0x3bd232c6,0x3bd6b27c,0x3a7ab8b2,0x3805baeb,0x2ef5bbf4,0xb4dbbb9f,0xb958b9f4,0xbb4cb68d,0xbc009cb6,0xbb54366b,
  0xbb7635c8,0xbc001648,0xbb78b5bc,0xb9f0b95d,0x34633bb2,0xadc93bf8,0xb7153b2c,0xb9e3396b,0x3bddb1e8,0x3bde31cf,0x3ad13830,0x38db3a5c,
  0xadfbbbf7,0x3457bbb3,0x38ccba67,0x3ac7b840,0xbb98350b,0xb962b9eb,0x3676bb52,0x3c009648,0x281f3bff,0xbb3536f4,0xba19b92e,0x3487bbac,
  0x3bbd340e,0x31223be5,0xbab3385f,0xbab6b85a,0x3825bad8,0x3bef3010,0x34933bab,0xba153933,0xbbb5344b,0x2e2dbbf6,0x3b27372c,0xb9eb3962,
  0xb2c63bd2,0xbab0b865,0x3a81b8a8,0x34023bbf,0x3a213924,0xbb0137bd,0xb05bbbed,0x3bc93359,0x3b68b60e,0x251b3c00,0xbb85b576,0x3941ba09,
  0xbbce330f,0x3a6bb8c7,0xb7dd3af7,0x2e2dbbf6,0xb7153b2c,0x294dbbfe,0x35df3b71,0xb9b3b99d,0x36af3b45,0xba00b94a,0x3ba134cf,0xbbf32f27,
  0x3bc033eb,0xbbe33153,0x3aacb86a,0xb8503abd,0xbbe13185,0x3bd93232,0xbac4b845,0x38c73a6b,0xb92e3a19,0x3b07b7a6,0xbbef3029,0x3bc63389,
  0xa17f3c00,0x35ebbb6f,0xb97039df,0x3b2fb70a,0x390c3a35,0xb4f3bb9c,0xaade3bfd,0x368dbb4c,0xbbf02fef,0x38203adb,0x3899ba8c,0xbbd9b232,
  0xba8138a8,0x3ae5380f,0x2f59bbf2,0xbba334c3,0xb6ff3b32,0x3bff2884,0xb5f7bb6c,0xb99439bc,0x29b13bfe,0x3b2ab721,0xba29b91b,0xb4573bb3,
  0xbbfa2cce,0xb49f3ba9,0x3a5038ea,0x3adbb820,0xbb7135df,0x1fdb3c00,0x3b7c35a5,0x3954b9f8,0xba3d3902,0x34db3b9f,0x3bfc2ba7,0x36a4bb47,
  0xb87a3aa2,0x38943a90,0x3bc5b3a2,0x3010bbef,0xbbff26ad,0xbb3a36dd,0xb9373a11,0xb49f3ba9,0xbbef3029,0xbad5382a,0xb88e3a93,0xb2013bdc,
  0xbbc83371,0xba5c38db,0xb7b23b04,0xad653bf9,0xbb8b3552,0xb9d2397d,0xb6313b60,0x251b3c00,0x3bf12fbd,0x3b103785,0x393c3a0d,0x356a3b87,
  0x3bd232c6,0x3ab03865,0x38a83a81,0x34023bbf,0x3ba134cf,0x3a4138fd,0x380a3ae8,0x31223be5,0x3b603631,0x39c5398b,0x36c63b3f,0x2c6a3bfb,
  0xbbe2b16c,0xb3d3bbc2,0x3a4db8ee,0x3b103785,0xbb2cb715,0x294dbbfe,0x3b71b5df,0x39b3399d,0xb9dfb970,0x352fbb92,0x3bf8ad97,0x37bd3b01,
  0xb815bae1,0x38a3ba85,0x3bd73263,0x32de3bd0,0x3bcf32f7,0xb86f3aa9,0xb89eba89,0x3bc2b3d3,0x3a19392e,0xbb0737a6,0xb029bbef,0x3bc63389,
  0x35f73b6c,0xbc002311,0x358dbb81,0x3a00394a,0xae913bf5,0xbb21b742,0x39f4b958,0x35b13b7a,0xbbb7b43e,0x3be9b0be,0xbac1384a,0x386fbaa9,
  0xb8a8ba81,0x3ae5380f,0xbbf2af59,0x3ba3b4c3,0x2ba7bbfc,0x35993b7f,0xb999b9b8,0x3b6f35eb,0x3966b9e7,0xb5173b96,0xadfbbbf7,0x37d23afb,
  0x3b9a34ff,0xba31b911,0x37e83af4,0xb0bebbe9,0x35df3b71,0x9fdbbc00,0xb5a53b7c,0x3954b9f8,0xb7b23b04,0x3a1db929,0xbb90353a,0x3bff2884,
  0xbbda3219,0x3be0319e,0xbad8b825,0x38e53a54,0xbb78b5bc,0x2a7a3bfd,0x3b24b737,0xba31b911,0xb029bbef,0xbad5382a,0x3a93388e,0x3201bbdc,
  0x3a7ab8b2,0xbaebb805,0xaef53bf4,0x3b9fb4db,0x3b3736e8,0x2776bbff,0xbb68360e,0x39c5398b,0x3b523676,0x39a6b9aa,0xb682bb4f,0xbbfd2a7a,
  0xaf593bf2,0x3b16376f,0x3a04b946,0xb581bb83,0xbbdd31e8,0xb1cf3bde,0x3ad13830,0x3a5cb8db,0xb77abb13,0xbbf22f8b,0xb3eb3bc0,0x3a8538a3,
  0xbb27b72c,0xbbfeaa16,0xbb7635c8,0xb9a639aa,0x35a5bb7c,0xab43bbfd,0xb74ebb1e,0xba39b907,0x3bbd340e,0x3be5b122,0x3ab3b85f,0x385abab6,
  0xb0d73be8,0x34323bb8,0x390c3a35,0x3b213742,0x3af737dd,0x39163a2d,0x350b3b98,0xaa163bfe,0xb88e3a93,0xba9e387f,0xbbcb3340,0xbbecb074,
  0xba21b924,0xb7bdbb01,0xb05bbbed,0x3359bbc9,0x39afb9a1,0x3b54b66b,0x3bfea9b1,0x3b963517,0xbac4b845,0x30a6bbea,0x3bb5b44b,0x39163a2d,
  0x3a04b946,0x3b4236bb,0xa4523c00,0xbb5e363c,0x36af3b45,0xb94a3a00,0xbba1b4cf,0xaf27bbf3,0xbbeb308d,0xb840bac7,0x387abaa2,0x3be0319e,
  0x3a8c3899,0xbaa53874,0xb30fbbce,0x3bea30a6,0xbb1e374e,0xaec3bbf5,0x3bba3426,0xb8b73a76,0x217fbc00,0x3b6f35eb,0xb97039df,0xb70abb2f,
  0x3b0a379b,0xba153933,0xb552bb8b,0x3bff2776,0xba50b8ea,0x3bc333ba,0xbbe13185,0x3aa5b874,0x3bcbb340,0xba6438d1,0x37c8bafe,0xadc93bf8,
  0xb6ff3b32,0x2884bbff,0x35f73b6c,0xb9bcb994,0xb6c6bb3f,0x3a093941,0xbba5b4b7,0x3bf2af8b,0x3a113937,0xb790bb0d,0x2fef3bf0,0x33babbc3,
  0xbc00a452,0x3b6a3602,0xb9d6b979,0x36f43b35,0x3a3db902,0xbb9f34db,0x3bfc2ba7,0xbb47b6a4,0xb2633bd7,0x3850babd,0xba7338bc,0x3bb8b432,
  0xb9cdb982,0xb55e3b89,0x3bfaacce,0xb790bb0d,0x3bba3426,0xb0f0bbe7,0xbaba3855,0x3ab03865,0xbbc83371,0x38db3a5c,0x37b2bb04,0xbbf9ad65,
  0x39f4b958,0xbb4cb68d,0x9cb63c00,0x3b54b66b,0x398639c9,0x3b63b625,0xa6adbbff,0xbb89b55e,0xbafeb7c8,0xba25391f,0x35233b94,0x3bfe294d,
  0x3bd43294,0x385abab6,0xb8b2ba7a,0xbbbc341a,0xbbf72dfb,0xb4573bb3,0x3a6738cc,0x3ac7b840,0xb93cba0d,0xbb3db6d2,0xbbffa5e4,0xbb633625,
  0x39d63979,0x3b8e3546,0x3bf9ad33,0x3b07b7a6,0xba60b8d6,0xbbc9b359,0xbbdd31e8,0xba973889,0x3ad83825,0x3bef3010,0x3babb493,0x3a15b933,
  0x38ee3a4d,0x34ab3ba7,0xac9c3bfb,0xb6d23b3d,0xb855baba,0xb27cbbd6,0x313bbbe4,0x380fbae5,0x37643b18,0x2f273bf3,0xb40e3bbd,0xb8ad3a7e,
  0xb60ebb68,0xa51bbc00,0x3576bb85,0x3941ba09,0xb89eba89,0x381abade,0x3bf12fbd,0x34ab3ba7,0x35233b94,0xb9e3396b,0xbb57b65f,0x9fdbbc00,
  0xa8e8bbfe,0x3b2fb70a,0x3a213924,0xb46f3bb0,0xb3eb3bc0,0xbbe33153,0xb86abaac,0x3850babd,0x384a3ac1,0xbbd8324b,0x316cbbe2,0x3ade381a,
  0xad33bbf9,0x3bac3487,0xb8e03a58,0xb82abad5,0xb6483b5c,0xb9bcb994,0x3b45b6af,0x2c063bfc,0x3a35b90c,0x34f33b9c,0xbbfdaade,0x368dbb4c,
  0xb7e8baf4,0x3a6f38c1,0xbbcfb2f7,0x3bd8b24b,0xb13b3be4,0xb402bbbf,0x38f83a45,0xbb16b76f,0x39fcb94f,0xb6a43b47,0x217fbc00,0x36543b59,
  0xbbfe29b1,0x3b2ab721,0xb91b3a29,0x3457bbb3,0x37373b24,0xae5fbbf6,0xb43e3bb7,0x38c1ba6f,0x365fbb57,0xb99d39b3,0x3b4ab699,0xbbfd2b43,
  0xbbae347b,0x3bf92d65,0xbb32b6ff,0x397439da,0x3aa2387a,0xb894ba90,0x33a23bc5,0x3010bbef,0xb682bb4f,0xb95d39f0,0x3b9a34ff,0xae5fbbf6,
  0xb8e03a58,0x3bc63389,0xb1b6bbdf,0xba9e387f,0x3be63109,0xb41abbbc,0xba3d3902,0x3b1b3759,0xb552bb8b,0xb9d2397d,0x3b603631,0xa51bbc00,
  0x35c83b76,0x3c009648,0x35bcbb78,0xb9f0b95d,0x3a45b8f8,0xb4c3bba3,0xbbfcac38,0xb6bb3b42,0xba9bb884,0xba973889,0x33713bc8,0x3bee3042,
  0xb4b73ba5,0x3a4938f3,0x3ae1b815,0xb153bbe3,0xb50bbb98,0xb962b9eb,0xbb52b676,0xbc001648,0xbb4a3699,0xb95439f8,0xb4e73b9e,0x2ec33bf5,
  0x380a3ae8,0x3a7e38ad,0x3bd43294,0x3bd3b2ad,0x3a73b8bc,0x37f3baf1,0x2e91bbf5,0xb4f3bb9c,0x344b3bb5,0xae2d3bf6,0xb72c3b27,0xb9eb3962,
  0x3bdfb1b6,0x3bdc3201,0x3acb383a,0x38d13a64,0xad97bbf8,0x346fbbb0,0x38d6ba60,0x3aceb835,0xbc009cb6,0xbb73b5d4,0xb9e7b966,0xb721bb2a,
  0xb30fbbce,0x3a6bb8c7,0x3af737dd,0xae2d3bf6,0xbbfcac38,0xb581bb83,0x39c0b990,0x3b6a3602,0xb58d3b81,0xbbfc2c06,0xb764bb18,0x38fdba41,
  0x3a6738cc,0xb3283bcc,0xbbda3219,0xb894ba90,0x31853be1,0xbbd9b232,0x3845bac4,0x38c73a6b,0x3b9e34e7,0xb9073a39,0xb7febaee,0x3be7b0f0,
  0x39b8b999,0x36543b59,0xbbfe28e8,0x352fbb92,0xb493bbab,0x3bfa2d00,0xb6e83b37,0xb97db9d2,0xafefbbf0,0x38203adb,0xba8cb899,0x3bd93232,
  0xbacbb83a,0x3bec3074,0xbbb23463,0x3a25b91f,0xbb90353a,0x39dab974,0xb6483b5c,0xa311bc00,0xb5763b85,0xac6abbfb,0x377a3b13,0xba49b8f3,
  0x2cce3bfa,0x349fbba9,0xb8ea3a50,0x3adbb820,0x399039c0,0xb63cbb5e,0x281f3bff,0x3546bb8e,0x3bf42ef5,0xbb1bb759,0x394f39fc,0xb599bb7f,
  0x3aacb86a,0xbbd032de,0x3be830d7,0xbaf1b7f3,0xa6adbbff,0xbb3a36dd,0x3a113937,0x349fbba9,0xb7febaee,0xb8b73a76,0x3bd232c6,0xb27cbbd6,
  0xbad1b830,0xb0423bee,0x3baeb47b,0xb929ba1d,0xbbfdaade,0x35b13b7a,0x39afb9a1,0xbb73b5d4,0xa5e43bff,0x3b65361a,0x3982b9cd,0xb6ddbb3a,
  0x34633bb2,0x3bf82dc9,0x3715bb2c,0xb96bb9e3,0x385f3ab3,0x3bd3b2ad,0x3109bbe6,0xbaebb805,0x3a29391b,0x3afbb7d2,0xb08dbbeb,0xbbccb328,
  0x2c9cbbfb,0xb56abb87,0xb986b9c9,0xbb65b61a,0xa81fbbff,0xb6f4bb35,0xba19b92e,0xbbacb487,0xb05bbbed,0xb835bace,0xba9bb884,0xbbdeb1cf,
  0xb3a2bbc5,0xb8e5ba54,0xbb0ab79b,0xbbfaad00,0x00000000,0x00000000,0x00000000,0x00000000,0xaa1f0000,0xaf64ada8,0xaf64b000,0xaa1fada8,
  0xada80000,0xada8b000,0x2da88000,0x2da83000,0xaf640000,0x2a1fada8,0x2a1f3000,0xaf64ada8,0xb0000000,0x30008000,0xb0000000,0x30008000,
  0xaf640000,0x2a1f2da8,0x2a1fb000,0xaf642da8,0xada80000,0xada83000,0x2da88000,0x2da8b000,0xaa1f0000,0xaf642da8,0xaf643000,0xaa1f2da8,
  0x00000000,0x00000000,0x00000000,0x00000000,0x2a1f8000,0x2f642da8,0x2f643000,0x2a1f2da8,0xada80000,0xada8b000,0x2da88000,0x2da83000,
  0x2f648000,0xaa1f2da8,0xaa1fb000,0x2f642da8,0xb0000000,0x30008000,0xb0000000,0x30008000,0x2f648000,0xaa1fada8,0xaa1f3000,0x2f64ada8,
  0xada80000,0xada83000,0x2da88000,0x2da8b000,0x2a1f8000,0x2f64ada8,0x2f64b000,0x2a1fada8,0x80000000,0x80000000,0x80000000,0x80000000,
  0x2a1f0000,0x2f64ada8,0x2f64b000,0x2a1fada8,0x2da80000,0x2da8b000,0xada88000,0xada83000,0x2f640000,0xaa1fada8,0xaa1f3000,0x2f64ada8,
  0x30000000,0xb0008000,0x30000000,0xb0008000,0x2f640000,0xaa1f2da8,0xaa1fb000,0x2f642da8,0x2da80000,0x2da83000,0xada88000,0xada8b000,
  0x2a1f0000,0x2f642da8,0x2f643000,0x2a1f2da8,0x80000000,0x80000000,0x80000000,0x80000000,0xaa1f8000,0xaf642da8,0xaf643000,0xaa1f2da8,
  0x2da80000,0x2da8b000,0xada88000,0xada83000,0xaf648000,0x2a1f2da8,0x2a1fb000,0xaf642da8,0x30000000,0xb0008000,0x30000000,0xb0008000,
  0xaf648000,0x2a1fada8,0x2a1f3000,0xaf64ada8,0x2da80000,0x2da83000,0xada88000,0xada8b000,0xaa1f8000,0xaf64ada8,0xaf64b000,0xaa1fada8,
  0x30003000,0x30003000,0x30003000,0x30003000,0x2f643000,0x2a1f2da8,0xaa1f0000,0xaf64ada8,0x2da83000,0xada80000,0xada8b000,0x2da88000,
  0x2a1f3000,0xaf64ada8,0x2f648000,0xaa1f2da8,0x00003000,0x8000b000,0x00003000,0x8000b000,0xaa1f3000,0x2f64ada8,0xaf640000,0x2a1f2da8,
  0xada83000,0x2da88000,0x2da8b000,0xada80000,0xaf643000,0xaa1f2da8,0x2a1f8000,0x2f64ada8,0x30003000,0x30003000,0x30003000,0x30003000,
  0xaf64b000,0xaa1fada8,0x2a1f8000,0x2f642da8,0x2da83000,0xada80000,0xada8b000,0x2da88000,0xaa1fb000,0x2f642da8,0xaf640000,0x2a1fada8,
  0x00003000,0x8000b000,0x00003000,0x8000b000,0x2a1fb000,0xaf642da8,0x2f648000,0xaa1fada8,0xada83000,0x2da88000,0x2da8b000,0xada80000,
  0x2f64b000,0x2a1fada8,0xaa1f0000,0xaf642da8,0xb0003000,0xb0003000,0xb0003000,0xb0003000,0xaf643000,0xaa1f2da8,0x2a1f0000,0x2f64ada8,
  0xada83000,0x2da80000,0x2da8b000,0xada88000,0xaa1f3000,0x2f64ada8,0xaf648000,0x2a1f2da8,0x80003000,0x0000b000,0x80003000,0x0000b000,
  0x2a1f3000,0xaf64ada8,0x2f640000,0xaa1f2da8,0x2da83000,0xada88000,0xada8b000,0x2da80000,0x2f643000,0x2a1f2da8,0xaa1f8000,0xaf64ada8,
  0xb0003000,0xb0003000,0xb0003000,0xb0003000,0x2f64b000,0x2a1fada8,0xaa1f8000,0xaf642da8,0xada83000,0x2da80000,0x2da8b000,0xada88000,
  0x2a1fb000,0xaf642da8,0x2f640000,0xaa1fada8,0x80003000,0x0000b000,0x80003000,0x0000b000,0xaa1fb000,0x2f642da8,0xaf648000,0x2a1fada8,
  0x2da83000,0xada88000,0xada8b000,0x2da80000,0xaf64b000,0xaa1fada8,0x2a1f0000,0x2f642da8,0x80008000,0x80008000,0x80008000,0x80008000,
  0x2a1f8000,0x2f642da8,0x2f643000,0x2a1f2da8,0x2da88000,0x2da83000,0xada80000,0xada8b000,0x2f648000,0xaa1f2da8,0xaa1fb000,0x2f642da8,
  0x30008000,0xb0000000,0x30008000,0xb0000000,0x2f648000,0xaa1fada8,0xaa1f3000,0x2f64ada8,0x2da88000,0x2da8b000,0xada80000,0xada83000,
  0x2a1f8000,0x2f64ada8,0x2f64b000,0x2a1fada8,0x80008000,0x80008000,0x80008000,0x80008000,0xaa1f0000,0xaf64ada8,0xaf64b000,0xaa1fada8,
  0x2da88000,0x2da83000,0xada80000,0xada8b000,0xaf640000,0x2a1fada8,0x2a1f3000,0xaf64ada8,0x30008000,0xb0000000,0x30008000,0xb0000000,
  0xaf640000,0x2a1f2da8,0x2a1fb000,0xaf642da8,0x2da88000,0x2da8b000,0xada80000,0xada83000,0xaa1f0000,0xaf642da8,0xaf643000,0xaa1f2da8,
  0x00008000,0x00008000,0x00008000,0x00008000,0xaa1f8000,0xaf642da8,0xaf643000,0xaa1f2da8,0xada88000,0xada83000,0x2da80000,0x2da8b000,
  0xaf648000,0x2a1f2da8,0x2a1fb000,0xaf642da8,0xb0008000,0x30000000,0xb0008000,0x30000000,0xaf648000,0x2a1fada8,0x2a1f3000,0xaf64ada8,
  0xada88000,0xada8b000,0x2da80000,0x2da83000,0xaa1f8000,0xaf64ada8,0xaf64b000,0xaa1fada8,0x00008000,0x00008000,0x00008000,0x00008000,
  0x2a1f0000,0x2f64ada8,0x2f64b000,0x2a1fada8,0xada88000,0xada83000,0x2da80000,0x2da8b000,0x2f640000,0xaa1fada8,0xaa1f3000,0x2f64ada8,
  0xb0008000,0x30000000,0xb0008000,0x30000000,0x2f640000,0xaa1f2da8,0xaa1fb000,0x2f642da8,0xada88000,0xada8b000,0x2da80000,0x2da83000,
  0x2a1f0000,0x2f642da8,0x2f643000,0x2a1f2da8,
};

constexpr int kThreads = 384;
constexpr int kCtas = 128;

#define EARLY 2
#define HT0 13800
#define HGAP 500
#define PREP0 1600
#define PREPGAP 650
#define L0 2
#define WQT 11800
#define QGAP 400
#define QT 17800
#define PSEQ 1
#define NY 18
#define ROT 1
#define MP 3
#define QM 0x9c000
#define OSEQ 0
#define TAIL 3
#define TAILE 0
#define ENDS 0
#define PUB 1
#define PSW 6
#define YV 4
#define PU 2
#define POSTGAP 1000
#define SAFE 1
#define EXP 0

constexpr int NS1 = 6;
__host__ __device__ constexpr int slot1(int it) { return (it + 4) % NS1; }
__host__ __device__ constexpr uint32_t w1_off(int s) { return (1 + s + (s >> 1)) * 16384; }
__host__ __device__ constexpr uint32_t x1_off(int it) { return ((it >> 1) & 3) * 49152; }
constexpr uint32_t ST2 = 32768;
constexpr uint32_t RA = 131072;
constexpr uint32_t RB = 163840;
constexpr uint32_t RU = 196608;
constexpr uint32_t Y_IN = RU;
constexpr uint32_t SM_ONES = 229376;
constexpr uint32_t SM_F2 = SM_ONES + 128;
constexpr uint32_t SM_BAR = 231424;
constexpr uint32_t SM_SCALE = SM_ONES + 1792;
constexpr uint32_t SM_MAX = SM_BAR + 512;
constexpr uint32_t SM_TOTAL = 232448;
constexpr uint32_t SM_BASE = 1024;
__host__ __device__ constexpr uint32_t kv_off(int h) { return RB + (h >> 1) * 16384 + (h & 1) * 2560; }

enum Bar { B_F1 = 0, B_F2 = 6, B_H = B_F2 + 4, B_KVL = 12, B_RDY = 20, B_Q = 34, B_MAX, B_ZERO, B_U, B_KV,
           B_E1 = 39, B_E2 = 45, B_I2 = B_E2 + 4,
           B_KVE = 51, B_VST, B_KVM, B_KVP, B_KVI, B_OW, B_ZST = 58,
           B_OFREE = 59, B_F2M, B_STG, B_Y, B_COUNT = 64, B_U2 = B_KVL };
__host__ __device__ constexpr int slot2(int n) { return n < 22 ? n & 3 : (0x1032510325ull >> (4 * (n - 22))) & 7; }
__host__ __device__ constexpr int par2(int n) { return n < 22 ? (n >> 2) & 1 : (0x326 >> (n - 22)) & 1; }

constexpr int KV_WORDS = 4096 + 128;
struct Scratch {
  float kv[8][KV_WORDS];
  unsigned kvflag[8 * 32], zflag[8 * 32], oflag[16 * 32], epoch[kCtas];
};
struct Params {
  CUtensorMap w1, x, k, v, w2, wo, o, outa, q, outb;
  const __nv_bfloat16* shift_k;
  const __nv_bfloat16* ssm_k;
  const __nv_bfloat16* ssm_d;
  const __nv_bfloat16* q_ptr;
  const __nv_bfloat16* w_ptr;
  const __nv_bfloat16* wo_ptr;
  uint64_t zero;
  Scratch* g;
  const uint32_t* tab;
};

__device__ __align__(128) Scratch g_scratch;
__device__ __align__(128) __nv_bfloat16 g_o[2048 * 1024];

#define TSTAMP(cond, i) do { } while (0)
#define GSTAMP(cond, i) do { } while (0)
#define KSTAMP(n) do { } while (0)
#define QSTAMP(n) do { } while (0)

constexpr int kSpinLimit = 1 << 14;

DEVI void mbar_init(uint32_t a, uint32_t c) { asm volatile("mbarrier.init.shared::cta.b64 [%0], %1;" :: "r"(a), "r"(c) : "memory"); }
DEVI void mbar_expect(uint32_t a, uint32_t b) { asm volatile("mbarrier.arrive.expect_tx.shared::cta.b64 _, [%0], %1;" :: "r"(a), "r"(b) : "memory"); }
DEVI void mbar_arrive(uint32_t a) { asm volatile("mbarrier.arrive.shared::cta.b64 _, [%0];" :: "r"(a) : "memory"); }
DEVI void mbar_arrive_if(uint32_t a, bool pred) {
  asm volatile("{\n.reg .pred p;\nsetp.ne.b32 p, %1, 0;\n@p mbarrier.arrive.shared::cta.b64 _, [%0];\n}" :: "r"(a), "r"((int)pred) : "memory");
}
DEVI void mbar_wait(uint32_t a, uint32_t parity) {
  asm volatile("{\n.reg .pred p;\n.reg .u32 n;\nmov.u32 n, 0;\nW_LOOP:\n"
               "mbarrier.try_wait.parity.shared::cta.b64 p, [%0], %1;\n@p bra W_DONE;\n"
               "add.u32 n, n, 1;\nsetp.lt.u32 p, n, %2;\n@p bra W_LOOP;\nW_DONE:\n}"
               :: "r"(a), "r"(parity), "n"(kSpinLimit) : "memory");
}
DEVI void mbar_wait_long(uint32_t a, uint32_t parity) {
  asm volatile("{\n.reg .pred p;\n.reg .u32 n;\nmov.u32 n, 0;\nW_LOOP:\n"
               "mbarrier.try_wait.parity.shared::cta.b64 p, [%0], %1, %3;\n@p bra W_DONE;\n"
               "add.u32 n, n, 1;\nsetp.lt.u32 p, n, %2;\n@p bra W_LOOP;\nW_DONE:\n}"
               :: "r"(a), "r"(parity), "n"(kSpinLimit), "r"(4000) : "memory");
}
DEVI void flag_wait(const unsigned* p, unsigned target) {
  int n = 0; unsigned v;
  do {
    asm volatile("ld.relaxed.gpu.global.u32 %0, [%1];" : "=r"(v) : "l"(p) : "memory");
  } while ((int)(v - target) < 0 && ++n < kSpinLimit);
  asm volatile("fence.acquire.gpu;" ::: "memory");
}
DEVI unsigned ld_relaxed(const unsigned* p) { unsigned v; asm volatile("ld.relaxed.gpu.global.u32 %0, [%1];" : "=r"(v) : "l"(p) : "memory"); return v; }
DEVI uint32_t clock32() { uint32_t t; asm volatile("mov.u32 %0, %%clock;" : "=r"(t)); return t; }
DEVI void pace(uint32_t t0, uint32_t n) { while (clock32() - t0 < n) __nanosleep(20); }
DEVI bool elect() { uint32_t p; asm volatile("{\n.reg .pred p;\nelect.sync _|p, 0xffffffff;\nselp.u32 %0, 1, 0, p;\n}" : "=r"(p)); return p; }
DEVI void fence_async_smem() { asm volatile("fence.proxy.async.shared::cta;" ::: "memory"); }
DEVI void bar_sync(int id, int n) { asm volatile("bar.sync %0, %1;" :: "r"(id), "r"(n) : "memory"); }
DEVI void cluster_sync() { asm volatile("barrier.cluster.arrive.relaxed.aligned;\nbarrier.cluster.wait.aligned;" ::: "memory"); }
DEVI void wg_fence() { asm volatile("wgmma.fence.sync.aligned;" ::: "memory"); }
DEVI void wg_commit() { asm volatile("wgmma.commit_group.sync.aligned;" ::: "memory"); }
template <int N> DEVI void wg_wait() { asm volatile("wgmma.wait_group.sync.aligned %0;" :: "n"(N) : "memory"); }
template <int N> DEVI void pin(uint32_t* r) {
#pragma unroll
  for (int i = 0; i < N; i++) asm volatile("" : "+r"(r[i]));
}
template <int N> DEVI void pin(float* r) {
#pragma unroll
  for (int i = 0; i < N; i++) asm volatile("" : "+f"(r[i]));
}

DEVI void tma2d(uint32_t dst, const CUtensorMap* m, int c0, int c1, uint32_t bar) {
  asm volatile("cp.async.bulk.tensor.2d.shared::cluster.global.mbarrier::complete_tx::bytes [%0], [%1, {%3, %4}], [%2];"
               :: "r"(dst), "l"(m), "r"(bar), "r"(c0), "r"(c1) : "memory");
}
DEVI void tma2d_mc(uint32_t dst, const CUtensorMap* m, int c0, int c1, uint32_t bar) {
  asm volatile("cp.async.bulk.tensor.2d.shared::cluster.global.mbarrier::complete_tx::bytes.multicast::cluster [%0], [%1, {%3, %4}], [%2], %5;"
               :: "r"(dst), "l"(m), "r"(bar), "r"(c0), "r"(c1), "h"((uint16_t)3) : "memory");
}
DEVI void tma3d(uint32_t dst, const CUtensorMap* m, int c0, int c1, int c2, uint32_t bar) {
  asm volatile("cp.async.bulk.tensor.3d.shared::cluster.global.mbarrier::complete_tx::bytes [%0], [%1, {%3, %4, %5}], [%2];"
               :: "r"(dst), "l"(m), "r"(bar), "r"(c0), "r"(c1), "r"(c2) : "memory");
}
DEVI void tma4d(uint32_t dst, const CUtensorMap* m, int c1, int c2, int c3, uint32_t bar) {
  asm volatile("cp.async.bulk.tensor.4d.shared::cluster.global.mbarrier::complete_tx::bytes [%0], [%1, {%3, %4, %5, %6}], [%2];"
               :: "r"(dst), "l"(m), "r"(bar), "r"(0), "r"(c1), "r"(c2), "r"(c3) : "memory");
}
DEVI void tma5d(uint32_t dst, const CUtensorMap* m, int c0, int c1, int c3, int c4, uint32_t bar) {
  asm volatile("cp.async.bulk.tensor.5d.shared::cluster.global.mbarrier::complete_tx::bytes [%0], [%1, {%3, %4, %5, %6, %7}], [%2];"
               :: "r"(dst), "l"(m), "r"(bar), "r"(c0), "r"(c1), "r"(0), "r"(c3), "r"(c4) : "memory");
}
DEVI void tma2d_store(const CUtensorMap* m, uint32_t src, int c0, int c1) {
  asm volatile("cp.async.bulk.tensor.2d.global.shared::cta.bulk_group [%0, {%2, %3}], [%1];" :: "l"(m), "r"(src), "r"(c0), "r"(c1) : "memory");
}
DEVI void tma2d_store_e(const CUtensorMap* m, uint32_t src, int c0, int c1) {
  asm volatile("{\n.reg .pred e;\nelect.sync _|e, 0xffffffff;\n@e cp.async.bulk.tensor.2d.global.shared::cta.bulk_group [%0, {%2, %3}], [%1];\n"
               "@e cp.async.bulk.commit_group;\n}" :: "l"(m), "r"(src), "r"(c0), "r"(c1) : "memory");
}
DEVI void tma5d_store(const CUtensorMap* m, uint32_t src, int c0, int c1, int c3, int c4) {
  asm volatile("cp.async.bulk.tensor.5d.global.shared::cta.bulk_group [%0, {%2, %3, %4, %5, %6}], [%1];\ncp.async.bulk.commit_group;"
               :: "l"(m), "r"(src), "r"(c0), "r"(c1), "r"(0), "r"(c3), "r"(c4) : "memory");
}
DEVI void bulk_load(uint32_t dst, const void* src, uint32_t bytes, uint32_t bar) {
  asm volatile("cp.async.bulk.shared::cluster.global.mbarrier::complete_tx::bytes [%0], [%1], %2, [%3];" :: "r"(dst), "l"(src), "r"(bytes), "r"(bar) : "memory");
}
DEVI uint32_t mapa(uint32_t a, int rank) { uint32_t r; asm("mapa.shared::cluster.u32 %0, %1, %2;" : "=r"(r) : "r"(a), "r"(rank)); return r; }
DEVI void st_async4(uint32_t dst, uint32_t a, uint32_t b, uint32_t c, uint32_t d, uint32_t bar) {
  asm volatile("st.async.weak.shared::cluster.mbarrier::complete_tx::bytes.v4.b32 [%0], {%1,%2,%3,%4}, [%5];"
               :: "r"(dst), "r"(a), "r"(b), "r"(c), "r"(d), "r"(bar) : "memory");
}
DEVI void st_either8(bool local, uint32_t dst, uint32_t bar, uint32_t a, uint32_t b, uint32_t c, uint32_t d, uint32_t e, uint32_t f, uint32_t g, uint32_t h) {
  asm volatile("{\n.reg .pred p;\nsetp.ne.b32 p, %10, 0;\n@p st.shared.v4.b32 [%0], {%2,%3,%4,%5};\n@p st.shared.v4.b32 [%0 + 4096], {%6,%7,%8,%9};\n@p bra.uni E_DONE;\n"
               "st.async.weak.shared::cluster.mbarrier::complete_tx::bytes.v4.b32 [%0], {%2,%3,%4,%5}, [%1];\n"
               "st.async.weak.shared::cluster.mbarrier::complete_tx::bytes.v4.b32 [%0 + 4096], {%6,%7,%8,%9}, [%1];\nE_DONE:\n}"
               :: "r"(dst), "r"(bar), "r"(a), "r"(b), "r"(c), "r"(d), "r"(e), "r"(f), "r"(g), "r"(h), "r"((int)local) : "memory");
}
DEVI void red_async_max(uint32_t dst, uint32_t a, uint32_t bar) {
  asm volatile("red.async.relaxed.cluster.shared::cluster.mbarrier::complete_tx::bytes.max.u32 [%0], %1, [%2];" :: "r"(dst), "r"(a), "r"(bar) : "memory");
}
DEVI void pf_line(const void* p) { asm volatile("prefetch.global.L2 [%0];" :: "l"(p) : "memory"); }
DEVI void bulk_commit() { asm volatile("cp.async.bulk.commit_group;" ::: "memory"); }
DEVI void bulk_wait_all() { asm volatile("cp.async.bulk.wait_group 0;" ::: "memory"); }
DEVI void bulk_wait_read() { asm volatile("cp.async.bulk.wait_group.read 0;" ::: "memory"); }
DEVI void prefetch_map(const CUtensorMap* m) { asm volatile("prefetch.tensormap [%0];" :: "l"(m) : "memory"); }

__host__ __device__ constexpr uint32_t dlo(uint32_t off, uint32_t lbo) { return (off >> 4) + ((lbo >> 4) << 16); }
struct Desc {
  uint64_t v;
  DEVI Desc(uint64_t z, uint32_t base, uint32_t sbo, uint32_t mode) : v(z + (base | (uint64_t)((sbo >> 4) | (mode << 30)) << 32)) { asm volatile("" : "+l"(v)); }
  DEVI void renew(uint64_t z) { asm volatile("add.s64 %0, %0, %1;" : "+l"(v) : "l"(z)); }
  DEVI uint64_t at(uint32_t lo) const { uint64_t r; asm volatile("add.s64 %0, %1, %2;" : "=l"(r) : "l"(v), "l"((int64_t)(int32_t)lo)); return r; }
};
DEVI uint32_t pack_bf16(float lo, float hi) { uint32_t r; asm("cvt.rn.bf16x2.f32 %0, %1, %2;" : "=r"(r) : "f"(hi), "f"(lo)); return r; }
DEVI uint32_t pack_f16(float lo, float hi) { uint32_t r; asm("cvt.rn.f16x2.f32 %0, %1, %2;" : "=r"(r) : "f"(hi), "f"(lo)); return r; }
DEVI void stsm4(uint32_t addr, uint32_t r0, uint32_t r1, uint32_t r2, uint32_t r3) {
  asm volatile("stmatrix.sync.aligned.m8n8.x4.shared.b16 [%0], {%1,%2,%3,%4};" :: "r"(addr), "r"(r0), "r"(r1), "r"(r2), "r"(r3) : "memory");
}
DEVI void sts128(uint32_t addr, uint32_t a, uint32_t b, uint32_t c, uint32_t d) {
  asm volatile("st.shared.v4.b32 [%0], {%1,%2,%3,%4};" :: "r"(addr), "r"(a), "r"(b), "r"(c), "r"(d) : "memory");
}
DEVI void sts32(uint32_t addr, uint32_t v) { asm volatile("st.shared.b32 [%0], %1;" :: "r"(addr), "r"(v) : "memory"); }
DEVI uint32_t lds32(uint32_t a) { uint32_t v; asm volatile("ld.shared.b32 %0, [%1];" : "=r"(v) : "r"(a)); return v; }
DEVI void lds128(uint32_t* v, uint32_t a) {
  asm volatile("ld.shared.v4.b32 {%0,%1,%2,%3}, [%4];" : "=r"(v[0]), "=r"(v[1]), "=r"(v[2]), "=r"(v[3]) : "r"(a));
}
DEVI void ldg128(uint32_t* v, const void* p) {
  asm volatile("ld.global.nc.L1::no_allocate.v4.b32 {%0,%1,%2,%3}, [%4];" : "=r"(v[0]), "=r"(v[1]), "=r"(v[2]), "=r"(v[3]) : "l"(p));
}
DEVI float rcp(float x) { float r; asm("rcp.approx.ftz.f32 %0, %1;" : "=f"(r) : "f"(x)); return r; }
DEVI float exp_sat(float t) {
  float e, s;
  asm("ex2.approx.ftz.f32 %0, %1;" : "=f"(e) : "f"(t * 1.4426950408889634f));
  asm("add.sat.f32 %0, %1, 0f358637BD;" : "=f"(s) : "f"(e));
  return s;
}
DEVI uint32_t phi2(float a, float b) {
  uint32_t r, o;
  asm("cvt.rn.relu.bf16x2.f32 %0, %1, %2;" : "=r"(r) : "f"(b), "f"(a));
  asm("add.rn.bf16x2 %0, %1, %2;" : "=r"(o) : "r"(r), "r"(pack_bf16(exp_sat(a), exp_sat(b))));
  return o;
}
DEVI void arrive_both(uint32_t bar, int lane, bool pred = true) {
  asm volatile("{\n.reg .pred p;\n.reg .b32 r;\nsetp.ne.b32 p, %2, 0;\nmapa.shared::cluster.u32 r, %0, %1;\n@p mbarrier.arrive.shared::cluster.b64 _, [r];\n}"
               :: "r"(bar), "r"(lane & 1), "r"((int)(pred && lane < 2)) : "memory");
}
DEVI uint32_t bmul2(uint32_t a, uint32_t b) { uint32_t r; asm("mul.rn.bf16x2 %0, %1, %2;" : "=r"(r) : "r"(a), "r"(b)); return r; }
DEVI uint32_t bfma2(uint32_t a, uint32_t b, uint32_t c) { uint32_t r; asm("fma.rn.bf16x2 %0, %1, %2, %3;" : "=r"(r) : "r"(a), "r"(b), "r"(c)); return r; }
DEVI uint32_t bamax2(uint32_t a, uint32_t b) { uint32_t r; asm("max.NaN.xorsign.abs.bf16x2 %0, %1, %2;" : "=r"(r) : "r"(a), "r"(b)); return r; }
DEVI uint32_t hmul2(uint32_t a, uint32_t b) { uint32_t r; asm("mul.rn.f16x2 %0, %1, %2;" : "=r"(r) : "r"(a), "r"(b)); return r; }
DEVI uint32_t hadd2(uint32_t a, uint32_t b) { uint32_t r; asm("add.rn.f16x2 %0, %1, %2;" : "=r"(r) : "r"(a), "r"(b)); return r; }
DEVI uint32_t hsub2(uint32_t a, uint32_t b) { uint32_t r; asm("sub.rn.f16x2 %0, %1, %2;" : "=r"(r) : "r"(a), "r"(b)); return r; }
DEVI uint32_t hfma2(uint32_t a, uint32_t b, uint32_t c) { uint32_t r; asm("fma.rn.f16x2 %0, %1, %2, %3;" : "=r"(r) : "r"(a), "r"(b), "r"(c)); return r; }
DEVI uint32_t hfnma2(uint32_t a, uint32_t b, uint32_t c) {
  uint32_t r; asm("{\n.reg .b32 n;\nneg.f16x2 n, %1;\nfma.rn.f16x2 %0, n, %2, %3;\n}" : "=r"(r) : "r"(a), "r"(b), "r"(c)); return r;
}
DEVI float bf_lo(uint32_t w) { return __uint_as_float(w << 16); }
DEVI float bf_hi(uint32_t w) { return __uint_as_float(w & 0xffff0000u); }

DEVI uint32_t chan_exponent(const uint32_t* w) {
  uint32_t m[4];
#pragma unroll
  for (int i = 0; i < 4; i++) m[i] = bamax2(w[i], w[i + 4]);
#pragma unroll
  for (int i = 8; i < 32; i++) m[i & 3] = bamax2(m[i & 3], w[i]);
  uint32_t x = bamax2(bamax2(m[0], m[1]), bamax2(m[2], m[3])) & 0x7fff7fffu;
  x = max(x >> 16, x & 0xffffu);
  x = __reduce_max_sync(0xffffffffu, x);
  return min(x >> 7, 251u);
}
DEVI uint32_t to_f16(uint32_t w, uint32_t mul) { const uint32_t y = bmul2(w, mul); return pack_f16(bf_lo(y), bf_hi(y)); }

struct Tile { int j, r; };
DEVI Tile tile_of() {
  int cta; asm volatile("mov.u32 %0, %%ctaid.x;" : "=r"(cta));
  const int cl = cta >> 1, lo = (cl - 4) >> 31, hi = (35 - cl) >> 31;
  const int p = cl - 4 + (lo & (36 + 7 * cl)) + (hi & ((((cl - 36) * 37) >> 8) + 1)), g = p & 7, rr = p >> 3;
  return Tile{(g & 6) | (cta & 1), 2 * rr + (g & 1)};
}

static_assert(TAIL <= 3, "stage 27 is released inside the loop");
__host__ __device__ constexpr bool prew(int it) { return it >= 28 && it < 31; }

DEVI void twiddle(uint32_t& ore, uint32_t& oim, uint32_t re, uint32_t im, uint32_t t, uint32_t s) {
  re = hfma2(t, im, re);
  oim = hfma2(s, re, im);
  ore = hfma2(t, oim, re);
}

__global__ void __cluster_dims__(2, 1, 1) __launch_bounds__(kThreads, 1)
fused_kernel(const __grid_constant__ Params P) {
  extern __shared__ __align__(1024) uint8_t smem[];
  const int tid = threadIdx.x, lane = tid & 31;
  const int warp = tid >> 5, warpu = __shfl_sync(0xffffffffu, tid >> 5, 0);
  const int cta = blockIdx.x, rho = cta & 1, cl = cta >> 1;
  const uint32_t sb = SM_BASE + (rho << 24);
  const uint32_t tstart = clock32();
  auto bar = [&](int i) INL { return sb + SM_BAR + 8u * i; };
  auto load1 = [&](int it, int s, int j, int r, bool mc) INL {
    const uint32_t fb = bar(B_F1 + s), xs = sb + x1_off(it);
    mbar_expect(fb, (it & 1) ? 16384 : 32768);
    tma4d(sb + w1_off(s), &P.w1, 32 * it, 2 * j, 1, fb);
    if (!(it & 1)) {
      if (mc) tma2d_mc(xs + rho * 8192, &P.x, 32 * it, 128 * r + 64 * rho, fb);
      else { tma2d(xs, &P.x, 32 * it, 128 * r, fb); tma2d(xs + 8192, &P.x, 32 * it, 128 * r + 64, fb); }
    }
  };
  TSTAMP(tid == 0, 0); GSTAMP(tid == 0, 62);

  if (warpu == 8 && elect()) {
    prefetch_map(&P.w1); prefetch_map(&P.x);
    for (int i = 0; i < EARLY; i++) mbar_init(bar(B_F1 + slot1(i)), 1);
    const Tile T = tile_of();
    for (int i = 0; i < EARLY; i++) load1(i, slot1(i), T.j, T.r, false);
    TSTAMP(true, 18);
    for (int i = EARLY; i < NS1; i++) mbar_init(bar(B_F1 + slot1(i)), 1);
    asm volatile("fence.mbarrier_init.release.cluster;" ::: "memory");
  }
  if (warpu == 9 && elect()) {
    if (sb != (uint32_t)__cvta_generic_to_shared(smem)) __trap();
#pragma unroll
    for (int i = B_F2; i < B_Q; i++) mbar_init(bar(i), 1);
    mbar_expect(bar(B_H), 32768);
    asm volatile("fence.mbarrier_init.release.cluster;" ::: "memory");
  }
  if (warpu == 10 && elect()) {
#pragma unroll
    for (int i = B_Q; i < B_KVE; i++) mbar_init(bar(i), i < B_E1 ? 1 : 16);
    mbar_expect(bar(B_Q), 32768); mbar_expect(bar(B_U), 16384); mbar_expect(bar(B_MAX), 1024);
    asm volatile("fence.mbarrier_init.release.cluster;" ::: "memory");
  }
  if (warpu == 11 && elect()) {
#pragma unroll
    for (int i = B_KVE; i < B_COUNT; i++) mbar_init(bar(i), i < B_OFREE ? 8 : i == B_F2M ? 3 : i < B_Y ? 4 : 9);
    mbar_expect(bar(B_Y), 8192); mbar_expect(bar(B_Y + 1), 8192);
    asm volatile("fence.mbarrier_init.release.cluster;" ::: "memory");
  }
  __syncwarp();
  cluster_sync();

  if (warpu < 8) {
    asm volatile("setmaxnreg.inc.sync.aligned.u32 %0;" :: "n"(232));
    const int wg = warp >> 2, wq = warp & 3, g = lane >> 2, q = lane & 3;
    constexpr uint32_t sbq = SM_BASE >> 4;
    const uint32_t wgu = warpu >> 2;
    const uint64_t z64 = P.zero;
    Desc dA(z64, sbq + wgu * 512, 1024, 1), dB(z64, sbq, 1024, 1);
    const int srow = wg * 64 + wq * 16 + (lane & 15);
    const uint32_t stm = srow * 128 + (((lane >> 4) ^ (srow & 7)) << 4);
    auto stage2 = [&](float* acc, int n, bool first, bool wait = true) INL {
      const int s = slot2(n);
      if (wait) mbar_wait(bar(B_F2 + s), par2(n));
      const uint32_t da = s * (ST2 >> 4) + dlo(0, 16), db = s * (ST2 >> 4) + dlo(16384, 8192);
      wg_fence();
      const uint64_t a0 = dA.at(da), b0 = dB.at(db);
      if (first) mma_n128_init(acc, a0, b0); else mma_n128(acc, a0, b0);
#pragma unroll
      for (int kk = 1; kk < 4; kk++) mma_n128(acc, a0 + 2 * kk, b0 + kk * (2048 >> 4));
      wg_commit();
    };
    auto release2 = [&](int n) INL { arrive_both(bar(B_E2 + slot2(n)), lane); };
    auto publish = [&](int b) INL { fence_async_smem(); __syncwarp(); mbar_arrive_if(bar(b), lane == 0); };

    float aq[64];
    uint32_t f1[8], tw[4];
    uint32_t su[2][32], sh[2][32];
    uint32_t x0[4][8], x1[4][8], p0[2][8], p1[2][8], z0[2][8], z1[2][8];
    auto s1 = [&](uint32_t* d, uint32_t base) INL {
      Desc db(z64, sbq + wgu * 1024 + dlo(base, 128), 512, 0);
      mma_s1_init(d, f1, db.v);
      mma_s1(d, f1 + 4, db.at(256 >> 4));
      wg_commit();
    };
    const uint64_t dre = Desc(z64, sbq + dlo(SM_F2 + 512, 128), 256, 0).v, dim = Desc(z64, sbq + dlo(SM_F2, 128), 256, 0).v;
    auto fwd2 = [&](uint32_t (*x)[8], int c) INL {
      uint32_t a[4][8];
#pragma unroll
      for (int t = 0; t < 4; t++) {
        uint32_t* s = (t < 2 ? sh[c >> 1] : su[c >> 1]) + 16 * (c & 1) + 8 * (t & 1);
        pin<8>(s);
#pragma unroll
        for (int i = 0; i < 4; i++) twiddle(a[t][i], a[t][4 + i], s[4 * (i & 1) + (i & 2)], s[4 * (i & 1) + (i & 2) + 1], tw[i & 2], tw[(i & 2) + 1]);
      }
      wg_fence();
#pragma unroll
      for (int t = 0; t < 4; t++) { mma_s2_init(x[t], a[t], dre); mma_s2(x[t], a[t] + 4, dim); }
      wg_commit();
    };
    auto half2 = [&](uint32_t (*x)[8], uint32_t* s) INL {
      uint32_t a[2][8];
      pin<16>(s);
#pragma unroll
      for (int t = 0; t < 2; t++)
#pragma unroll
        for (int i = 0; i < 4; i++) twiddle(a[t][i], a[t][4 + i], s[8 * t + 4 * (i & 1) + (i & 2)], s[8 * t + 4 * (i & 1) + (i & 2) + 1], tw[i & 2], tw[(i & 2) + 1]);
      wg_fence();
#pragma unroll
      for (int t = 0; t < 2; t++) { mma_s2_init(x[t], a[t], dre); mma_s2(x[t], a[t] + 4, dim); }
      wg_commit();
    };
    auto product = [&](uint32_t (*a)[8], uint32_t (*x)[8], int i) INL {
#pragma unroll
      for (int t = 0; t < 4; t++) { pin<2>(x[t] + i); pin<2>(x[t] + 4 + i); }
      auto hr = [&](int l) INL { return x[l >> 1][i + (l & 1)]; };
      auto hi = [&](int l) INL { return x[l >> 1][4 + i + (l & 1)]; };
      auto ur = [&](int l) INL { return x[2 + (l >> 1)][i + (l & 1)]; };
      auto ui = [&](int l) INL { return x[2 + (l >> 1)][4 + i + (l & 1)]; };
      uint32_t gr[4], gi[4];
      gr[0] = hr(0); gi[0] = hi(0);
#pragma unroll
      for (int l = 1; l < 4; l++) { gr[l] = hadd2(hr(l), hi(l - 1)); gi[l] = hsub2(hi(l), hr(l - 1)); }
#pragma unroll
      for (int p = 0; p < 4; p++) {
        uint32_t re = hfnma2(gi[0], ui(p), hmul2(gr[0], ur(p))), im = hfma2(gi[0], ur(p), hmul2(gr[0], ui(p)));
#pragma unroll
        for (int l = 1; l <= p; l++) {
          re = hfnma2(gi[l], ui(p - l), hfma2(gr[l], ur(p - l), re));
          im = hfma2(gi[l], ur(p - l), hfma2(gr[l], ui(p - l), im));
        }
        a[p >> 1][i + (p & 1)] = re; a[p >> 1][4 + i + (p & 1)] = im;
      }
#pragma unroll
      for (int t = 0; t < 2; t++) { pin<2>(a[t] + i); pin<2>(a[t] + 4 + i); }
    };
    auto inv1 = [&](uint32_t (*z)[8], uint32_t (*a)[8]) INL {
      wg_fence();
#pragma unroll
      for (int t = 0; t < 2; t++) { mma_s2_init(z[t], a[t], dre); mma_s2_neg(z[t], a[t] + 4, dim); }
      wg_commit();
    };
    auto zstore = [&](uint32_t (*z)[8], int c) INL {
      const uint32_t zoff = sb + RB + (q >> 1) * (RU + 16 - RB) + (8 * rho + 4 * wg) * 2048 + (4 * (8 * wq + g) + 2 * (q & 1)) * 16;
#pragma unroll
      for (int t = 0; t < 2; t++) {
        uint32_t a[8];
        pin<8>(z[t]);
#pragma unroll
        for (int i = 0; i < 4; i++) twiddle(a[i], a[4 + i], z[t][i], z[t][4 + i], tw[i & 2], tw[(i & 2) + 1]);
        const uint32_t dst = zoff + t * (16384 - rho * 32768) + c * 2048;
        sts128(dst, a[0], a[1], a[2], a[3]);
        sts128(dst + 16, a[4], a[5], a[6], a[7]);
      }
    };
    float kvr[18];
    auto kvstore = [&]() INL {
      const uint32_t dst = sb + kv_off(warp >> 1) + (warp & 1) * 256 + lane * 4;
      pin<18>(kvr);
#pragma unroll
      for (int b = 0; b < 4; b++) { sts32(dst + b * 512, pack_bf16(kvr[4 * b], kvr[4 * b + 1])); sts32(dst + b * 512 + 128, pack_bf16(kvr[4 * b + 2], kvr[4 * b + 3])); }
      sts32(dst + 2048, pack_bf16(kvr[16], kvr[16])); sts32(dst + 2176, pack_bf16(kvr[17], kvr[17]));
      publish(B_KVI);
    };
    {
      float ak[64], av[64];
      Desc dK(z64, sbq + wgu * 256, 1024, 1);
      auto kstep = [&](int c, int i) INL {
        const int s = slot1(c);
        if (!prew(c - 1)) mbar_wait(bar(B_F1 + s), (c / NS1 + i) & 1);
        TSTAMP(tid == 0 && c == 0, 1);
        const uint32_t dx = dlo(x1_off(c + 6 * i), 16), dk = dlo(w1_off(s), 16), dv = dlo(w1_off(s) + 8192, 4096);
        const uint64_t xa = dA.at(dx) + (c & 1) * 4, xb = dB.at(dx) + (c & 1) * 4;
        wg_fence();
        if (c == 0) { mma_kt_init(ak, dK.at(dk), xb); mma_n128_init(av, xa, dB.at(dv)); }
        else { mma_kt(ak, dK.at(dk), xb); mma_n128(av, xa, dB.at(dv)); }
        mma_kt(ak, dK.at(dk + (2048 >> 4)), xb + 2);
        mma_n128(av, xa + 2, dB.at(dv + (2048 >> 4)));
        wg_commit();
        wg_wait<1>();
        if (c > 0) arrive_both(bar(B_E1 + (s + NS1 - 1) % NS1), lane);
        if (prew(c)) mbar_wait(bar(B_F1 + slot1(c + 1)), ((c + 1) / NS1) & 1);
        KSTAMP(c + 6 * i);
      };
      auto renew = [&]() INL { dK.renew(z64); dA.renew(z64); dB.renew(z64); };
      uint32_t kk[7], u[36], sw[4], mx[2], um = 0, eu;
      unsigned short dskip;
      const int cp = 4 * (warp & 1) + (lane >> 3), run = 8 * (warp >> 1) + (lane & 7);
      const uint32_t ua = sb + RB + run * 32 + ((warp ^ (lane >> 2)) & 1) * 16 + (lane >> 3) * 4;
      sts32(sb + SM_MAX + (lane & 15) * 4, 0);
      ldg128(sw, P.shift_k + (cl * 16 + 2 * cp) * 4);
      asm volatile("ld.global.nc.b16 %0, [%1];" : "=h"(dskip) : "l"(P.ssm_d + 8 * cta + warp));
#pragma unroll
      for (int c = 0; c < L0; c++) kstep(c, 0);
      {
        pin<4>(sw);
        const uint32_t t0 = __byte_perm(sw[0], sw[2], 0x5410), t1 = __byte_perm(sw[0], sw[2], 0x7632), t2 = __byte_perm(sw[1], sw[3], 0x5410);
        sw[3] = __byte_perm(sw[1], sw[3], 0x7632); sw[0] = t0; sw[1] = t1; sw[2] = t2;
        pin<4>(sw);
      }
      float tap0 = lane == 0 ? bf_lo(dskip) : 0.f;
      pin<1>(&tap0);
#pragma unroll
      for (int e = 0; e < 36; e++) u[e] = 0;
#pragma unroll
      for (int e = 0; e < 7; e++) kk[e] = 0;
      renew();
#pragma unroll
      for (int c = L0; c < L0 + 6; c++) kstep(c, 0);
      renew();
#pragma unroll 1
      for (int i = 1; i < 4; i++) {
#pragma unroll
        for (int h = 0; h < 3; h++) {
          kstep(L0 + 2 * h, i);
          {
            const int slot = (3 * i + h + 4) & 7;
#pragma unroll
            for (int e = 4 * h; e < 4 * h + 4; e++) { u[e] = u[e + 12]; u[e + 12] = u[e + 24]; }
            pin<4>(u + 4 * h); pin<4>(u + 4 * h + 12);
            mbar_wait(bar(B_KVL + slot), h == 2 && i == 3);
#pragma unroll
            for (int e = 0; e < 4; e++) { kk[3 + e] = lds32(ua + slot * 8192 + e * 1024); u[24 + 4 * h + e] = lds32(ua + slot * 8192 + 4096 + e * 1024); }
          }
          kstep(L0 + 2 * h + 1, i);
          pin<7>(kk); pin<4>(u + 24 + 4 * h);
#pragma unroll
          for (int e = 0; e < 4; e++) {
            uint32_t& y = u[24 + 4 * h + e];
            y = bmul2(bfma2(kk[3 + e], sw[0], bfma2(kk[2 + e], sw[1], bfma2(kk[1 + e], sw[2], bmul2(kk[e], sw[3])))), y);
            um = bamax2(um, y);
          }
          if (h == 0) um = i == 1 ? 0 : um;
          kk[0] = kk[4]; kk[1] = kk[5]; kk[2] = kk[6];
          pin<4>(u + 24 + 4 * h); pin<1>(&um);
          if (h == 1) mbar_arrive_if(bar(B_KVE), lane == 0 && i == 2);
        }
      }
      um = bamax2(um, __shfl_xor_sync(0xffffffffu, um, 1));
      um = bamax2(um, __shfl_xor_sync(0xffffffffu, um, 2));
      red_async_max(mapa(sb + SM_MAX + cp * 8 + (q & 1) * 4, q >> 1), min((um >> (7 + 16 * (q & 1))) & 0xffu, 251u), mapa(bar(B_MAX), q >> 1));
      renew();
#pragma unroll
      for (int c = L0 + 24; c < 28; c++) {
        kstep(c, 0);
        if (c == L0 + 24) { ldg128(f1, P.tab + (tid & 127) * 4); ldg128(f1 + 4, P.tab + 512 + (tid & 127) * 4); ldg128(tw, P.tab + 1024 + (tid & 127) * 4); }
      }
      mbar_wait(bar(B_MAX), 0);
      TSTAMP(tid == 0, 5);
      asm volatile("ld.shared.v2.b32 {%0,%1}, [%2];" : "=r"(mx[0]), "=r"(mx[1]) : "r"(sb + SM_MAX + cp * 8));
      eu = lds32(sb + SM_MAX + (8 * rho + warp) * 4);
      const uint32_t ud = mapa(sb + RU + (lane >> 3) * 8192 + (2 * rho + wg) * 1024 + (run & 15) * 16, warp & 1), ub = mapa(bar(B_U), rho ^ 1);
#pragma unroll
      for (int i = 0; i < 4; i++) {
        kstep(28 + i, 0);
        if (i == 0) { pin<2>(mx); mx[0] = (0x00fd00fdu - (mx[0] | mx[1] << 16)) << 7; }
        uint32_t* y = u + 4 + 8 * i;
        pin<8>(y);
#pragma unroll
        for (int e = 0; e < 8; e++) y[e] = bmul2(y[e], mx[0]);
        st_either8((warpu & 1) == rho, ud + (i & 1) * 512 + (i >> 1) * 256, ub,
                   pack_f16(bf_lo(y[0]), bf_lo(y[1])), pack_f16(bf_lo(y[2]), bf_lo(y[3])), pack_f16(bf_lo(y[4]), bf_lo(y[5])), pack_f16(bf_lo(y[6]), bf_lo(y[7])),
                   pack_f16(bf_hi(y[0]), bf_hi(y[1])), pack_f16(bf_hi(y[2]), bf_hi(y[3])), pack_f16(bf_hi(y[4]), bf_hi(y[5])), pack_f16(bf_hi(y[6]), bf_hi(y[7])));
      }
      auto qstep = [&](int n, bool wait = true) INL {
        if ((n & 3) == 0) { dA.renew(z64); dB.renew(z64); }
        stage2(aq, n, n == 0, wait);
        wg_wait<1>();
        if (n == 0) arrive_both(bar(B_E1 + NS1 - 1), lane); else release2(n - 1);
        QSTAMP(n);
      };
      uint32_t pk[32];
      auto phik = [&](int i0, int i1) INL {
#pragma unroll
        for (int i = i0; i < i1; i++) { pin<2>(ak + 2 * i); pk[i] = phi2(ak[2 * i], ak[2 * i + 1]); pin<1>(pk + i); }
      };
      const uint32_t rot = ROT == 0 ? 0 : ROT == 1 ? tile_of().r & 3 : (tile_of().r >> 1) & 3, stv = stm ^ (rot << 4);
      auto vst1 = [&](int kt) INL {
        float* a = av + 8 * kt;
        pin<8>(a);
        stsm4(sb + RA + (kt >> 2) * 16384 + (stv ^ ((kt & 3) << 5)), pack_bf16(a[0], a[1]), pack_bf16(a[2], a[3]), pack_bf16(a[4], a[5]), pack_bf16(a[6], a[7]));
      };
      auto vst = [&](int k0, int k1) INL {
#pragma unroll
        for (int kt = k0; kt < k1; kt++) vst1(kt);
      };
      float dkv[36];
      Desc dV(z64, sbq + wgu * (1024u - (1024u << 16)) + dlo(RA, SM_ONES - RA), 1024, 1);
      auto kvmma = [&](int k0, int k1) INL {
        wg_fence();
#pragma unroll
        for (int ks = k0; ks < k1; ks++) {
          const uint64_t db = dV.at(ks * (128u - (128u << 16)));
          if (ks == 0) mma_kv_init(dkv, pk, db); else mma_kv(dkv, pk + 4 * ks, db);
        }
        wg_commit();
      };
      float* gacc;
      auto kvred = [&](int b) INL {
        const bool hh = wq >> 1;
        asm volatile("red.relaxed.gpu.global.add.v4.f32 [%0], {%1,%2,%3,%4};" :: "l"(gacc + (b ^ rot) * 128), "f"(hh ? dkv[16 + 4 * b] : dkv[4 * b]),
                     "f"(hh ? dkv[17 + 4 * b] : dkv[1 + 4 * b]), "f"(hh ? dkv[18 + 4 * b] : dkv[2 + 4 * b]), "f"(hh ? dkv[19 + 4 * b] : dkv[3 + 4 * b]) : "memory");
        if (b == 3) {
          asm volatile("{\n.reg .pred p;\nsetp.eq.s32 p, %3, 0;\n@p red.relaxed.gpu.global.add.v2.f32 [%0], {%1,%2};\n}"
                       :: "l"(gacc + 4096 - warp * 496 - g * 14), "f"(dkv[32]), "f"(dkv[34]), "r"(q) : "memory");
          __syncwarp();
          mbar_arrive_if(bar(B_KVP), lane == 0);
          TSTAMP(tid == 0, 4);
        }
      };
      auto consts = [&]() INL {
        gacc = &P.g->kv[tile_of().j][warp * 512 + lane * 4];
      };
      uint32_t w[32], hmul;
      auto hload = [&](int i0, int i1) INL {
        const uint32_t a = sb + RB + warp * 4096 + (((lane >> 2) & 1) + (lane & 2) + 4 * (lane & 1) + (((lane << 2) ^ lane) & 24)) * 16;
#pragma unroll
        for (int i = i0; i < i1; i++) lds128(w + 4 * i, a + i * 512);
      };
      auto hmax = [&]() INL {
        pin<32>(w);
        tap0 += bf_lo(w[0]);
        w[0] = pack_bf16(tap0, bf_hi(w[0]));
        hmul = (252u - chan_exponent(w)) * 0x00800080u;
        const int e = min(max((int)(eu + 128 - (hmul >> 23)), 0), 254);
        asm volatile("st.shared.b16 [%0], %1;" :: "r"(sb + SM_SCALE + 2 * warp), "h"((unsigned short)(e << 7)) : "memory");
      };
      auto hstore = [&](int i0, int i1) INL {
        const uint32_t dst = sb + RB + warp * 4096 + (lane & 6) * 128 + ((lane ^ ((lane >> 2) & 6)) & 7) * 16;
#pragma unroll
        for (int i = i0; i < i1; i++) {
          pin<4>(w + 4 * i);
          const uint32_t w0 = i == 0 ? pack_f16(tap0 * bf_lo(hmul), bf_hi(w[0]) * bf_lo(hmul)) : to_f16(w[4 * i], hmul);
          sts128(dst + (i >> 1) * 1024 + (i & 1) * 128, w0, to_f16(w[4 * i + 1], hmul), to_f16(w[4 * i + 2], hmul), to_f16(w[4 * i + 3], hmul));
        }
      };
      auto kvload = [&]() INL {
        mbar_wait(bar(B_KV), 0);
        TSTAMP(tid == 0, 7);
#pragma unroll
        for (int b = 0; b < 4; b++)
          asm volatile("ld.global.cg.v4.f32 {%0,%1,%2,%3}, [%4];" : "=f"(kvr[4 * b]), "=f"(kvr[4 * b + 1]), "=f"(kvr[4 * b + 2]), "=f"(kvr[4 * b + 3]) : "l"(gacc + b * 128) : "memory");
        asm volatile("ld.global.cg.v2.f32 {%0,%1}, [%2];" : "=f"(kvr[16]), "=f"(kvr[17]) : "l"(gacc + 4096 - warp * 496 - g * 14 - q * 4) : "memory");
      };
      qstep(0);
      TSTAMP(tid == 0, 2);
#define WE1 mbar_wait(bar(B_E1 + NS1 - 1), 1)
#define PV publish(B_VST)
#define WV0 mbar_wait(bar(B_ZERO), 0); mbar_wait(bar(B_VST), 0)
#define WH mbar_wait(bar(B_H), 0)
#define KVD pin<36>(dkv); mbar_arrive_if(bar(B_KVM), lane == 0)
#define S1U0 mbar_wait(bar(B_U2), 1); wg_fence(); s1(su[0], RU)
#define S1H0 mbar_wait(bar(B_VST), 1); wg_fence(); s1(sh[0], RB)
#define WF mbar_wait(bar(B_F2M), 0)
#define HU(c) half2((c ? x1 : x0) + 2, su[0] + 16 * c)
#define HH(c) half2(c ? x1 : x0, sh[0] + 16 * c)
#define PD(n) product(n < 2 ? p0 : p1, n < 2 ? x0 : x1, 2 * (n & 1))
#define Q(n) qstep(n)
#define QL(n, code) mbar_wait(bar(B_F2 + slot2(n)), par2(n)); code; qstep(n, false)
      phik(0, 4); WE1; vst(0, 3); Q(1); vst(3, 6); phik(4, 8); Q(2); vst(6, 8); PV; phik(8, 13); Q(3); WV0; kvmma(0, 3); phik(13, 20); Q(4); kvmma(3, 5); WH; hload(0, 3); phik(20, 26); consts(); Q(5); hload(3, 5); phik(26, 32); kvmma(5, 8); hload(5, 8); Q(6); KVD; kvred(0); S1U0; hmax(); kvred(1); Q(7); hstore(0, 3); kvred(2); Q(8); hstore(3, 6); kvred(3); Q(9); hstore(6, 8); PV; Q(10); S1H0; WF; HU(0); HU(1); Q(11); HH(0); HH(1); Q(12); PD(0); Q(13); PD(1); kvload(); Q(14); PD(2); Q(15); PD(3);
    }

    float acc[64];
    {
      uint32_t pq[4][8];
      float dn[4][20];
      Desc dO(z64, sbq + dlo(0, 128), 512, 0);
      auto phiq = [&](int h) INL {
        pin<16>(aq + 16 * h);
#pragma unroll
        for (int i = 0; i < 8; i++) pq[h][i] = phi2(aq[16 * h + 2 * i], aq[16 * h + 2 * i + 1]);
        pin<8>(pq[h]);
      };
      auto omma = [&](int h) INL {
        wg_fence();
        mma_o_init(dn[h], pq[h], dO.at(kv_off(h) >> 4));
        mma_o(dn[h], pq[h] + 4, dO.at((kv_off(h) + 256) >> 4));
        wg_commit();
      };
      auto onorm = [&](int h) INL {
        pin<20>(dn[h]);
        const float i0 = rcp(dn[h][16] + 1e-6f), i1 = rcp(dn[h][18] + 1e-6f);
#pragma unroll
        for (int hf = 0; hf < 2; hf++) {
          const float* a = dn[h] + 8 * hf;
          stsm4(sb + (h >> 1) * ST2 + (stm ^ (((h & 1) * 2 + hf) << 5)), pack_bf16(a[0] * i0, a[1] * i0), pack_bf16(a[2] * i1, a[3] * i1),
                pack_bf16(a[4] * i0, a[5] * i0), pack_bf16(a[6] * i1, a[7] * i1));
        }
        if (h & 1) publish(B_OW + (h >> 1));
      };
      wg_fence();
      s1(su[1], RU + 8192);
      kvstore();
      wg_wait<1>();
      release2(15);
      TSTAMP(tid == 0, 6);
      auto own = [&](int c) INL { if (c == 0) { dA.renew(z64); dB.renew(z64); } stage2(acc, 16 + c, c == 0); };
      uint32_t gf[4][4];
#define WKV mbar_wait(bar(B_KVI), 0)
#define W(n) wg_wait<n>()
#define S1H wg_fence(); s1(sh[1], RB + 8192)
#define T8 TSTAMP(tid == 0, 8)
#define T9 TSTAMP(tid == 0, 9)
#define WS1 mbar_wait(bar(B_OW + 1), 0)
#define PR(p, x) product(p, x, 0); product(p, x, 2)
#define GL ldg128(gf[1], P.tab + 1536 + (tid & 127) * 4); ldg128(gf[3], P.tab + 2048 + (tid & 127) * 4)
      auto gdup = [&]() INL {
#pragma unroll
        for (int i = 0; i < 4; i += 2) {
          pin<4>(gf[i + 1]);
          gf[i][0] = gf[i][1] = gf[i + 1][0]; gf[i][2] = gf[i][3] = gf[i + 1][1];
          gf[i + 1][0] = gf[i + 1][1] = gf[i + 1][2]; gf[i + 1][2] = gf[i + 1][3];
          pin<4>(gf[i]); pin<4>(gf[i + 1]);
        }
      };
      const uint32_t qa = sb + RA + warp * 4096 + lane * 32 + ((rho ^ g) & 1) * 16;
      uint32_t qv[4][4];
      auto qload = [&]() INL {
        mbar_wait(bar(B_Q), 0);
#pragma unroll
        for (int i = 0; i < 4; i++) lds128(qv[i], qa + i * 1024);
      };
#define PZ publish(B_ZST); TSTAMP(tid == 0, 10)
      phiq(0); phiq(1); WKV; omma(0); omma(1); W(1); onorm(0); W(0); onorm(1); T8; S1H; phiq(2); omma(2); phiq(3); W(0); onorm(2); omma(3); inv1(z0, p0); W(1); onorm(3); T9; inv1(z1, p1); fwd2(x0, 2); W(1); WS1; zstore(z0, 0); zstore(z1, 1); W(0); own(0); fwd2(x1, 3); PR(p0, x0); inv1(z0, p0); own(1); W(2); release2(16); GL; PR(p1, x1); inv1(z1, p1); W(2); zstore(z0, 2); gdup(); W(0); release2(17); zstore(z1, 3); PZ; qload();
      mbar_wait(bar(B_ZST), 0);
      float y[64];
      {
        Desc db(z64, sbq + wgu * ((RU + 16 - RB) >> 4) + dlo(RB, 128), 2048, 0);
        wg_fence();
        mma_i2_init(y, gf[0], db.v, 0xEEEE4444u);
#pragma unroll
        for (int i = 1; i < 4; i++) mma_i2(y, gf[i], db.at(i * (512 >> 4)), 0xEEEE4444u);
        wg_commit();
      }
      uint32_t sc[4];
      lds128(sc, sb + SM_SCALE);
      TSTAMP(tid == 0, 11);
      stage2(acc, NY, false);
      TSTAMP(tid == 0, 13);
      wg_wait<1>();
      QSTAMP(NY);
      arrive_both(bar(B_I2), lane);
      pin<64>(y);
      uint32_t yv[8][4];
#pragma unroll
      for (int i = 0; i < 8; i++)
#pragma unroll
        for (int m = 0; m < 4; m++) yv[i][m] = bmul2(pack_bf16(y[32 * (i >> 2) + (i & 3) + 8 * m], y[32 * (i >> 2) + (i & 3) + 8 * m + 4]), sc[m]);
      pin<32>(&yv[0][0]);
      stage2(acc, NY + 1, false);
      wg_wait<1>();
      QSTAMP(NY + 1);
      release2(NY);
      mbar_wait(bar(B_I2), 0);
      const uint32_t yr = mapa(sb + Y_IN + tid * 16 + warp * 1536, rho ^ 1), yb = mapa(bar(B_Y), rho ^ 1);
      dA.renew(z64); dB.renew(z64);
#pragma unroll
      for (int i = 0; i < 4; i++) {
        if (i == 2 || (i && YV == 4) || (i == 1 && YV == 3)) {
          const int n = NY + 1 + (YV == 2 ? 1 : i);
          stage2(acc, n, false); wg_wait<1>(); QSTAMP(n); release2(n - 1);
        }
        pin<4>(qv[i]);
        sts128(qa + i * 1024, bmul2(yv[i][0], qv[i][0]), bmul2(yv[i][1], qv[i][1]), bmul2(yv[i][2], qv[i][2]), bmul2(yv[i][3], qv[i][3]));
        st_async4(yr + i * 512, yv[4 + i][0], yv[4 + i][1], yv[4 + i][2], yv[4 + i][3], yb + 8 * (i >> 1));
        if (i & 1) { __syncwarp(); mbar_arrive_if(bar(B_Y + (i >> 1)), lane == 0); }
      }
      TSTAMP(tid == 0, 12);
    }
#pragma unroll 1
    for (int n = NY + 1 + YV; n < 32 - TAIL; n++) {
      stage2(acc, n, false);
      TSTAMP(tid == 0 && n == 26, 14);
      wg_wait<1>();
      release2(n - 1);
      QSTAMP(n);
    }
    {
      const Tile T = tile_of();
      dA.renew(z64); dB.renew(z64);
      if (TAIL > 1) mbar_wait(bar(B_STG), wgu ^ 1);
#pragma unroll
      for (int n = 32 - TAIL; n < 32; n++) {
        if (n == 31 && TAILE) mbar_arrive_if(bar(B_STG), wgu == 0 && lane == 0);
        stage2(acc, n, false);
      }
      if (!TAILE) mbar_arrive_if(bar(B_STG), wgu == 0 && lane == 0);
      mbar_wait(bar(B_E2 + 5), 1);
      wg_wait<0>();
      TSTAMP(tid == 0, 17); TSTAMP(tid == 128, 15);
      pin<64>(acc);
#pragma unroll
      for (int c = 0; c < 2; c++) {
#pragma unroll
        for (int t = 0; t < 4; t++) {
          const float* a = acc + 32 * c + 8 * t;
          stsm4(sb + RB + c * 16384 + (stm ^ (t << 5)), pack_bf16(a[0], a[1]), pack_bf16(a[2], a[3]), pack_bf16(a[4], a[5]), pack_bf16(a[6], a[7]));
        }
        fence_async_smem();
        __syncwarp();
        tma2d_store_e(&P.outa, sb + RB + c * 16384 + warpu * 2048, 128 * T.j + 64 * c, 128 * T.r + 16 * warpu);
      }
      bulk_wait_read();
      TSTAMP(tid == 128, 16);
    }
    if (ENDS) { __syncwarp(); cluster_sync(); }
  } else {
    asm volatile("setmaxnreg.dec.sync.aligned.u32 %0;" :: "n"(40));
    const Tile T = tile_of();
    const int j = T.j, r = T.r;
    auto kcol = [&](int n) INL {
      return n < 20 ? 128 * (j ^ ((n >> 1) & 1)) + 64 * (n & 1) : 128 * (((j & 6) + n - (n < 26 ? 18 : 24)) & 7) + (n < 26 ? 0 : 64);
    };
    if (warpu == 8) {
      uint32_t ph = 0;
      int s = slot1(EARLY);
#pragma unroll 1
      for (int it = EARLY; it < 32; ++it, s = s + 1 == NS1 ? 0 : s + 1) {
        if (it >= NS1) { mbar_wait(bar(B_E1 + s), (ph >> s) & 1); ph ^= 1u << s; }
        if (elect()) load1(it, s, j, r, true);
      }
      int qn = 0;
      auto loadq = [&](int n) INL {
        if ((QM >> n) & 1) { if (elect()) tma5d(sb + RA + qn * 8192, &P.q, 16 * cl, 2 * rho, 2 * (qn & 2), 2 * (qn & 1), bar(B_Q)); qn++; }
      };
#pragma unroll 1
      for (int n = 0; n < 16; ++n) {
        const int s = n & 3, i = n + (n >> 1);
        mbar_wait(bar(n < 4 ? B_E1 + i : B_E2 + s), n < 4 ? (ph >> i) & 1 : ((n >> 2) - 1) & 1);
        const uint32_t st = sb + s * ST2, fb = bar(B_F2 + s);
        if (elect()) {
          mbar_expect(fb, ST2);
          tma4d(st + 16384, &P.w2, 64 * n, 2 * j, 0, fb);
          tma2d_mc(st + rho * 8192, &P.x, 64 * n, 128 * r + 64 * rho, fb);
        }
        loadq(n);
      }
      auto loadw = [&](int n) INL {
        const int s = n & 3;
        mbar_wait(bar(B_E2 + s), ((n >> 2) - 1) & 1);
        if (elect()) { mbar_expect(bar(B_F2 + s), n < 18 ? 16384 : ST2); tma4d(sb + s * ST2 + 16384, &P.wo, kcol(n), 2 * j, 0, bar(B_F2 + s)); }
      };
#pragma unroll 1
      for (int n = 16; n < 20; ++n) {
        loadw(n);
        loadq(n);
      }
#pragma unroll 1
      for (int n = 18; n < 20; ++n) {
        const uint32_t st = sb + (n & 3) * ST2, fb = bar(B_F2 + (n & 3));
        mbar_wait(bar(B_RDY + n - 18), 0);
        asm volatile("fence.proxy.async.global;" ::: "memory");
        if (elect()) { tma2d(st, &P.o, kcol(n), 128 * r, fb); tma2d(st + 8192, &P.o, kcol(n), 128 * r + 64, fb); }
      }
      mbar_wait(bar(B_OFREE), 0);
      uint64_t slots = 0x103251032510ull, frees = 0x103251032410ull;
      uint32_t pars = 0xc9f, kc = 128 * (j & 6) + 256;
#pragma unroll 1
      for (int n = 20; n < 32; ++n, slots >>= 4, frees >>= 4, pars >>= 1, kc += n == 26 ? 448 : 128) {
        const uint32_t s = slots & 7, st = sb + s * ST2, fb = bar(B_F2 + s);
        mbar_wait(bar(B_RDY + n - 18), 0);
        mbar_wait(bar(B_E2 + (frees & 7)), ~pars & 1);
        if (elect()) {
          mbar_expect(fb, ST2);
          tma4d(st + 16384, &P.wo, kc & 1023, 2 * j, 0, fb);
          tma2d_mc(st + rho * 8192, &P.o, kc & 1023, 128 * r + 64 * rho, fb);
        }
      }
    } else {
      const int at = tid - 288, aw = warpu - 9;
      const unsigned epoch = ld_relaxed(&P.g->epoch[cta]);
      if (aw < 2) {
        float4* zp = reinterpret_cast<float4*>(&P.g->kv[j][r * (KV_WORDS / 16)]) + at;
        zp[0] = zp[2] = make_float4(0.f, 0.f, 0.f, 0.f);
        sts128(sb + SM_ONES + (at & 15) * 128 + (at & 7) * 16, 0x3f803f80u, 0x3f803f80u, 0x3f803f80u, 0x3f803f80u);
        fence_async_smem();
        bar_sync(4, 64);
        if (at == 0) {
          asm volatile("fence.release.gpu;\nred.relaxed.gpu.global.add.u32 [%0], 1;" :: "l"(&P.g->zflag[j * 32]) : "memory");
          flag_wait(&P.g->zflag[j * 32], 16u * (epoch + 1));
          mbar_arrive(bar(B_ZERO));
        }
        __syncwarp();
      } else {
#pragma unroll 1
        for (int m = -1; m < 16; m++) {
          const int s = (m >> 1) & 7;
          pace(tstart, PREP0 + (m + 1) * PREPGAP);
          if (m == 14) mbar_wait(bar(B_KVE), 0);
          if (elect()) {
            if (m < 0 || !(m & 1)) mbar_expect(bar(B_KVL + s), m < 0 ? 4096 : 8192);
            tma3d(sb + RB + (m < 0 ? 14 : m) * 4096, m > 0 && (m & 1) ? &P.v : &P.k, 16 * cl, 32 * rho + (m >> 31), 2 * (m & 14), bar(B_KVL + s));
          }
        }
#pragma unroll 1
        for (int m = 0; m < 8; m++) {
          pace(tstart, HT0 + m * HGAP);
          if (elect()) bulk_load(sb + RB + m * 4096, P.ssm_k + (size_t)(8 * cta + m) * 2048, 4096, bar(B_H));
        }
      }
      if (aw == 1) {
        if (cta < 3) pf_line(P.tab + cta * 768 + lane * 32);
#pragma unroll 1
        for (int m = 0; m < 16; m++) {
          pace(tstart, m < 4 ? WQT + m * 500 : QT + (m - 4) * QGAP);
          pf_line(m < 4 ? P.w_ptr + (size_t)(cta + (2 * m + (lane >> 4)) * 128) * 3072 + (lane & 15) * 64
                        : (m < 12 ? P.q_ptr + cta * 16384 - 8192 : P.wo_ptr + cta * 8192 - 24576) + m * 2048 + lane * 64);
        }
      }
      uint32_t f2[4];
      ldg128(f2, P.tab + 2560 + at * 4);
      if (at == 0) { mbar_wait_long(bar(B_U), 0); fence_async_smem(); mbar_arrive(bar(B_U2)); }
      mbar_wait_long(bar(B_KVM), 0);
      sts128(sb + SM_F2 + at * 16, f2[0], f2[1], f2[2], f2[3]);
      fence_async_smem();
      __syncwarp();
      mbar_arrive_if(bar(B_F2M), lane == 0);
      if (aw == 2 && elect()) {
        mbar_wait(bar(B_KVP), 0);
        asm volatile("fence.release.gpu;\nred.relaxed.gpu.global.add.u32 [%0], 1;" :: "l"(&P.g->kvflag[j * 32]) : "memory");
        flag_wait(&P.g->kvflag[j * 32], 16u * (epoch + 1));
        mbar_arrive(bar(B_KV));
        TSTAMP(true, 19);
      }
      __syncwarp();
      if (aw < 2) {
        {
          const int c = aw;
          if (MP && c == 1) {
            mbar_wait_long(bar(B_KVI), 0);
            if (elect()) { if (MP & 1) prefetch_map(&P.o); if (MP & 2) { prefetch_map(&P.outb); prefetch_map(&P.outa); } }
          }
          mbar_wait_long(bar(B_OW + c), 0);
          if (c == 1 && PUB) mbar_wait(bar(B_ZERO), 1);
          if (elect()) {
            const uint32_t src = sb + c * ST2;
            tma2d_store(&P.o, src, 128 * j + 64 * c, 128 * r);
            tma2d_store(&P.o, src + 8192, 128 * j + 64 * c, 128 * r + 64);
            bulk_commit();
            bulk_wait_all();
            TSTAMP(c == 0, 21); TSTAMP(c == 1, 26);
            if (c == 0) mbar_arrive(bar(B_ZERO));
            asm volatile("mbarrier.arrive.shared::cluster.b64 _, [%0];\nmbarrier.arrive.shared::cluster.b64 _, [%1];"
                         :: "r"(mapa(bar(B_OFREE), 0)), "r"(mapa(bar(B_OFREE), 1)) : "memory");
            asm volatile("fence.release.gpu;\nst.relaxed.gpu.global.u32 [%0], %1;\nmbarrier.arrive.shared::cluster.b64 _, [%2];"
                         :: "l"(&P.g->oflag[r * 32 + 2 * j + c]), "r"(epoch + 1), "r"(mapa(bar(B_RDY + c), rho ^ 1)) : "memory");
            TSTAMP(c == 0, 22); TSTAMP(c == 1, 23);
          }
          __syncwarp();
        }
      } else {
        const unsigned* fp = &P.g->oflag[r * 32 + (kcol(18 + min(lane, 13)) >> 6)];
        bool done = lane > 13 || lane < 2;
        mbar_wait_long(bar(B_OW), 0);
        for (int i = 0; !__all_sync(0xffffffffu, done) && i < kSpinLimit; i++) {
          const bool now = !done && (int)(ld_relaxed(fp) - epoch) > 0;
          if (__any_sync(0xffffffffu, now)) {
            asm volatile("fence.acquire.gpu;\nfence.proxy.async.global;" ::: "memory");
            mbar_arrive_if(bar(B_RDY + lane), now);
            TSTAMP(lane == 2 && now, 24);
          }
          done |= now;
        }
        if (lane == 0) P.g->epoch[cta] = epoch + 1;
        TSTAMP(lane == 0, 25);
      }
#pragma unroll 1
      for (int m = aw; m < ((EXP & 64) ? 0 : 16); m += 3) {
        const int u = 4 * (m & 7) + 2 * (m >> 3);
        mbar_wait_long(bar(B_Y + (m >> 3)), 0);
        TSTAMP(at == 0 && m == 0, 20);
        const uint32_t t0 = clock32();
        const uint32_t qa = sb + RA + u * 1024 + lane * 32 + ((rho ^ 1 ^ (lane >> 2)) & 1) * 16, ya = sb + Y_IN + u * 512 + lane * 16;
        uint32_t qv[PU][4], yv[PU][4];
#pragma unroll
        for (int h = 0; h < PU; h++) { lds128(qv[h], qa + h * 1024); lds128(yv[h], ya + h * 512); }
#pragma unroll
        for (int h = 0; h < PU; h++) sts128(qa + h * 1024, bmul2(qv[h][0], yv[h][0]), bmul2(qv[h][1], yv[h][1]), bmul2(qv[h][2], yv[h][2]), bmul2(qv[h][3], yv[h][3]));
        fence_async_smem();
        __syncwarp();
        if (elect()) tma5d_store(&P.outb, sb + RA + u * 1024, 1024 + 16 * cl, 2 * rho, (u >> 4) * 4 + (u & 3), (u >> 2) & 3);
        if (m < PSW) pace(t0, POSTGAP);
      }
      bulk_wait_read();
      TSTAMP(at == 0, 27);
    }
    if (ENDS) { __syncwarp(); cluster_sync(); }
  }
  TSTAMP(tid == 128, 61); GSTAMP(tid == 128, 63);
}

typedef CUresult (*EncodeFn)(CUtensorMap*, CUtensorMapDataType, cuuint32_t, void*, const cuuint64_t*, const cuuint64_t*,
                             const cuuint32_t*, const cuuint32_t*, CUtensorMapInterleave, CUtensorMapSwizzle,
                             CUtensorMapL2promotion, CUtensorMapFloatOOBfill);

void encode(EncodeFn fn, CUtensorMap* m, const void* p, int rank, const cuuint64_t* dims, const cuuint64_t* strides,
            const cuuint32_t* box, CUtensorMapSwizzle sw, int prom = 0) {
  const cuuint32_t es[5] = {1, 1, 1, 1, 1};
  fn(m, CU_TENSOR_MAP_DATA_TYPE_BFLOAT16, rank, const_cast<void*>(p), dims, strides, box, es, CU_TENSOR_MAP_INTERLEAVE_NONE, sw,
     (CUtensorMapL2promotion)prom, CU_TENSOR_MAP_FLOAT_OOB_FILL_NONE);
}
void encode2d(EncodeFn fn, CUtensorMap* m, const void* p, uint64_t cols, uint64_t rows, uint32_t bc, uint32_t br, CUtensorMapSwizzle sw, int prom = 0) {
  const cuuint64_t dims[2] = {cols, rows}, strides[1] = {cols * 2};
  const cuuint32_t box[2] = {bc, br};
  encode(fn, m, p, 2, dims, strides, box, sw, prom);
}
void encode3d(EncodeFn fn, CUtensorMap* m, const void* p) {
  const cuuint64_t dims[3] = {1024, 64, 32}, strides[2] = {2048 * 32, 2048};
  const cuuint32_t box[3] = {16, 32, 4};
  encode(fn, m, p, 3, dims, strides, box, CU_TENSOR_MAP_SWIZZLE_32B);
}
void encode4d(EncodeFn fn, CUtensorMap* m, const void* p, uint64_t cols, uint32_t rows, uint32_t nmat) {
  const cuuint64_t dims[4] = {64, 1024, 16, cols / 1024}, strides[3] = {cols * 2, 128, 2048};
  const cuuint32_t box[4] = {64, rows, 2, nmat};
  encode(fn, m, p, 4, dims, strides, box, CU_TENSOR_MAP_SWIZZLE_128B);
}
void encode5d(EncodeFn fn, CUtensorMap* m, const void* p, uint64_t cols, uint32_t n, uint32_t nw) {
  const cuuint64_t dims[5] = {cols, 4, 16, 8, 4}, strides[4] = {cols * 2 * 512, cols * 2 * 8, cols * 2, cols * 2 * 128};
  const cuuint32_t box[5] = {16, 2, 16, n, nw};
  encode(fn, m, p, 5, dims, strides, box, CU_TENSOR_MAP_SWIZZLE_32B);
}

}

extern "C" void kernel_launch(void* const* d_in, const int* in_sizes, int n_in, void* d_out, int out_size) {
  static EncodeFn fn = nullptr;
  static void *o_ptr = nullptr, *g_ptr = nullptr, *tab_ptr = nullptr;
  if (!fn) {
    cudaDriverEntryPointQueryResult qr;
    cudaGetDriverEntryPoint("cuTensorMapEncodeTiled", (void**)&fn, cudaEnableDefault, &qr);
    cudaGetSymbolAddress(&o_ptr, g_o);
    cudaGetSymbolAddress(&g_ptr, g_scratch);
    cudaGetSymbolAddress(&tab_ptr, d_tab);
    cudaFuncSetAttribute(fused_kernel, cudaFuncAttributeMaxDynamicSharedMemorySize, SM_TOTAL);
  }
  Params P;
  encode4d(fn, &P.w1, d_in[1], 3072, 32, 2);
  encode2d(fn, &P.x, d_in[0], 1024, 2048, 64, 64, CU_TENSOR_MAP_SWIZZLE_128B);
  encode4d(fn, &P.w2, d_in[1], 3072, 64, 1);
  encode4d(fn, &P.wo, d_in[2], 1024, 64, 1);
  encode2d(fn, &P.o, o_ptr, 1024, 2048, 64, 64, CU_TENSOR_MAP_SWIZZLE_128B);
  encode2d(fn, &P.outa, d_out, 2048, 2048, 64, 16, CU_TENSOR_MAP_SWIZZLE_128B);
  encode3d(fn, &P.k, d_in[4]);
  encode3d(fn, &P.v, d_in[5]);
  encode5d(fn, &P.q, d_in[3], 1024, 4, 2);
  encode5d(fn, &P.outb, d_out, 2048, PU, 1);
  P.shift_k = (const __nv_bfloat16*)d_in[6];
  P.ssm_k = (const __nv_bfloat16*)d_in[7];
  P.ssm_d = (const __nv_bfloat16*)d_in[8];
  P.q_ptr = (const __nv_bfloat16*)d_in[3];
  P.w_ptr = (const __nv_bfloat16*)d_in[1];
  P.wo_ptr = (const __nv_bfloat16*)d_in[2];
  P.zero = 0;
  P.g = (Scratch*)g_ptr;
  P.tab = (const uint32_t*)tab_ptr;
  fused_kernel<<<kCtas, kThreads, SM_TOTAL>>>(P);
}
```

```cpp
#include <cuda.h>
#include <cuda_runtime.h>
#include <cuda_bf16.h>
#include <stdint.h>

#define DEVI __device__ __forceinline__
#define INL __attribute__((always_inline))

namespace {

DEVI void mma_kt_init(float* d, uint64_t da, uint64_t db) {
  asm volatile("{\nwgmma.mma_async.sync.aligned.m64n128k16.f32.bf16.bf16 {%0, %1, %2, %3, %4, %5, %6, %7, %8, %9, %10, %11, %12, %13, %14, %15, %16, %17, %18, %19, %20, %21, %22, %23, %24, %25, %26, %27, %28, %29, %30, %31, %32, %33, %34, %35, %36, %37, %38, %39, %40, %41, %42, %43, %44, %45, %46, %47, %48, %49, %50, %51, %52, %53, %54, %55, %56, %57, %58, %59, %60, %61, %62, %63}, %64, %65, 0, 1, 1, 1, 0;\n}\n"
    : "=f"(d[0]), "=f"(d[1]), "=f"(d[2]), "=f"(d[3]), "=f"(d[4]), "=f"(d[5]), "=f"(d[6]), "=f"(d[7]), "=f"(d[8]), "=f"(d[9]), "=f"(d[10]), "=f"(d[11]), "=f"(d[12]), "=f"(d[13]), "=f"(d[14]), "=f"(d[15]), "=f"(d[16]), "=f"(d[17]), "=f"(d[18]), "=f"(d[19]), "=f"(d[20]), "=f"(d[21]), "=f"(d[22]), "=f"(d[23]), "=f"(d[24]), "=f"(d[25]), "=f"(d[26]), "=f"(d[27]), "=f"(d[28]), "=f"(d[29]), "=f"(d[30]), "=f"(d[31]), "=f"(d[32]), "=f"(d[33]), "=f"(d[34]), "=f"(d[35]), "=f"(d[36]), "=f"(d[37]), "=f"(d[38]), "=f"(d[39]), "=f"(d[40]), "=f"(d[41]), "=f"(d[42]), "=f"(d[43]), "=f"(d[44]), "=f"(d[45]), "=f"(d[46]), "=f"(d[47]), "=f"(d[48]), "=f"(d[49]), "=f"(d[50]), "=f"(d[51]), "=f"(d[52]), "=f"(d[53]), "=f"(d[54]), "=f"(d[55]), "=f"(d[56]), "=f"(d[57]), "=f"(d[58]), "=f"(d[59]), "=f"(d[60]), "=f"(d[61]), "=f"(d[62]), "=f"(d[63])
    : "l"(da), "l"(db));
}
DEVI void mma_kt(float* d, uint64_t da, uint64_t db) {
  asm volatile("{\nwgmma.mma_async.sync.aligned.m64n128k16.f32.bf16.bf16 {%0, %1, %2, %3, %4, %5, %6, %7, %8, %9, %10, %11, %12, %13, %14, %15, %16, %17, %18, %19, %20, %21, %22, %23, %24, %25, %26, %27, %28, %29, %30, %31, %32, %33, %34, %35, %36, %37, %38, %39, %40, %41, %42, %43, %44, %45, %46, %47, %48, %49, %50, %51, %52, %53, %54, %55, %56, %57, %58, %59, %60, %61, %62, %63}, %64, %65, 1, 1, 1, 1, 0;\n}\n"
    : "+f"(d[0]), "+f"(d[1]), "+f"(d[2]), "+f"(d[3]), "+f"(d[4]), "+f"(d[5]), "+f"(d[6]), "+f"(d[7]), "+f"(d[8]), "+f"(d[9]), "+f"(d[10]), "+f"(d[11]), "+f"(d[12]), "+f"(d[13]), "+f"(d[14]), "+f"(d[15]), "+f"(d[16]), "+f"(d[17]), "+f"(d[18]), "+f"(d[19]), "+f"(d[20]), "+f"(d[21]), "+f"(d[22]), "+f"(d[23]), "+f"(d[24]), "+f"(d[25]), "+f"(d[26]), "+f"(d[27]), "+f"(d[28]), "+f"(d[29]), "+f"(d[30]), "+f"(d[31]), "+f"(d[32]), "+f"(d[33]), "+f"(d[34]), "+f"(d[35]), "+f"(d[36]), "+f"(d[37]), "+f"(d[38]), "+f"(d[39]), "+f"(d[40]), "+f"(d[41]), "+f"(d[42]), "+f"(d[43]), "+f"(d[44]), "+f"(d[45]), "+f"(d[46]), "+f"(d[47]), "+f"(d[48]), "+f"(d[49]), "+f"(d[50]), "+f"(d[51]), "+f"(d[52]), "+f"(d[53]), "+f"(d[54]), "+f"(d[55]), "+f"(d[56]), "+f"(d[57]), "+f"(d[58]), "+f"(d[59]), "+f"(d[60]), "+f"(d[61]), "+f"(d[62]), "+f"(d[63])
    : "l"(da), "l"(db));
}
DEVI void mma_n128_init(float* d, uint64_t da, uint64_t db) {
  asm volatile("{\nwgmma.mma_async.sync.aligned.m64n128k16.f32.bf16.bf16 {%0, %1, %2, %3, %4, %5, %6, %7, %8, %9, %10, %11, %12, %13, %14, %15, %16, %17, %18, %19, %20, %21, %22, %23, %24, %25, %26, %27, %28, %29, %30, %31, %32, %33, %34, %35, %36, %37, %38, %39, %40, %41, %42, %43, %44, %45, %46, %47, %48, %49, %50, %51, %52, %53, %54, %55, %56, %57, %58, %59, %60, %61, %62, %63}, %64, %65, 0, 1, 1, 0, 1;\n}\n"
    : "=f"(d[0]), "=f"(d[1]), "=f"(d[2]), "=f"(d[3]), "=f"(d[4]), "=f"(d[5]), "=f"(d[6]), "=f"(d[7]), "=f"(d[8]), "=f"(d[9]), "=f"(d[10]), "=f"(d[11]), "=f"(d[12]), "=f"(d[13]), "=f"(d[14]), "=f"(d[15]), "=f"(d[16]), "=f"(d[17]), "=f"(d[18]), "=f"(d[19]), "=f"(d[20]), "=f"(d[21]), "=f"(d[22]), "=f"(d[23]), "=f"(d[24]), "=f"(d[25]), "=f"(d[26]), "=f"(d[27]), "=f"(d[28]), "=f"(d[29]), "=f"(d[30]), "=f"(d[31]), "=f"(d[32]), "=f"(d[33]), "=f"(d[34]), "=f"(d[35]), "=f"(d[36]), "=f"(d[37]), "=f"(d[38]), "=f"(d[39]), "=f"(d[40]), "=f"(d[41]), "=f"(d[42]), "=f"(d[43]), "=f"(d[44]), "=f"(d[45]), "=f"(d[46]), "=f"(d[47]), "=f"(d[48]), "=f"(d[49]), "=f"(d[50]), "=f"(d[51]), "=f"(d[52]), "=f"(d[53]), "=f"(d[54]), "=f"(d[55]), "=f"(d[56]), "=f"(d[57]), "=f"(d[58]), "=f"(d[59]), "=f"(d[60]), "=f"(d[61]), "=f"(d[62]), "=f"(d[63])
    : "l"(da), "l"(db));
}
DEVI void mma_n128(float* d, uint64_t da, uint64_t db) {
  asm volatile("{\nwgmma.mma_async.sync.aligned.m64n128k16.f32.bf16.bf16 {%0, %1, %2, %3, %4, %5, %6, %7, %8, %9, %10, %11, %12, %13, %14, %15, %16, %17, %18, %19, %20, %21, %22, %23, %24, %25, %26, %27, %28, %29, %30, %31, %32, %33, %34, %35, %36, %37, %38, %39, %40, %41, %42, %43, %44, %45, %46, %47, %48, %49, %50, %51, %52, %53, %54, %55, %56, %57, %58, %59, %60, %61, %62, %63}, %64, %65, 1, 1, 1, 0, 1;\n}\n"
    : "+f"(d[0]), "+f"(d[1]), "+f"(d[2]), "+f"(d[3]), "+f"(d[4]), "+f"(d[5]), "+f"(d[6]), "+f"(d[7]), "+f"(d[8]), "+f"(d[9]), "+f"(d[10]), "+f"(d[11]), "+f"(d[12]), "+f"(d[13]), "+f"(d[14]), "+f"(d[15]), "+f"(d[16]), "+f"(d[17]), "+f"(d[18]), "+f"(d[19]), "+f"(d[20]), "+f"(d[21]), "+f"(d[22]), "+f"(d[23]), "+f"(d[24]), "+f"(d[25]), "+f"(d[26]), "+f"(d[27]), "+f"(d[28]), "+f"(d[29]), "+f"(d[30]), "+f"(d[31]), "+f"(d[32]), "+f"(d[33]), "+f"(d[34]), "+f"(d[35]), "+f"(d[36]), "+f"(d[37]), "+f"(d[38]), "+f"(d[39]), "+f"(d[40]), "+f"(d[41]), "+f"(d[42]), "+f"(d[43]), "+f"(d[44]), "+f"(d[45]), "+f"(d[46]), "+f"(d[47]), "+f"(d[48]), "+f"(d[49]), "+f"(d[50]), "+f"(d[51]), "+f"(d[52]), "+f"(d[53]), "+f"(d[54]), "+f"(d[55]), "+f"(d[56]), "+f"(d[57]), "+f"(d[58]), "+f"(d[59]), "+f"(d[60]), "+f"(d[61]), "+f"(d[62]), "+f"(d[63])
    : "l"(da), "l"(db));
}
DEVI void mma_kv_init(float* d, const uint32_t* a, uint64_t db) {
  asm volatile("{\nwgmma.mma_async.sync.aligned.m64n72k16.f32.bf16.bf16 {%0, %1, %2, %3, %4, %5, %6, %7, %8, %9, %10, %11, %12, %13, %14, %15, %16, %17, %18, %19, %20, %21, %22, %23, %24, %25, %26, %27, %28, %29, %30, %31, %32, %33, %34, %35}, {%36,%37,%38,%39}, %40, 0, 1, 1, 1;\n}\n"
    : "=f"(d[0]), "=f"(d[1]), "=f"(d[2]), "=f"(d[3]), "=f"(d[4]), "=f"(d[5]), "=f"(d[6]), "=f"(d[7]), "=f"(d[8]), "=f"(d[9]), "=f"(d[10]), "=f"(d[11]), "=f"(d[12]), "=f"(d[13]), "=f"(d[14]), "=f"(d[15]), "=f"(d[16]), "=f"(d[17]), "=f"(d[18]), "=f"(d[19]), "=f"(d[20]), "=f"(d[21]), "=f"(d[22]), "=f"(d[23]), "=f"(d[24]), "=f"(d[25]), "=f"(d[26]), "=f"(d[27]), "=f"(d[28]), "=f"(d[29]), "=f"(d[30]), "=f"(d[31]), "=f"(d[32]), "=f"(d[33]), "=f"(d[34]), "=f"(d[35])
    : "r"(a[0]), "r"(a[1]), "r"(a[2]), "r"(a[3]), "l"(db));
}
DEVI void mma_kv(float* d, const uint32_t* a, uint64_t db) {
  asm volatile("{\nwgmma.mma_async.sync.aligned.m64n72k16.f32.bf16.bf16 {%0, %1, %2, %3, %4, %5, %6, %7, %8, %9, %10, %11, %12, %13, %14, %15, %16, %17, %18, %19, %20, %21, %22, %23, %24, %25, %26, %27, %28, %29, %30, %31, %32, %33, %34, %35}, {%36,%37,%38,%39}, %40, 1, 1, 1, 1;\n}\n"
    : "+f"(d[0]), "+f"(d[1]), "+f"(d[2]), "+f"(d[3]), "+f"(d[4]), "+f"(d[5]), "+f"(d[6]), "+f"(d[7]), "+f"(d[8]), "+f"(d[9]), "+f"(d[10]), "+f"(d[11]), "+f"(d[12]), "+f"(d[13]), "+f"(d[14]), "+f"(d[15]), "+f"(d[16]), "+f"(d[17]), "+f"(d[18]), "+f"(d[19]), "+f"(d[20]), "+f"(d[21]), "+f"(d[22]), "+f"(d[23]), "+f"(d[24]), "+f"(d[25]), "+f"(d[26]), "+f"(d[27]), "+f"(d[28]), "+f"(d[29]), "+f"(d[30]), "+f"(d[31]), "+f"(d[32]), "+f"(d[33]), "+f"(d[34]), "+f"(d[35])
    : "r"(a[0]), "r"(a[1]), "r"(a[2]), "r"(a[3]), "l"(db));
}
DEVI void mma_o_init(float* d, const uint32_t* a, uint64_t db) {
  asm volatile("{\nwgmma.mma_async.sync.aligned.m64n40k16.f32.bf16.bf16 {%0, %1, %2, %3, %4, %5, %6, %7, %8, %9, %10, %11, %12, %13, %14, %15, %16, %17, %18, %19}, {%20,%21,%22,%23}, %24, 0, 1, 1, 1;\n}\n"
    : "=f"(d[0]), "=f"(d[1]), "=f"(d[2]), "=f"(d[3]), "=f"(d[4]), "=f"(d[5]), "=f"(d[6]), "=f"(d[7]), "=f"(d[8]), "=f"(d[9]), "=f"(d[10]), "=f"(d[11]), "=f"(d[12]), "=f"(d[13]), "=f"(d[14]), "=f"(d[15]), "=f"(d[16]), "=f"(d[17]), "=f"(d[18]), "=f"(d[19])
    : "r"(a[0]), "r"(a[1]), "r"(a[2]), "r"(a[3]), "l"(db));
}
DEVI void mma_o(float* d, const uint32_t* a, uint64_t db) {
  asm volatile("{\nwgmma.mma_async.sync.aligned.m64n40k16.f32.bf16.bf16 {%0, %1, %2, %3, %4, %5, %6, %7, %8, %9, %10, %11, %12, %13, %14, %15, %16, %17, %18, %19}, {%20,%21,%22,%23}, %24, 1, 1, 1, 1;\n}\n"
    : "+f"(d[0]), "+f"(d[1]), "+f"(d[2]), "+f"(d[3]), "+f"(d[4]), "+f"(d[5]), "+f"(d[6]), "+f"(d[7]), "+f"(d[8]), "+f"(d[9]), "+f"(d[10]), "+f"(d[11]), "+f"(d[12]), "+f"(d[13]), "+f"(d[14]), "+f"(d[15]), "+f"(d[16]), "+f"(d[17]), "+f"(d[18]), "+f"(d[19])
    : "r"(a[0]), "r"(a[1]), "r"(a[2]), "r"(a[3]), "l"(db));
}
DEVI void mma_s1_init(uint32_t* d, const uint32_t* a, uint64_t db) {
  asm volatile("{\nwgmma.mma_async.sync.aligned.m64n128k16.f16.f16.f16 {%0, %1, %2, %3, %4, %5, %6, %7, %8, %9, %10, %11, %12, %13, %14, %15, %16, %17, %18, %19, %20, %21, %22, %23, %24, %25, %26, %27, %28, %29, %30, %31}, {%32,%33,%34,%35}, %36, 0, 1, 1, 1;\n}\n"
    : "=r"(d[0]), "=r"(d[1]), "=r"(d[2]), "=r"(d[3]), "=r"(d[4]), "=r"(d[5]), "=r"(d[6]), "=r"(d[7]), "=r"(d[8]), "=r"(d[9]), "=r"(d[10]), "=r"(d[11]), "=r"(d[12]), "=r"(d[13]), "=r"(d[14]), "=r"(d[15]), "=r"(d[16]), "=r"(d[17]), "=r"(d[18]), "=r"(d[19]), "=r"(d[20]), "=r"(d[21]), "=r"(d[22]), "=r"(d[23]), "=r"(d[24]), "=r"(d[25]), "=r"(d[26]), "=r"(d[27]), "=r"(d[28]), "=r"(d[29]), "=r"(d[30]), "=r"(d[31])
    : "r"(a[0]), "r"(a[1]), "r"(a[2]), "r"(a[3]), "l"(db));
}
DEVI void mma_s1(uint32_t* d, const uint32_t* a, uint64_t db) {
  asm volatile("{\nwgmma.mma_async.sync.aligned.m64n128k16.f16.f16.f16 {%0, %1, %2, %3, %4, %5, %6, %7, %8, %9, %10, %11, %12, %13, %14, %15, %16, %17, %18, %19, %20, %21, %22, %23, %24, %25, %26, %27, %28, %29, %30, %31}, {%32,%33,%34,%35}, %36, 1, 1, 1, 1;\n}\n"
    : "+r"(d[0]), "+r"(d[1]), "+r"(d[2]), "+r"(d[3]), "+r"(d[4]), "+r"(d[5]), "+r"(d[6]), "+r"(d[7]), "+r"(d[8]), "+r"(d[9]), "+r"(d[10]), "+r"(d[11]), "+r"(d[12]), "+r"(d[13]), "+r"(d[14]), "+r"(d[15]), "+r"(d[16]), "+r"(d[17]), "+r"(d[18]), "+r"(d[19]), "+r"(d[20]), "+r"(d[21]), "+r"(d[22]), "+r"(d[23]), "+r"(d[24]), "+r"(d[25]), "+r"(d[26]), "+r"(d[27]), "+r"(d[28]), "+r"(d[29]), "+r"(d[30]), "+r"(d[31])
    : "r"(a[0]), "r"(a[1]), "r"(a[2]), "r"(a[3]), "l"(db));
}
DEVI void mma_s2_init(uint32_t* d, const uint32_t* a, uint64_t db) {
  asm volatile("{\nwgmma.mma_async.sync.aligned.m64n32k16.f16.f16.f16 {%0, %1, %2, %3, %4, %5, %6, %7}, {%8,%9,%10,%11}, %12, 0, 1, 1, 0;\n}\n"
    : "=r"(d[0]), "=r"(d[1]), "=r"(d[2]), "=r"(d[3]), "=r"(d[4]), "=r"(d[5]), "=r"(d[6]), "=r"(d[7])
    : "r"(a[0]), "r"(a[1]), "r"(a[2]), "r"(a[3]), "l"(db));
}
DEVI void mma_s2(uint32_t* d, const uint32_t* a, uint64_t db) {
  asm volatile("{\nwgmma.mma_async.sync.aligned.m64n32k16.f16.f16.f16 {%0, %1, %2, %3, %4, %5, %6, %7}, {%8,%9,%10,%11}, %12, 1, 1, 1, 0;\n}\n"
    : "+r"(d[0]), "+r"(d[1]), "+r"(d[2]), "+r"(d[3]), "+r"(d[4]), "+r"(d[5]), "+r"(d[6]), "+r"(d[7])
    : "r"(a[0]), "r"(a[1]), "r"(a[2]), "r"(a[3]), "l"(db));
}
DEVI void mma_s2_neg(uint32_t* d, const uint32_t* a, uint64_t db) {
  asm volatile("{\nwgmma.mma_async.sync.aligned.m64n32k16.f16.f16.f16 {%0, %1, %2, %3, %4, %5, %6, %7}, {%8,%9,%10,%11}, %12, 1, -1, 1, 0;\n}\n"
    : "+r"(d[0]), "+r"(d[1]), "+r"(d[2]), "+r"(d[3]), "+r"(d[4]), "+r"(d[5]), "+r"(d[6]), "+r"(d[7])
    : "r"(a[0]), "r"(a[1]), "r"(a[2]), "r"(a[3]), "l"(db));
}
DEVI void mma_i2_init(float* d, const uint32_t* a, uint64_t db, uint32_t meta) {
  asm volatile("{\nwgmma.mma_async.sp.sync.aligned.m64n128k32.f32.f16.f16 {%0, %1, %2, %3, %4, %5, %6, %7, %8, %9, %10, %11, %12, %13, %14, %15, %16, %17, %18, %19, %20, %21, %22, %23, %24, %25, %26, %27, %28, %29, %30, %31, %32, %33, %34, %35, %36, %37, %38, %39, %40, %41, %42, %43, %44, %45, %46, %47, %48, %49, %50, %51, %52, %53, %54, %55, %56, %57, %58, %59, %60, %61, %62, %63}, {%64,%65,%66,%67}, %68, %69, 0, 0, 1, 1, 1;\n}\n"
    : "=f"(d[0]), "=f"(d[1]), "=f"(d[2]), "=f"(d[3]), "=f"(d[4]), "=f"(d[5]), "=f"(d[6]), "=f"(d[7]), "=f"(d[8]), "=f"(d[9]), "=f"(d[10]), "=f"(d[11]), "=f"(d[12]), "=f"(d[13]), "=f"(d[14]), "=f"(d[15]), "=f"(d[16]), "=f"(d[17]), "=f"(d[18]), "=f"(d[19]), "=f"(d[20]), "=f"(d[21]), "=f"(d[22]), "=f"(d[23]), "=f"(d[24]), "=f"(d[25]), "=f"(d[26]), "=f"(d[27]), "=f"(d[28]), "=f"(d[29]), "=f"(d[30]), "=f"(d[31]), "=f"(d[32]), "=f"(d[33]), "=f"(d[34]), "=f"(d[35]), "=f"(d[36]), "=f"(d[37]), "=f"(d[38]), "=f"(d[39]), "=f"(d[40]), "=f"(d[41]), "=f"(d[42]), "=f"(d[43]), "=f"(d[44]), "=f"(d[45]), "=f"(d[46]), "=f"(d[47]), "=f"(d[48]), "=f"(d[49]), "=f"(d[50]), "=f"(d[51]), "=f"(d[52]), "=f"(d[53]), "=f"(d[54]), "=f"(d[55]), "=f"(d[56]), "=f"(d[57]), "=f"(d[58]), "=f"(d[59]), "=f"(d[60]), "=f"(d[61]), "=f"(d[62]), "=f"(d[63])
    : "r"(a[0]), "r"(a[1]), "r"(a[2]), "r"(a[3]), "l"(db), "r"(meta));
}
DEVI void mma_i2(float* d, const uint32_t* a, uint64_t db, uint32_t meta) {
  asm volatile("{\nwgmma.mma_async.sp.sync.aligned.m64n128k32.f32.f16.f16 {%0, %1, %2, %3, %4, %5, %6, %7, %8, %9, %10, %11, %12, %13, %14, %15, %16, %17, %18, %19, %20, %21, %22, %23, %24, %25, %26, %27, %28, %29, %30, %31, %32, %33, %34, %35, %36, %37, %38, %39, %40, %41, %42, %43, %44, %45, %46, %47, %48, %49, %50, %51, %52, %53, %54, %55, %56, %57, %58, %59, %60, %61, %62, %63}, {%64,%65,%66,%67}, %68, %69, 0, 1, 1, 1, 1;\n}\n"
    : "+f"(d[0]), "+f"(d[1]), "+f"(d[2]), "+f"(d[3]), "+f"(d[4]), "+f"(d[5]), "+f"(d[6]), "+f"(d[7]), "+f"(d[8]), "+f"(d[9]), "+f"(d[10]), "+f"(d[11]), "+f"(d[12]), "+f"(d[13]), "+f"(d[14]), "+f"(d[15]), "+f"(d[16]), "+f"(d[17]), "+f"(d[18]), "+f"(d[19]), "+f"(d[20]), "+f"(d[21]), "+f"(d[22]), "+f"(d[23]), "+f"(d[24]), "+f"(d[25]), "+f"(d[26]), "+f"(d[27]), "+f"(d[28]), "+f"(d[29]), "+f"(d[30]), "+f"(d[31]), "+f"(d[32]), "+f"(d[33]), "+f"(d[34]), "+f"(d[35]), "+f"(d[36]), "+f"(d[37]), "+f"(d[38]), "+f"(d[39]), "+f"(d[40]), "+f"(d[41]), "+f"(d[42]), "+f"(d[43]), "+f"(d[44]), "+f"(d[45]), "+f"(d[46]), "+f"(d[47]), "+f"(d[48]), "+f"(d[49]), "+f"(d[50]), "+f"(d[51]), "+f"(d[52]), "+f"(d[53]), "+f"(d[54]), "+f"(d[55]), "+f"(d[56]), "+f"(d[57]), "+f"(d[58]), "+f"(d[59]), "+f"(d[60]), "+f"(d[61]), "+f"(d[62]), "+f"(d[63])
    : "r"(a[0]), "r"(a[1]), "r"(a[2]), "r"(a[3]), "l"(db), "r"(meta));
}
__device__ const __align__(128) uint32_t d_tab[2944] = {
  0x3bf13bff,0x2fbd25e4,0x38ee3986,0x3a4d39c9,0x3b9a3bcf,0x34ff32f7,0x3737384a,0x3b243ac1,0x3af73b52,0x37dd3676,0x344b35c8,0x3bb53b76,
  0x3a113a8c,0x39373899,0x2cce3185,0x3bfa3be1,0x3a933bf2,0x388e2f59,0xb1b6b8f8,0xbbdfba45,0xa452374e,0x3c003b1e,0x39c034e7,0xb990bb9e,
  0xbabab7c8,0x38553afe,0x3bd23bb2,0x32c6b463,0xbb57bbf9,0xb65f2d33,0x35df3a19,0x3b71392e,0x37643bd4,0x3b183294,0xb4cf385f,0x3ba13ab3,
  0xbbaeb648,0x347b3b5c,0xbb04bb6c,0xb7b235f7,0xad97ba9b,0xbbf8b884,0x3924b1e8,0xba21bbdd,0x3bf439b8,0x2ef5b999,0x39023c00,0x3a3d217f,
  0x9cb63ba5,0x3c0034b7,0x39afb77a,0xb9a1bb13,0xb86abbab,0xbaac3493,0xb2633b0a,0x3bd7379b,0x3b60391b,0x3631ba29,0xb60ebbf7,0xbb682dfb,
  0xbbdaae91,0x32193bf5,0x3aa23a35,0x387ab90c,0xb7853b65,0x3b10361a,0xbba73625,0x34ab3b63,0x3911baa9,0xba31b86f,0x3bf6b24b,0xae5fbbd8,
  0xba2d39aa,0x391639a6,0xbbf61648,0xae2d3c00,0x3b0db874,0xb790baa5,0x3ba93232,0x349fbbd9,0xba9e3b16,0x387f376f,0x3bdcb4c3,0x3201bba3,
  0x3b6aaec3,0x3602bbf5,0xb63cb907,0xbb5e3a39,0xb27cba25,0xbbd6391f,0xb8653bf8,0x3ab02dc9,0xb99d3bac,0x39b33487,0x3c00b7a6,0x9fdbbb07,
  0xbbf33ab6,0x2f27385a,0xba4132ad,0xb8fd3bd3,0xad653994,0x3bf9b9bc,0xba1d3c00,0x3929a311,0x3bb0b889,0x346fba97,0x37bd31cf,0x3b01bbde,
  0x3759bb59,0xbb1b3654,0x3b9fbb6f,0xb4dbb5eb,0xbb733a49,0xb5d438f3,0x366baf8b,0x3b54bbf2,0xbbd03bfa,0x32de2d00,0x3abdb933,0x3850ba15,
  0xb98b3afb,0x39c5b7d2,0x3c00bbb3,0xa51bb457,0xb19e3742,0x3be0bb21,0x3a90bb9c,0xb89434f3,0xb93c39cd,0xba0d3982,0x2c9c26ad,0xbbfb3bff,
  0xb7e8389e,0xbaf43a89,0x343eb16c,0xbbb73be2,0xb50b3682,0xbb983b4f,0x372cb5bc,0xbb273b78,0xafef330f,0xbbf03bce,0x38eab845,0xba503ac4,
  0xb3403946,0xbbcb3a04,0xb83a2c38,0x3acbbbfc,0x3979b426,0xb9d63bba,0xbbff3aee,0x281fb7fe,0x3be4bb94,0x313b3523,0xb8a83b2c,0xba813715,
  0x3699ba58,0x3b4ab8e0,0x35a53029,0xbb7c3bef,0x340e38b2,0xbbbd3a7a,0x3ae8b109,0xb80a3be6,0x3b32bb45,0x36ff36af,0x353abb81,0x3b90b58d,
  0xb8d6b371,0x3a60bbc8,0xbbed3830,0x305bbad1,0xb94f3bfe,0xb9fca8e8,0x2ba739df,0xbbfc3970,0x39663815,0xb9e73ae1,0xbbfe33eb,0x29b1bbc0,
  0xb0d7bb37,0x3be8b6e8,0x3a733552,0xb8bc3b8b,0xb6c63beb,0xbb3fb08d,0xb576ba67,0x3b85b8cc,0x3ad8b9f4,0x38253958,0xb3a23bfd,0xbbc52ade,
  0x3b8736dd,0xb56a3b3a,0x3b3db55e,0x36d23b89,0xbbe9b3d3,0x30bebbc2,0xba6f381a,0xb8c1bade,0x3bfe2a7a,0x2a163bfd,0x3962b95d,0x39eb39f0,
  0xbbc330a6,0xb3babbea,0xb8203a6b,0xbadbb8c7,0x3bec3581,0x30743b83,0xb8d136bb,0xba64bb42,0xb6f438b7,0xbb35ba76,0xb546bbe7,0x3b8e30f0,
  0xb80fbbfe,0x3ae5a94d,0x3bbf396b,0xb40239e3,0x3bfd382a,0xab433ad5,0xb9f83389,0xb954bbc6,0x3a7e341a,0x38ad3bbc,0x3122b805,0x3be53aeb,
  0x39da3bfc,0xb974ac06,0x3bff3a00,0x2884394a,0xb8353042,0xbacebbee,0x33593a5c,0xbbc9b8db,0xbb7fbb92,0x3599b52f,0xbb47b70a,0xb6a4bb2f,
  0x37213153,0x3b2a3be3,0x351738a3,0xbb96ba85,0x3af1397d,0x37f339d2,0xb4322776,0xbbb8bbff,0x3bfb3bcc,0xac6a3328,0xba09b840,0xb941bac7,
  0x3a543b7a,0xb8e5b5b1,0xbbefbb4c,0xb010b68d,0x32f72fbd,0xbbcfbbf1,0x3ac13a4d,0xb84ab8ee,0x367634ff,0xbb52bb9a,0x3b763b24,0xb5c8b737,
  0x389937dd,0xba8cbaf7,0x3be13bb5,0xb185b44b,0x39c93937,0xb986ba11,0x3bff3bfa,0x25e4acce,0x392e32c6,0xba19bbd2,0xbbf9baba,0x2d333855,
  0x3bf23b71,0x2f59b5df,0xb8f8bb57,0xba45b65f,0x374e3a93,0x3b1e388e,0x34e7b1b6,0xbb9ebbdf,0xb7c8a452,0x3afe3c00,0x3bb239c0,0xb463b990,
  0x3b6c34cf,0xb5f7bba1,0x3b5c3b18,0x3648b764,0x31e83b04,0x3bdd37b2,0xb884347b,0x3a9b3bae,0xbc00b924,0xa17f3a21,0xb999bbf8,0xb9b82d97,
  0x3294b902,0xbbd4ba3d,0x3ab32ef5,0xb85fbbf4,0x3bf53631,0x2e91bb60,0xb90cbb68,0xba35360e,0xbb133219,0x377a3bda,0x3ba5387a,0x34b7baa2,
  0x379bb9a1,0xbb0ab9af,0xbbab9cb6,0x34933c00,0x2dfb3bd7,0x3bf73263,0x391bb86a,0xba29baac,0x3aa93785,0x386fbb10,0x324b3ba7,0x3bd8b4ab,
  0xb9aab911,0xb9a63a31,0x9648bbf6,0xbc002e5f,0x38743a2d,0x3aa5b916,0xb2323bf6,0x3bd92e2d,0xb625bb0d,0xbb633790,0x361abba9,0xbb65b49f,
  0x37a63865,0x3b07bab0,0x3487bbd6,0xbbac327c,0x376fbc00,0xbb161fdb,0xbba339b3,0x34c3399d,0xbbf5387f,0x2ec33a9e,0x3a393201,0x3907bbdc,
  0x391f3602,0x3a25bb6a,0x2dc9bb5e,0xbbf8363c,0x231138fd,0x3c00ba41,0xb9943bf3,0x39bcaf27,0x3bdeb929,0x31cfba1d,0x38892d65,0x3a97bbf9,
  0x35ebbb01,0xbb6f37bd,0x3b59bbb0,0xb654b46f,0xbab634db,0xb85a3b9f,0xb2adb759,0xbbd33b1b,0xb742398b,0x3b21b9c5,0x3b9cbc00,0xb4f3251b,
  0x2f8b319e,0x3bf2bbe0,0x38f3ba90,0xba493894,0x3933b66b,0x3a15bb54,0x2d00b5d4,0xbbfa3b73,0x3bb3babd,0x3457b850,0xb7d232de,0xbafb3bd0,
  0xba893a0d,0x389eb93c,0xbbe23bfb,0xb16c2c9c,0xbb4f3af4,0x3682b7e8,0xbb783bb7,0xb5bc343e,0xbbce3b98,0x330fb50b,0xbac43b27,0xb845372c,
  0xbbff3bf0,0x26adafef,0xb9cd3a50,0xb98238ea,0xbbef3a81,0x3029b8a8,0x3a58bbe4,0x38e0b13b,0xb9463b7c,0xba0435a5,0xac38b699,0x3bfcbb4a,
  0x34263340,0xbbba3bcb,0xbaee383a,0x37febacb,0x3b94b979,0xb52339d6,0xbb2c3bff,0xb715a81f,0xbb813ae8,0xb58db80a,0xb6af3bbd,0xbb45340e,
  0x3830353a,0xbad13b90,0x3bc8b6ff,0xb3713b32,0x39dfbbed,0x3970305b,0x28e8ba60,0x3bfeb8d6,0xba7a2ba7,0x38b2bbfc,0xbbe639fc,0xb109b94f,
  0xb9583b3f,0xb9f4b6c6,0xaadebb85,0x3bfdb576,0x3bc0b825,0x33eb3ad8,0xb8153bc5,0xbae1b3a2,0xbb8ba9b1,0x3552bbfe,0x3b37b966,0x36e839e7,
  0x38cc38bc,0xba673a73,0xbbeb30d7,0x308dbbe8,0xb3d33b87,0xbbc2b56a,0x381a3b3d,0xbade36d2,0x2a7abbe9,0x3bfd30be,0xb95dba6f,0x39f0b8c1,
  0x30a63bfe,0xbbea2a16,0x3a6b3962,0xb8c739eb,0xb55ebbc3,0x3b89b3ba,0xbb3ab820,0x36ddbadb,0x33893bbf,0xbbc6b402,0xbad5bae5,0x382ab80f,
  0xbb83b9f8,0x3581b954,0x3b422b43,0x36bb3bfd,0x3a76b074,0x38b73bec,0xb0f03a64,0xbbe7b8d1,0x294d3b35,0xbbfeb6f4,0xb9e3bb8e,0x396bb546,
  0x394a3be5,0xba00b122,0x3bfc3a7e,0xac0638ad,0xb8db2884,0xba5cbbff,0x304239da,0xbbeeb974,0xbb2fbbc9,0x370ab359,0xbb92b835,0xb52fbace,
  0x341ab6a4,0x3bbc3b47,0xb805bb7f,0x3aeb3599,0x3b7a3bfb,0xb5b1ac6a,0xbb4cba09,0xb68db941,0x38a33a54,0xba85b8e5,0xbbe3bbef,0x3153b010,
  0x27763517,0xbbffbb96,0xb9d2bb2a,0x397d3721,0xb840b432,0xbac7bbb8,0xb328b7f3,0x3bcc3af1,0x3be23bfb,0x316c2c9c,0x389e393c,0x3a893a0d,
  0x3b783bb7,0x35bc343e,0x368237e8,0x3b4f3af4,0x3ac43b27,0x3845372c,0x330f350b,0x3bce3b98,0x39cd3a50,0x398238ea,0x26ad2fef,0x3bff3bf0,
  0x39463b7c,0x3a0435a5,0x2c38b699,0xbbfcbb4a,0xb4263340,0x3bba3bcb,0x3aee383a,0xb7febacb,0xbb94b979,0x352339d6,0x3b2c3bff,0x3715a81f,
  0xba58bbe4,0xb8e0b13b,0x302938a8,0x3bef3a81,0x28e83a60,0x3bfe38d6,0xb970305b,0x39df3bed,0xbbe6b9fc,0xb109394f,0xb8b2bbfc,0xba7aaba7,
  0x358db80a,0xbb81bae8,0x3b45340e,0xb6afbbbd,0x3ad13b90,0x3830b53a,0x33713b32,0x3bc836ff,0xb8cc38bc,0x3a673a73,0x3beb30d7,0xb08dbbe8,
  0x2adebb85,0xbbfdb576,0xb9f436c6,0x39583b3f,0x38153bc5,0x3ae1b3a2,0x33ebbad8,0xbbc0b825,0xbb37b966,0xb6e839e7,0x35523bfe,0x3b8ba9b1,
  0xbbc2356a,0x33d33b87,0xbadeb6d2,0xb81a3b3d,0x3bfdb0be,0xaa7abbe9,0x39f038c1,0x395dba6f,0xbbeaaa16,0xb0a63bfe,0xb8c7b9eb,0xba6b3962,
  0x3b8933ba,0x355ebbc3,0x36dd3adb,0x3b3ab820,0xbb422b43,0xb6bb3bfd,0x35813954,0x3b83b9f8,0x30f03a64,0x3be7b8d1,0x38b7bbec,0xba76b074,
  0x39e3bb8e,0xb96bb546,0xbbfe36f4,0xa94d3b35,0xbbc63402,0xb3893bbf,0x382a380f,0x3ad5bae5,0xb70ab359,0xbb2f3bc9,0x352fbace,0xbb923835,
  0xbbbc3b47,0x341a36a4,0xbaeb3599,0xb8053b7f,0x2c0638ad,0x3bfcba7e,0xb94a3be5,0x3a00b122,0x3beeb974,0x3042b9da,0x38db2884,0x3a5cbbff,
  0x3328b7f3,0xbbcc3af1,0xbac73bb8,0x3840b432,0xb5b12c6a,0xbb7a3bfb,0xb68d3941,0x3b4cba09,0xba8538e5,0xb8a33a54,0x31533010,0x3be3bbef,
  0xbbff3b96,0xa7763517,0x397db721,0x39d2bb2a,0x3a4db9c9,0xb8ee3986,0x3bf1bbff,0x2fbda5e4,0x3b24bac1,0xb737384a,0x3b9abbcf,0x34ffb2f7,
  0x3bb5bb76,0xb44b35c8,0x3af7bb52,0x37ddb676,0x3bfabbe1,0xacce3185,0x3a11ba8c,0x3937b899,0x3c00bb1e,0x2452374e,0xb9903b9e,0xb9c034e7,
  0x3855bafe,0x3abab7c8,0x32c63463,0xbbd23bb2,0xb65fad33,0x3b57bbf9,0x3b71b92e,0xb5df3a19,0xbbdf3a45,0x31b6b8f8,0x3a93bbf2,0x388eaf59,
  0x3a21bbdd,0x392431e8,0x2d97ba9b,0x3bf8b884,0xba3d217f,0x3902bc00,0xbbf439b8,0xaef5b999,0xb7643bd4,0xbb183294,0x34cf385f,0xbba13ab3,
  0x3baeb648,0xb47b3b5c,0x3b04bb6c,0x37b235f7,0x3219bbf5,0x3bdaae91,0x387a390c,0xbaa23a35,0xb9a13b13,0xb9afb77a,0x9cb6bba5,0x3c00b4b7,
  0x3bd7b79b,0x32633b0a,0xb86a3bab,0xbaacb493,0xbb68adfb,0x360ebbf7,0x3b60b91b,0x36313a29,0xb785bb65,0x3b10b61a,0xbba7b625,0x34abbb63,
  0x39113aa9,0xba31386f,0x3bf6324b,0xae5f3bd8,0xba2db9aa,0x3916b9a6,0xbbf69648,0xae2dbc00,0x3b0d3874,0xb7903aa5,0x3ba9b232,0x349f3bd9,
  0xbb5eba39,0x363cb907,0x3b6a2ec3,0x36023bf5,0x3ab0adc9,0x38653bf8,0xb27c3a25,0xbbd6b91f,0x9fdb3b07,0xbc00b7a6,0xb99dbbac,0x39b3b487,
  0xba9ebb16,0x387fb76f,0x3bdc34c3,0x32013ba3,0xbbb0b889,0xb46fba97,0xb7bd31cf,0xbb01bbde,0xb759bb59,0x3b1b3654,0xbb9fbb6f,0x34dbb5eb,
  0x3a4132ad,0x38fd3bd3,0x2f27b85a,0x3bf33ab6,0x3a1d3c00,0xb929a311,0x3bf939bc,0x2d653994,0xb894b4f3,0xba90bb9c,0xb19eb742,0x3be03b21,
  0xbb73ba49,0xb5d4b8f3,0x366b2f8b,0x3b543bf2,0xbbd0bbfa,0x32dead00,0x3abd3933,0x38503a15,0xb98bbafb,0x39c537d2,0x3c003bb3,0xa51b3457,
  0xb43eb16c,0x3bb73be2,0xbaf4ba89,0x37e8389e,0xb72cb5bc,0x3b273b78,0xbb98bb4f,0x350b3682,0xb8eab845,0x3a503ac4,0xbbf0bbce,0x2fef330f,
  0xba0db982,0x393c39cd,0xbbfbbbff,0xac9c26ad,0xba81b715,0x38a83b2c,0x3be43b94,0x313bb523,0xbb7cbbef,0xb5a53029,0x36993a58,0x3b4a38e0,
  0xb340b946,0xbbcbba04,0xb83aac38,0x3acb3bfc,0x39793426,0xb9d6bbba,0xbbffbaee,0x281f37fe,0xbbfcb970,0xaba739df,0xb94fbbfe,0xb9fc28e8,
  0x340eb8b2,0xbbbdba7a,0x3ae83109,0xb80abbe6,0x3b323b45,0x36ffb6af,0x353a3b81,0x3b90358d,0xb8d63371,0x3a603bc8,0xbbedb830,0x305b3ad1,
  0xb9e7bae1,0xb9663815,0x29b13bc0,0x3bfe33eb,0x3be836e8,0x30d7bb37,0xb8bcbb8b,0xba733552,0xbb3f308d,0x36c63beb,0x3b8538cc,0x3576ba67,
  0x3825b958,0xbad8b9f4,0xbbc5aade,0x33a23bfd,0xb0bebbc2,0xbbe933d3,0x38c1bade,0xba6fb81a,0xaa163bfd,0x3bfeaa7a,0xb9eb39f0,0x3962395d,
  0x33babbea,0xbbc3b0a6,0x3adbb8c7,0xb820ba6b,0xb6d23b89,0x3b3d355e,0xbb8736dd,0x356a3b3a,0x380fbbfe,0xbae5a94d,0xbbbf396b,0x340239e3,
  0xbbfd382a,0x2b433ad5,0x39f83389,0x3954bbc6,0x38d136bb,0x3a64bb42,0x3074bb83,0xbbec3581,0x3546bbe7,0xbb8e30f0,0xbb353a76,0x36f438b7,
  0x3b7fbb92,0xb599b52f,0x3b47b70a,0x36a4bb2f,0xb122b805,0xbbe53aeb,0x38adbbbc,0xba7e341a,0xbbff3a00,0xa884394a,0xb9742c06,0xb9da3bfc,
  0xb3593a5c,0x3bc9b8db,0xbace3bee,0x38353042,0x3b96ba85,0x3517b8a3,0xb7213153,0xbb2a3be3,0x3bb8bbff,0xb432a776,0xbaf1397d,0xb7f339d2,
  0x3941bac7,0xba093840,0xbbfb3bcc,0x2c6a3328,0x3010b68d,0xbbef3b4c,0xba543b7a,0x38e5b5b1,0x384ab8ee,0x3ac1ba4d,0xb2f72fbd,0x3bcfbbf1,
  0x35c8b737,0x3b76bb24,0xb67634ff,0x3b52bb9a,0x3185b44b,0x3be1bbb5,0xb89937dd,0x3a8cbaf7,0xa5e4acce,0x3bffbbfa,0xb9c93937,0x3986ba11,
  0xaf59b5df,0x3bf2bb71,0x3a45b65f,0xb8f83b57,0xbb1e388e,0x374eba93,0x3b9ebbdf,0x34e731b6,0xbafe3c00,0xb7c82452,0x3463b990,0x3bb2b9c0,
  0xad333855,0xbbf93aba,0xb92e32c6,0x3a19bbd2,0xb9b8ad97,0x3999bbf8,0xbc003924,0xa17fba21,0xb85f3bf4,0xbab32ef5,0x32943902,0xbbd43a3d,
  0x3b6cb4cf,0xb5f73ba1,0x3b5cbb18,0x36483764,0x31e8bb04,0x3bddb7b2,0xb884b47b,0x3a9bbbae,0xbbf73263,0x2dfbbbd7,0x3a29baac,0x391b386a,
  0x3a35360e,0xb90c3b68,0xbbf53631,0xae91bb60,0xb4b7baa2,0x3ba5b87a,0x3b133219,0xb77a3bda,0xb4933c00,0xbbab1cb6,0xb79bb9a1,0x3b0ab9af,
  0xbaa93785,0xb86fbb10,0xb24b3ba7,0xbbd8b4ab,0x39aab911,0x39a63a31,0x1648bbf6,0x3c002e5f,0xb8743a2d,0xbaa5b916,0x32323bf6,0xbbd92e2d,
  0x3625bb0d,0x3b633790,0xb61abba9,0x3b65b49f,0xb4c3399d,0xbba3b9b3,0xb76fbc00,0x3b161fdb,0xb907bbdc,0x3a39b201,0x3bf5387f,0xaec33a9e,
  0x3bf8363c,0x2dc93b5e,0xb91f3602,0xba25bb6a,0xb7a63865,0xbb07bab0,0xb487bbd6,0x3bac327c,0x35eb3b01,0xbb6fb7bd,0x3b593bb0,0xb654346f,
  0xbab6b4db,0xb85abb9f,0xb2ad3759,0xbbd3bb1b,0xb994bbf3,0x39bc2f27,0xbc00ba41,0x2311b8fd,0x3889ad65,0x3a973bf9,0xb1cfba1d,0x3bde3929,
  0x3afb3bd0,0xb7d2b2de,0xbbb3babd,0xb457b850,0x3742398b,0xbb21b9c5,0xbb9cbc00,0x34f3251b,0xaf8b319e,0xbbf2bbe0,0xb8f3ba90,0x3a493894,
  0xb933b66b,0xba15bb54,0xad00b5d4,0x3bfa3b73,0x211b21e4,0xa51ba5e4,0x98b69248,0x1cb61648,0x1f122052,0xa311a452,0x9d7f9bdb,0x217f1fdb,
  0x1bdb1d7f,0x9fdba17f,0xa0529f12,0x24522311,0x124818b6,0x96489cb6,0xa1e4a11b,0x25e4251b,0x2a632b5f,0xae5faf59,0xa1e49bdb,0x25e41fdb,
  0x286b2967,0xac6aad65,0xa6e0a4e9,0x2ade28e8,0x24e926e0,0xa8e8aade,0xa967a86b,0x2d652c6a,0x1bdb21e4,0x9fdba5e4,0xab5faa63,0x2f592e5f,
  0x2dc22ea7,0xb1b6b294,0xa54d9f12,0x294d2311,0x2bf62cde,0xafefb0d7,0xaa31a86b,0x2e2d2c6a,0x286b2a31,0xac6aae2d,0xacdeabf6,0x30d72fef,
  0x1f12254d,0xa311a94d,0xaea7adc2,0x329431b6,0x302c30d2,0xb41ab4b7,0xa7a9a11b,0x2ba7251b,0x2dc22f0c,0xb1b6b2f7,0xac79aa63,0x30742e5f,
  0x2a632c79,0xae5fb074,0xaf0cadc2,0x32f731b6,0x211b27a9,0xa51baba7,0xb0d2b02c,0x34b7341a,0x317a3257,0xb552b61a,0xa902a2ad,0x2d0026ad,
  0x2f8c309f,0xb371b487,0xaddcac2e,0x31cf3029,0x2c2e2ddc,0xb029b1cf,0xb09faf8c,0x34873371,0x22ad2902,0xa6adad00,0xb257b17a,0x361a3552,
  0x32cd33e3,0xb682b76f,0xaa31a420,0x2e2d281f,0x30ac31bb,0xb493b58d,0xaf3fad2a,0x33283122,0x2d2a2f3f,0xb122b328,0xb1bbb0ac,0x358d3493,
  0x24202a31,0xa81fae2d,0xb3e3b2cd,0x376f3682,0x341334bc,0xb7a6b85a,0xab5fa4e9,0x2f5928e8,0x319432da,0xb56ab68d,0xb052ae28,0x343e3219,
  0x2e283052,0xb219b43e,0xb2dab194,0x368d356a,0x24e92b5f,0xa8e8af59,0xb4bcb413,0x385a37a6,0x34c3358c,0xb85fb8f3,0xac47a5b2,0x304229b1,
  0x327e33fd,0xb63cb785,0xb106af26,0x34e7330f,0x2f263106,0xb30fb4e7,0xb3fdb27e,0x3785363c,0x25b22c47,0xa9b1b042,0xb58cb4c3,0x38f3385f,
  0x35773662,0xb8e5b982,0xacdea67b,0x30d72a7a,0x336b3493,0xb70ab83a,0xb1bbb012,0x358d3402,0x301231bb,0xb402b58d,0xb493b36b,0x383a370a,
  0x267b2cde,0xaa7ab0d7,0xb662b577,0x398238e5,0x36303741,0xb962ba04,0xad76a744,0x316c2b43,0x342e352a,0xb7d2b8ad,0xb271b092,0x3631347b,
  0x30923271,0xb47bb631,0xb52ab42e,0x38ad37d2,0x27442d76,0xab43b16c,0xb741b630,0x3a043962,0x36ee3815,0xb9d6ba7a,0xae0ea807,0x32012c06,
  0x34a735c4,0xb84ab91b,0xb329b113,0x36d234f3,0x31133329,0xb4f3b6d2,0xb5c4b4a7,0x391b384a,0x28072e0e,0xac06b201,0xb815b6ee,0x3a7a39d6,
  0x37b4388e,0xba41bae1,0xaea7a86b,0x32942c6a,0x35233662,0xb8a8b982,0xb3e3b194,0x376f356a,0x319433e3,0xb56ab76f,0xb662b523,0x398238a8,
  0x286b2ea7,0xac6ab294,0xb88eb7b4,0x3ae13a41,0x3841390f,0xbaa2bb3a,0xaf3fa8d0,0x33282cce,0x35a13705,0xb902b9e3,0xb44fb216,0x380535df,
  0x3216344f,0xb5dfb805,0xb705b5a1,0x39e33902,0x28d02f3f,0xacceb328,0xb90fb841,0x3b3a3aa2,0x38ac3997,0xbaf7bb83,0xafd8a935,0x33ba2d33,
  0x362137ac,0xb958ba3d,0xb4aeb298,0x38503654,0x329834ae,0xb654b850,0xb7acb621,0x3a3d3958,0x29352fd8,0xad33b3ba,0xb997b8ac,0x3b833af7,
  0x391c3a28,0xbb42bbbc,0xb039a999,0x34262d97,0x36a4382d,0xb9aaba90,0xb50eb31c,0x389936c6,0x331c350e,0xb6c6b899,0xb82db6a4,0x3a9039aa,
  0x29993039,0xad97b426,0xba28b91c,0x3bbc3b42,0x39923ac3,0xbb81bbe3,0xb085a9fe,0x346f2dfb,0x372a3886,0xb9f8badb,0xb570b3a0,0x38e03737,
  0x33a03570,0xb737b8e0,0xb886b72a,0x3adb39f8,0x29fe3085,0xadfbb46f,0xbac3b992,0x3be33b81,0xb9cfbb16,0x3b9c3bf1,0x30ac2a31,0xb493ae2d,
  0xb76fb8b4,0x3a1d3afe,0x35a133e3,0xb902b76f,0xb3e3b5a1,0x376f3902,0x38b4376f,0xbafeba1d,0xaa31b0ac,0x2e2d3493,0x3b1639cf,0xbbf1bb9c,
  0xb956ba74,0x3b633bd2,0x305f29cc,0xb44badc9,0xb6e7b859,0x39d23ab6,0x353f335e,0xb8bcb6ff,0xb35eb53f,0x36ff38bc,0x385936e7,0xbab6b9d2,
  0xa9ccb05f,0x2dc9344b,0x3a743956,0xbbd2bb63,0xb8e3b9de,0x3b1e3ba1,0x30122967,0xb402ad65,0xb662b801,0x39823a67,0x34de32da,0xb874b68d,
  0xb2dab4de,0x368d3874,0x38013662,0xba67b982,0xa967b012,0x2d653402,0x39de38e3,0xbba1bb1e,0xb876b952,0x3ace3b60,0x2f8c2902,0xb371ad00,
  0xb5e1b758,0x392e3a11,0x347e3257,0xb82ab61a,0xb257b47e,0x361a382a,0x375835e1,0xba11b92e,0xa902af8c,0x2d003371,0x39523876,0xbb60bace,
  0xb80db8ce,0x3a733b10,0x2ef3289e,0xb2deac9c,0xb562b6b3,0x38d639b3,0x342031d5,0xb7bdb5a5,0xb1d5b420,0x35a537bd,0x36b33562,0xb9b3b8d6,
  0xa89eaef3,0x2c9c32de,0x38ce380d,0xbb10ba73,0xb750b851,0x3a0d3ab0,0x2e5a2839,0xb24bac38,0xb4e5b613,0x387a394f,0x33863153,0xb721b52f,
  0xb153b386,0x352f3721,0x361334e5,0xb94fb87a,0xa839ae5a,0x2c38324b,0x38513750,0xbab0ba0d,0xb68eb7b4,0x399d3a41,0x2dc227a9,0xb1b6aba7,
  0xb46ab577,0x381a38e5,0x32cd30d2,0xb682b4b7,0xb0d2b2cd,0x34b73682,0x3577346a,0xb8e5b81a,0xa7a9adc2,0x2ba731b6,0x37b4368e,0xba41b99d,
  0xb5d2b6d1,0x392439c5,0x2d2a26e0,0xb122aade,0xb3e3b4de,0x376f3874,0x32163052,0xb5dfb43e,0xb052b216,0x343e35df,0x34de33e3,0xb874b76f,
  0xa6e0ad2a,0x2ade3122,0x36d135d2,0xb9c5b924,0xb51cb5f6,0x38a3393c,0x2c932617,0xb08daa16,0xb2f4b448,0x36a437fe,0x31602fa5,0xb53ab389,
  0xafa5b160,0x3389353a,0x344832f4,0xb7feb6a4,0xa617ac93,0x2a16308d,0x35f6351c,0xb93cb8a3,0xb46ab523,0x381a38a8,0x2bf6254d,0xafefa94d,
  0xb209b36b,0x35d4370a,0x30ac2ea7,0xb493b294,0xaea7b0ac,0x32943493,0x336b3209,0xb70ab5d4,0xa54dabf6,0x294d2fef,0x3523346a,0xb8a8b81a,
  0xb378b456,0x3715380a,0x2ac82484,0xaec3a884,0xb120b24a,0x34ff360e,0x2ff22da9,0xb3d3b19e,0xada9aff2,0x319e33d3,0x324a3120,0xb60eb4ff,
  0xa484aac8,0x28842ec3,0x34563378,0xb80ab715,0xb223b31c,0x35eb36c6,0x29992376,0xad97a776,0xb039b12d,0x3426350b,0x2e8d2cac,0xb27cb0a6,
  0xacacae8d,0x30a6327c,0x312d3039,0xb50bb426,0xa376a999,0x27762d97,0x331c3223,0xb6c6b5eb,0xb0d2b194,0x34b7356a,0x286b21e4,0xac6aa5e4,
  0xaea7b012,0x32943402,0x2d2a2b5f,0xb122af59,0xab5fad2a,0x2f593122,0x30122ea7,0xb402b294,0xa1e4a86b,0x25e42c6a,0x319430d2,0xb56ab4b7,
  0xaf0cb012,0x32f73402,0x267b2052,0xaa7aa452,0xacdeadf5,0x30d731e8,0x2b912967,0xaf8bad65,0xa967ab91,0x2d652f8b,0x2df52cde,0xb1e8b0d7,
  0xa052a67b,0x24522a7a,0x30122f0c,0xb402b2f7,0xac79ad2a,0x30743122,0x24201d7f,0xa81fa17f,0xaa31ab91,0x2e2d2f8b,0x28d026e0,0xacceaade,
  0xa6e0a8d0,0x2ade2cce,0x2b912a31,0xaf8bae2d,0x9d7fa420,0x217f281f,0x2d2a2c79,0xb122b074,0xa7a9a86b,0x2ba72c6a,0x1f1218b6,0xa3119cb6,
  0xa54da67b,0x294d2a7a,0x242021e4,0xa81fa5e4,0xa1e4a420,0x25e4281f,0x267b254d,0xaa7aa94d,0x98b69f12,0x1cb62311,0x286b27a9,0xac6aaba7,
  0xa5e43bff,0xb61a3b65,0xb98239cd,0xbb3a36dd,0xaf593bf2,0xb76f3b16,0xba043946,0xbb833581,0xb2943bd4,0xb85a3ab6,0xba7a38b2,0xbbbc341a,
  0xb4b73ba5,0xb8f33a49,0xbae13815,0xbbe33153,0xac9c3bfb,0xbb87356a,0xb986b9c9,0x361abb65,0xb5a53b7c,0xbbfd2b43,0xb74ebb1e,0x3907ba39,
  0xb8d63a60,0xbbc9b359,0xb1e8bbdd,0x3a97b889,0xba7338bc,0xbaf1b7f3,0x2e91bbf5,0x3b9cb4f3,0xafbd3bf1,0xbb10b785,0x3a0db93c,0x356a3b87,
  0xb88e3a93,0xb87fba9e,0x3bcbb340,0xb0743bec,0xbb183764,0xaf27bbf3,0x3bbd340e,0xb8ad3a7e,0xbc009cb6,0x35d4bb73,0x39e73966,0xbb2a3721,
  0xb16c3be2,0xb3d3bbc2,0x38ee3a4d,0xbb10b785,0xba043946,0x36bbbb42,0xa4523c00,0xb63cbb5e,0xbbfe28e8,0x3b2fb70a,0xb9243a21,0x346fbbb0,
  0xba67b8cc,0x3bcc3328,0xbbda3219,0x3a90b894,0xb2f73bcf,0x386fbaa9,0xba89389e,0x3bc2b3d3,0xbb1e374e,0x3bf5aec3,0xbbbab426,0x3a7638b7,
  0xbb5cb648,0x39bc3994,0xb6afbb45,0x2c063bfc,0xb493bbab,0xad003bfa,0x36e8bb37,0xb9d2397d,0xb43e3bb7,0x3be9b0be,0xb84abac1,0xb86f3aa9,
  0xbbcb3340,0x38d13a64,0x37c8bafe,0xbbf8adc9,0xb94fb9fc,0xb6a43b47,0x3c00217f,0xb654bb59,0x3576bb85,0xbbfb2c6a,0x377a3b13,0x38f3ba49,
  0xb4ff3b9a,0x3a313911,0x3af4b7e8,0xb0bebbe9,0xbc00a452,0xb6023b6a,0x39d63979,0x3b35b6f4,0xb47bbbae,0xbbf9ad65,0xb6ff3b32,0x397439da,
  0x3aacb86a,0xb2debbd0,0xbbe8b0d7,0xb7f33af1,0xb5bc3b78,0x2a7a3bfd,0x37373b24,0x3a313911,0xbbbab426,0xbbe730f0,0xbaba3855,0xb8653ab0,
  0x3109bbe6,0xb41abbbc,0xb902ba3d,0xbb1bb759,0x3bfd2ade,0x3b7ab5b1,0x39afb9a1,0x35d4bb73,0xb6763b52,0xb9a639aa,0xbb4f3682,0xbbfd2a7a,
  0xbafeb7c8,0xb91fba25,0xb523bb94,0x294dbbfe,0x3884ba9b,0x3a97b889,0x3bc8b371,0x3bee3042,0x3a29391b,0x37d23afb,0x308d3beb,0xb3283bcc,
  0xb72c3b27,0xbbfeaa16,0xb5c8bb76,0x39a6b9aa,0xb9d6b979,0x3546bb8e,0x3bf9ad33,0x37a63b07,0x3ae8b80a,0x3a7e38ad,0xb2943bd4,0xbbd332ad,
  0x33a23bc5,0xba5438e5,0xbb0ab79b,0x2d00bbfa,0xb7dd3af7,0xb916ba2d,0x3b98b50b,0xaa163bfe,0xb855baba,0x3bd6b27c,0xb13b3be4,0xbae5b80f,
  0x3bf8ad97,0xb46f3bb0,0xba60b8d6,0x3aceb835,0xb6313b60,0xb9c5b98b,0x3b3fb6c6,0x2c6a3bfb,0xb8453ac4,0x30a6bbea,0x344b3bb5,0xb916ba2d,
  0xb523bb94,0x396b39e3,0xbb57b65f,0x3c009fdb,0x3b81358d,0xbbfc2c06,0x3b18b764,0xb8fd3a41,0xbae13815,0x38a3ba85,0xb2633bd7,0xb2debbd0,
  0xb8993a8c,0x3aa5b874,0xbbce330f,0x3bea30a6,0xad33bbf9,0xb4873bac,0x38e0ba58,0xbad5382a,0x399939b8,0xb654bb59,0x28e83bfe,0x352fbb92,
  0xbbf5ae91,0x3b213742,0xb958b9f4,0x35b13b7a,0xb8ea3a50,0x3bc333ba,0xb185bbe1,0xbaa53874,0x313bbbe4,0xbbbf3402,0x38f83a45,0x376fbb16,
  0x353a3b90,0x39dab974,0xbb5cb648,0x23113c00,0xb9e7b966,0xb5173b96,0x3bf7adfb,0xb7d2bafb,0xb9373a11,0x37903b0d,0x3bf0afef,0x33babbc3,
  0x365fbb57,0xb9b3b99d,0xbb4a3699,0x2b433bfd,0xaef53bf4,0x3b1b3759,0x39fcb94f,0xb599bb7f,0xb219bbda,0xbbe0b19e,0xb8253ad8,0x38e53a54,
  0xb98239cd,0xb55e3b89,0x2cce3bfa,0x37903b0d,0x38e0ba58,0x3389bbc6,0xb1b6bbdf,0xb87fba9e,0xb8303ad1,0xb0423bee,0x347b3bae,0x39293a1d,
  0x36e8bb37,0x2776bbff,0xb60ebb68,0xb9c5b98b,0xb9c93986,0xbb633625,0xbbff26ad,0xbb89b55e,0x3a45b8f8,0x3ba3b4c3,0x3bfc2c38,0x3b4236bb,
  0xbab3385f,0xbbd332ad,0xbbe6b109,0xbaebb805,0x3b13b77a,0x3bf2af8b,0x3bc033eb,0x3a8538a3,0xba0d393c,0xbb3db6d2,0x25e4bbff,0x3b63b625,
  0x3b4ab699,0x39f83954,0xb4e73b9e,0xbbf52ec3,0xbbed305b,0xb835bace,0x3884ba9b,0x3bde31cf,0x3be830d7,0x34323bb8,0xba35390c,0xbb21b742,
  0xba4d38ee,0xb4abbba7,0x3bfb2c9c,0xb6d23b3d,0x3bdfb1b6,0xb2013bdc,0xbacbb83a,0x3a64b8d1,0xbba1b4cf,0x38fdba41,0x380a3ae8,0xbbe53122,
  0x39a139af,0xbb54366b,0xa9b1bbfe,0x3b963517,0xba89389e,0x381abade,0xafbd3bf1,0xb4abbba7,0x3bfc2c38,0xbb833581,0x39c0b990,0xb6023b6a,
  0xb9dfb970,0x3b92352f,0xbbf82d97,0x3b01b7bd,0x308d3beb,0xb840bac7,0x3aa2387a,0xbbe0b19e,0xbac1384a,0x3bd8b24b,0xbbe2b16c,0x3ade381a,
  0x3b9e34e7,0xba39b907,0x37fe3aee,0xb0f0bbe7,0xb5f7bb6c,0x23113c00,0x358dbb81,0xb94a3a00,0xb79b3b0a,0x3a15b933,0xbb8b3552,0x3bff2776,
  0xbaf437e8,0x3a6f38c1,0x32f7bbcf,0xbbd8324b,0x3acb383a,0x3074bbec,0xbbb23463,0x391f3a25,0x2ba7bbfc,0xbb7f3599,0x399939b8,0x35ebbb6f,
  0xbb3f36c6,0x3a093941,0x34b7bba5,0xbbf22f8b,0xbb243737,0x2e5f3bf6,0x3bb7343e,0x38c1ba6f,0x399039c0,0x3b5eb63c,0xa81fbbff,0xbb8eb546,
  0x37b2bb04,0xb929ba1d,0xbb90353a,0xa8843bff,0xbbd7b263,0xb8503abd,0x38bc3a73,0x3bb8b432,0xbb4f3682,0xb95d39f0,0xb4ff3b9a,0x2e5f3bf6,
  0x37fe3aee,0x3a7638b7,0x3bd232c6,0x3bd6b27c,0x3a7ab8b2,0x3805baeb,0x2ef5bbf4,0xb4dbbb9f,0xb958b9f4,0xbb4cb68d,0xbc009cb6,0xbb54366b,
  0xbb7635c8,0xbc001648,0xbb78b5bc,0xb9f0b95d,0x34633bb2,0xadc93bf8,0xb7153b2c,0xb9e3396b,0x3bddb1e8,0x3bde31cf,0x3ad13830,0x38db3a5c,
  0xadfbbbf7,0x3457bbb3,0x38ccba67,0x3ac7b840,0xbb98350b,0xb962b9eb,0x3676bb52,0x3c009648,0x281f3bff,0xbb3536f4,0xba19b92e,0x3487bbac,
  0x3bbd340e,0x31223be5,0xbab3385f,0xbab6b85a,0x3825bad8,0x3bef3010,0x34933bab,0xba153933,0xbbb5344b,0x2e2dbbf6,0x3b27372c,0xb9eb3962,
  0xb2c63bd2,0xbab0b865,0x3a81b8a8,0x34023bbf,0x3a213924,0xbb0137bd,0xb05bbbed,0x3bc93359,0x3b68b60e,0x251b3c00,0xbb85b576,0x3941ba09,
  0xbbce330f,0x3a6bb8c7,0xb7dd3af7,0x2e2dbbf6,0xb7153b2c,0x294dbbfe,0x35df3b71,0xb9b3b99d,0x36af3b45,0xba00b94a,0x3ba134cf,0xbbf32f27,
  0x3bc033eb,0xbbe33153,0x3aacb86a,0xb8503abd,0xbbe13185,0x3bd93232,0xbac4b845,0x38c73a6b,0xb92e3a19,0x3b07b7a6,0xbbef3029,0x3bc63389,
  0xa17f3c00,0x35ebbb6f,0xb97039df,0x3b2fb70a,0x390c3a35,0xb4f3bb9c,0xaade3bfd,0x368dbb4c,0xbbf02fef,0x38203adb,0x3899ba8c,0xbbd9b232,
  0xba8138a8,0x3ae5380f,0x2f59bbf2,0xbba334c3,0xb6ff3b32,0x3bff2884,0xb5f7bb6c,0xb99439bc,0x29b13bfe,0x3b2ab721,0xba29b91b,0xb4573bb3,
  0xbbfa2cce,0xb49f3ba9,0x3a5038ea,0x3adbb820,0xbb7135df,0x1fdb3c00,0x3b7c35a5,0x3954b9f8,0xba3d3902,0x34db3b9f,0x3bfc2ba7,0x36a4bb47,
  0xb87a3aa2,0x38943a90,0x3bc5b3a2,0x3010bbef,0xbbff26ad,0xbb3a36dd,0xb9373a11,0xb49f3ba9,0xbbef3029,0xbad5382a,0xb88e3a93,0xb2013bdc,
  0xbbc83371,0xba5c38db,0xb7b23b04,0xad653bf9,0xbb8b3552,0xb9d2397d,0xb6313b60,0x251b3c00,0x3bf12fbd,0x3b103785,0x393c3a0d,0x356a3b87,
  0x3bd232c6,0x3ab03865,0x38a83a81,0x34023bbf,0x3ba134cf,0x3a4138fd,0x380a3ae8,0x31223be5,0x3b603631,0x39c5398b,0x36c63b3f,0x2c6a3bfb,
  0xbbe2b16c,0xb3d3bbc2,0x3a4db8ee,0x3b103785,0xbb2cb715,0x294dbbfe,0x3b71b5df,0x39b3399d,0xb9dfb970,0x352fbb92,0x3bf8ad97,0x37bd3b01,
  0xb815bae1,0x38a3ba85,0x3bd73263,0x32de3bd0,0x3bcf32f7,0xb86f3aa9,0xb89eba89,0x3bc2b3d3,0x3a19392e,0xbb0737a6,0xb029bbef,0x3bc63389,
  0x35f73b6c,0xbc002311,0x358dbb81,0x3a00394a,0xae913bf5,0xbb21b742,0x39f4b958,0x35b13b7a,0xbbb7b43e,0x3be9b0be,0xbac1384a,0x386fbaa9,
  0xb8a8ba81,0x3ae5380f,0xbbf2af59,0x3ba3b4c3,0x2ba7bbfc,0x35993b7f,0xb999b9b8,0x3b6f35eb,0x3966b9e7,0xb5173b96,0xadfbbbf7,0x37d23afb,
  0x3b9a34ff,0xba31b911,0x37e83af4,0xb0bebbe9,0x35df3b71,0x9fdbbc00,0xb5a53b7c,0x3954b9f8,0xb7b23b04,0x3a1db929,0xbb90353a,0x3bff2884,
  0xbbda3219,0x3be0319e,0xbad8b825,0x38e53a54,0xbb78b5bc,0x2a7a3bfd,0x3b24b737,0xba31b911,0xb029bbef,0xbad5382a,0x3a93388e,0x3201bbdc,
  0x3a7ab8b2,0xbaebb805,0xaef53bf4,0x3b9fb4db,0x3b3736e8,0x2776bbff,0xbb68360e,0x39c5398b,0x3b523676,0x39a6b9aa,0xb682bb4f,0xbbfd2a7a,
  0xaf593bf2,0x3b16376f,0x3a04b946,0xb581bb83,0xbbdd31e8,0xb1cf3bde,0x3ad13830,0x3a5cb8db,0xb77abb13,0xbbf22f8b,0xb3eb3bc0,0x3a8538a3,
  0xbb27b72c,0xbbfeaa16,0xbb7635c8,0xb9a639aa,0x35a5bb7c,0xab43bbfd,0xb74ebb1e,0xba39b907,0x3bbd340e,0x3be5b122,0x3ab3b85f,0x385abab6,
  0xb0d73be8,0x34323bb8,0x390c3a35,0x3b213742,0x3af737dd,0x39163a2d,0x350b3b98,0xaa163bfe,0xb88e3a93,0xba9e387f,0xbbcb3340,0xbbecb074,
  0xba21b924,0xb7bdbb01,0xb05bbbed,0x3359bbc9,0x39afb9a1,0x3b54b66b,0x3bfea9b1,0x3b963517,0xbac4b845,0x30a6bbea,0x3bb5b44b,0x39163a2d,
  0x3a04b946,0x3b4236bb,0xa4523c00,0xbb5e363c,0x36af3b45,0xb94a3a00,0xbba1b4cf,0xaf27bbf3,0xbbeb308d,0xb840bac7,0x387abaa2,0x3be0319e,
  0x3a8c3899,0xbaa53874,0xb30fbbce,0x3bea30a6,0xbb1e374e,0xaec3bbf5,0x3bba3426,0xb8b73a76,0x217fbc00,0x3b6f35eb,0xb97039df,0xb70abb2f,
  0x3b0a379b,0xba153933,0xb552bb8b,0x3bff2776,0xba50b8ea,0x3bc333ba,0xbbe13185,0x3aa5b874,0x3bcbb340,0xba6438d1,0x37c8bafe,0xadc93bf8,
  0xb6ff3b32,0x2884bbff,0x35f73b6c,0xb9bcb994,0xb6c6bb3f,0x3a093941,0xbba5b4b7,0x3bf2af8b,0x3a113937,0xb790bb0d,0x2fef3bf0,0x33babbc3,
  0xbc00a452,0x3b6a3602,0xb9d6b979,0x36f43b35,0x3a3db902,0xbb9f34db,0x3bfc2ba7,0xbb47b6a4,0xb2633bd7,0x3850babd,0xba7338bc,0x3bb8b432,
  0xb9cdb982,0xb55e3b89,0x3bfaacce,0xb790bb0d,0x3bba3426,0xb0f0bbe7,0xbaba3855,0x3ab03865,0xbbc83371,0x38db3a5c,0x37b2bb04,0xbbf9ad65,
  0x39f4b958,0xbb4cb68d,0x9cb63c00,0x3b54b66b,0x398639c9,0x3b63b625,0xa6adbbff,0xbb89b55e,0xbafeb7c8,0xba25391f,0x35233b94,0x3bfe294d,
  0x3bd43294,0x385abab6,0xb8b2ba7a,0xbbbc341a,0xbbf72dfb,0xb4573bb3,0x3a6738cc,0x3ac7b840,0xb93cba0d,0xbb3db6d2,0xbbffa5e4,0xbb633625,
  0x39d63979,0x3b8e3546,0x3bf9ad33,0x3b07b7a6,0xba60b8d6,0xbbc9b359,0xbbdd31e8,0xba973889,0x3ad83825,0x3bef3010,0x3babb493,0x3a15b933,
  0x38ee3a4d,0x34ab3ba7,0xac9c3bfb,0xb6d23b3d,0xb855baba,0xb27cbbd6,0x313bbbe4,0x380fbae5,0x37643b18,0x2f273bf3,0xb40e3bbd,0xb8ad3a7e,
  0xb60ebb68,0xa51bbc00,0x3576bb85,0x3941ba09,0xb89eba89,0x381abade,0x3bf12fbd,0x34ab3ba7,0x35233b94,0xb9e3396b,0xbb57b65f,0x9fdbbc00,
  0xa8e8bbfe,0x3b2fb70a,0x3a213924,0xb46f3bb0,0xb3eb3bc0,0xbbe33153,0xb86abaac,0x3850babd,0x384a3ac1,0xbbd8324b,0x316cbbe2,0x3ade381a,
  0xad33bbf9,0x3bac3487,0xb8e03a58,0xb82abad5,0xb6483b5c,0xb9bcb994,0x3b45b6af,0x2c063bfc,0x3a35b90c,0x34f33b9c,0xbbfdaade,0x368dbb4c,
  0xb7e8baf4,0x3a6f38c1,0xbbcfb2f7,0x3bd8b24b,0xb13b3be4,0xb402bbbf,0x38f83a45,0xbb16b76f,0x39fcb94f,0xb6a43b47,0x217fbc00,0x36543b59,
  0xbbfe29b1,0x3b2ab721,0xb91b3a29,0x3457bbb3,0x37373b24,0xae5fbbf6,0xb43e3bb7,0x38c1ba6f,0x365fbb57,0xb99d39b3,0x3b4ab699,0xbbfd2b43,
  0xbbae347b,0x3bf92d65,0xbb32b6ff,0x397439da,0x3aa2387a,0xb894ba90,0x33a23bc5,0x3010bbef,0xb682bb4f,0xb95d39f0,0x3b9a34ff,0xae5fbbf6,
  0xb8e03a58,0x3bc63389,0xb1b6bbdf,0xba9e387f,0x3be63109,0xb41abbbc,0xba3d3902,0x3b1b3759,0xb552bb8b,0xb9d2397d,0x3b603631,0xa51bbc00,
  0x35c83b76,0x3c009648,0x35bcbb78,0xb9f0b95d,0x3a45b8f8,0xb4c3bba3,0xbbfcac38,0xb6bb3b42,0xba9bb884,0xba973889,0x33713bc8,0x3bee3042,
  0xb4b73ba5,0x3a4938f3,0x3ae1b815,0xb153bbe3,0xb50bbb98,0xb962b9eb,0xbb52b676,0xbc001648,0xbb4a3699,0xb95439f8,0xb4e73b9e,0x2ec33bf5,
  0x380a3ae8,0x3a7e38ad,0x3bd43294,0x3bd3b2ad,0x3a73b8bc,0x37f3baf1,0x2e91bbf5,0xb4f3bb9c,0x344b3bb5,0xae2d3bf6,0xb72c3b27,0xb9eb3962,
  0x3bdfb1b6,0x3bdc3201,0x3acb383a,0x38d13a64,0xad97bbf8,0x346fbbb0,0x38d6ba60,0x3aceb835,0xbc009cb6,0xbb73b5d4,0xb9e7b966,0xb721bb2a,
  0xb30fbbce,0x3a6bb8c7,0x3af737dd,0xae2d3bf6,0xbbfcac38,0xb581bb83,0x39c0b990,0x3b6a3602,0xb58d3b81,0xbbfc2c06,0xb764bb18,0x38fdba41,
  0x3a6738cc,0xb3283bcc,0xbbda3219,0xb894ba90,0x31853be1,0xbbd9b232,0x3845bac4,0x38c73a6b,0x3b9e34e7,0xb9073a39,0xb7febaee,0x3be7b0f0,
  0x39b8b999,0x36543b59,0xbbfe28e8,0x352fbb92,0xb493bbab,0x3bfa2d00,0xb6e83b37,0xb97db9d2,0xafefbbf0,0x38203adb,0xba8cb899,0x3bd93232,
  0xbacbb83a,0x3bec3074,0xbbb23463,0x3a25b91f,0xbb90353a,0x39dab974,0xb6483b5c,0xa311bc00,0xb5763b85,0xac6abbfb,0x377a3b13,0xba49b8f3,
  0x2cce3bfa,0x349fbba9,0xb8ea3a50,0x3adbb820,0x399039c0,0xb63cbb5e,0x281f3bff,0x3546bb8e,0x3bf42ef5,0xbb1bb759,0x394f39fc,0xb599bb7f,
  0x3aacb86a,0xbbd032de,0x3be830d7,0xbaf1b7f3,0xa6adbbff,0xbb3a36dd,0x3a113937,0x349fbba9,0xb7febaee,0xb8b73a76,0x3bd232c6,0xb27cbbd6,
  0xbad1b830,0xb0423bee,0x3baeb47b,0xb929ba1d,0xbbfdaade,0x35b13b7a,0x39afb9a1,0xbb73b5d4,0xa5e43bff,0x3b65361a,0x3982b9cd,0xb6ddbb3a,
  0x34633bb2,0x3bf82dc9,0x3715bb2c,0xb96bb9e3,0x385f3ab3,0x3bd3b2ad,0x3109bbe6,0xbaebb805,0x3a29391b,0x3afbb7d2,0xb08dbbeb,0xbbccb328,
  0x2c9cbbfb,0xb56abb87,0xb986b9c9,0xbb65b61a,0xa81fbbff,0xb6f4bb35,0xba19b92e,0xbbacb487,0xb05bbbed,0xb835bace,0xba9bb884,0xbbdeb1cf,
  0xb3a2bbc5,0xb8e5ba54,0xbb0ab79b,0xbbfaad00,0x00000000,0x00000000,0x00000000,0x00000000,0xaa1f0000,0xaf64ada8,0xaf64b000,0xaa1fada8,
  0xada80000,0xada8b000,0x2da88000,0x2da83000,0xaf640000,0x2a1fada8,0x2a1f3000,0xaf64ada8,0xb0000000,0x30008000,0xb0000000,0x30008000,
  0xaf640000,0x2a1f2da8,0x2a1fb000,0xaf642da8,0xada80000,0xada83000,0x2da88000,0x2da8b000,0xaa1f0000,0xaf642da8,0xaf643000,0xaa1f2da8,
  0x00000000,0x00000000,0x00000000,0x00000000,0x2a1f8000,0x2f642da8,0x2f643000,0x2a1f2da8,0xada80000,0xada8b000,0x2da88000,0x2da83000,
  0x2f648000,0xaa1f2da8,0xaa1fb000,0x2f642da8,0xb0000000,0x30008000,0xb0000000,0x30008000,0x2f648000,0xaa1fada8,0xaa1f3000,0x2f64ada8,
  0xada80000,0xada83000,0x2da88000,0x2da8b000,0x2a1f8000,0x2f64ada8,0x2f64b000,0x2a1fada8,0x80000000,0x80000000,0x80000000,0x80000000,
  0x2a1f0000,0x2f64ada8,0x2f64b000,0x2a1fada8,0x2da80000,0x2da8b000,0xada88000,0xada83000,0x2f640000,0xaa1fada8,0xaa1f3000,0x2f64ada8,
  0x30000000,0xb0008000,0x30000000,0xb0008000,0x2f640000,0xaa1f2da8,0xaa1fb000,0x2f642da8,0x2da80000,0x2da83000,0xada88000,0xada8b000,
  0x2a1f0000,0x2f642da8,0x2f643000,0x2a1f2da8,0x80000000,0x80000000,0x80000000,0x80000000,0xaa1f8000,0xaf642da8,0xaf643000,0xaa1f2da8,
  0x2da80000,0x2da8b000,0xada88000,0xada83000,0xaf648000,0x2a1f2da8,0x2a1fb000,0xaf642da8,0x30000000,0xb0008000,0x30000000,0xb0008000,
  0xaf648000,0x2a1fada8,0x2a1f3000,0xaf64ada8,0x2da80000,0x2da83000,0xada88000,0xada8b000,0xaa1f8000,0xaf64ada8,0xaf64b000,0xaa1fada8,
  0x30003000,0x30003000,0x30003000,0x30003000,0x2f643000,0x2a1f2da8,0xaa1f0000,0xaf64ada8,0x2da83000,0xada80000,0xada8b000,0x2da88000,
  0x2a1f3000,0xaf64ada8,0x2f648000,0xaa1f2da8,0x00003000,0x8000b000,0x00003000,0x8000b000,0xaa1f3000,0x2f64ada8,0xaf640000,0x2a1f2da8,
  0xada83000,0x2da88000,0x2da8b000,0xada80000,0xaf643000,0xaa1f2da8,0x2a1f8000,0x2f64ada8,0x30003000,0x30003000,0x30003000,0x30003000,
  0xaf64b000,0xaa1fada8,0x2a1f8000,0x2f642da8,0x2da83000,0xada80000,0xada8b000,0x2da88000,0xaa1fb000,0x2f642da8,0xaf640000,0x2a1fada8,
  0x00003000,0x8000b000,0x00003000,0x8000b000,0x2a1fb000,0xaf642da8,0x2f648000,0xaa1fada8,0xada83000,0x2da88000,0x2da8b000,0xada80000,
  0x2f64b000,0x2a1fada8,0xaa1f0000,0xaf642da8,0xb0003000,0xb0003000,0xb0003000,0xb0003000,0xaf643000,0xaa1f2da8,0x2a1f0000,0x2f64ada8,
  0xada83000,0x2da80000,0x2da8b000,0xada88000,0xaa1f3000,0x2f64ada8,0xaf648000,0x2a1f2da8,0x80003000,0x0000b000,0x80003000,0x0000b000,
  0x2a1f3000,0xaf64ada8,0x2f640000,0xaa1f2da8,0x2da83000,0xada88000,0xada8b000,0x2da80000,0x2f643000,0x2a1f2da8,0xaa1f8000,0xaf64ada8,
  0xb0003000,0xb0003000,0xb0003000,0xb0003000,0x2f64b000,0x2a1fada8,0xaa1f8000,0xaf642da8,0xada83000,0x2da80000,0x2da8b000,0xada88000,
  0x2a1fb000,0xaf642da8,0x2f640000,0xaa1fada8,0x80003000,0x0000b000,0x80003000,0x0000b000,0xaa1fb000,0x2f642da8,0xaf648000,0x2a1fada8,
  0x2da83000,0xada88000,0xada8b000,0x2da80000,0xaf64b000,0xaa1fada8,0x2a1f0000,0x2f642da8,0x80008000,0x80008000,0x80008000,0x80008000,
  0x2a1f8000,0x2f642da8,0x2f643000,0x2a1f2da8,0x2da88000,0x2da83000,0xada80000,0xada8b000,0x2f648000,0xaa1f2da8,0xaa1fb000,0x2f642da8,
  0x30008000,0xb0000000,0x30008000,0xb0000000,0x2f648000,0xaa1fada8,0xaa1f3000,0x2f64ada8,0x2da88000,0x2da8b000,0xada80000,0xada83000,
  0x2a1f8000,0x2f64ada8,0x2f64b000,0x2a1fada8,0x80008000,0x80008000,0x80008000,0x80008000,0xaa1f0000,0xaf64ada8,0xaf64b000,0xaa1fada8,
  0x2da88000,0x2da83000,0xada80000,0xada8b000,0xaf640000,0x2a1fada8,0x2a1f3000,0xaf64ada8,0x30008000,0xb0000000,0x30008000,0xb0000000,
  0xaf640000,0x2a1f2da8,0x2a1fb000,0xaf642da8,0x2da88000,0x2da8b000,0xada80000,0xada83000,0xaa1f0000,0xaf642da8,0xaf643000,0xaa1f2da8,
  0x00008000,0x00008000,0x00008000,0x00008000,0xaa1f8000,0xaf642da8,0xaf643000,0xaa1f2da8,0xada88000,0xada83000,0x2da80000,0x2da8b000,
  0xaf648000,0x2a1f2da8,0x2a1fb000,0xaf642da8,0xb0008000,0x30000000,0xb0008000,0x30000000,0xaf648000,0x2a1fada8,0x2a1f3000,0xaf64ada8,
  0xada88000,0xada8b000,0x2da80000,0x2da83000,0xaa1f8000,0xaf64ada8,0xaf64b000,0xaa1fada8,0x00008000,0x00008000,0x00008000,0x00008000,
  0x2a1f0000,0x2f64ada8,0x2f64b000,0x2a1fada8,0xada88000,0xada83000,0x2da80000,0x2da8b000,0x2f640000,0xaa1fada8,0xaa1f3000,0x2f64ada8,
  0xb0008000,0x30000000,0xb0008000,0x30000000,0x2f640000,0xaa1f2da8,0xaa1fb000,0x2f642da8,0xada88000,0xada8b000,0x2da80000,0x2da83000,
  0x2a1f0000,0x2f642da8,0x2f643000,0x2a1f2da8,
};

constexpr int kThreads = 384;
constexpr int kCtas = 128;

#define PREP0 1600
#define PREPGAP 650
#define HT0 13800
#define HGAP 500
#define WQT 11800
#define QT 17800
#define QGAP 400
#define POSTGAP 1000
constexpr int EARLY = 2, L0 = 2, TAIL = 3;

constexpr int NS1 = 6;
__host__ __device__ constexpr int slot1(int it) { return (it + 4) % NS1; }
__host__ __device__ constexpr uint32_t w1_off(int s) { return (1 + s + (s >> 1)) * 16384; }
__host__ __device__ constexpr uint32_t x1_off(int it) { return ((it >> 1) & 3) * 49152; }
constexpr uint32_t ST2 = 32768;
constexpr uint32_t RA = 131072;
constexpr uint32_t RB = 163840;
constexpr uint32_t RU = 196608;
constexpr uint32_t Y_IN = RU;
constexpr uint32_t SM_ONES = 229376;
constexpr uint32_t SM_F2 = SM_ONES + 128;
constexpr uint32_t SM_BAR = 231424;
constexpr uint32_t SM_SCALE = SM_ONES + 1792;
constexpr uint32_t SM_MAX = SM_BAR + 512;
constexpr uint32_t SM_TOTAL = 232448;
constexpr uint32_t SM_BASE = 1024;
__host__ __device__ constexpr uint32_t kv_off(int h) { return RB + (h >> 1) * 16384 + (h & 1) * 2560; }

enum Bar { B_F1 = 0, B_F2 = 6, B_H = B_F2 + 4, B_KVL = 12, B_RDY = 20, B_Q = 34, B_MAX, B_ZERO, B_U, B_KV,
           B_E1 = 39, B_E2 = 45, B_I2 = B_E2 + 4,
           B_KVE = 51, B_VST, B_KVM, B_KVP, B_KVI, B_OW, B_ZST = 58,
           B_OFREE = 59, B_F2M, B_STG, B_Y, B_COUNT = 64, B_U2 = B_KVL };
__host__ __device__ constexpr int slot2(int n) { return n < 22 ? n & 3 : (0x1032510325ull >> (4 * (n - 22))) & 7; }
__host__ __device__ constexpr int par2(int n) { return n < 22 ? (n >> 2) & 1 : (0x326 >> (n - 22)) & 1; }

constexpr int KV_WORDS = 4096 + 128;
struct Scratch {
  float kv[8][KV_WORDS];
  unsigned kvflag[8 * 32], zflag[8 * 32], oflag[16 * 32], epoch[kCtas];
};
struct Params {
  CUtensorMap w1, x, k, v, w2, wo, o, outa, q, outb;
  const __nv_bfloat16* shift_k;
  const __nv_bfloat16* ssm_k;
  const __nv_bfloat16* ssm_d;
  const __nv_bfloat16* q_ptr;
  const __nv_bfloat16* w_ptr;
  const __nv_bfloat16* wo_ptr;
  uint64_t zero;
  Scratch* g;
  const uint32_t* tab;
};

__device__ __align__(128) Scratch g_scratch;
__device__ __align__(128) __nv_bfloat16 g_o[2048 * 1024];

#define TSTAMP(cond, i) do { } while (0)
#define GSTAMP(cond, i) do { } while (0)
#define KSTAMP(n) do { } while (0)
#define QSTAMP(n) do { } while (0)

#define JIT() do { } while (0)
constexpr int kSpinLimit = 1 << 16;

DEVI void mbar_init(uint32_t a, uint32_t c) { asm volatile("mbarrier.init.shared::cta.b64 [%0], %1;" :: "r"(a), "r"(c) : "memory"); }
DEVI void mbar_expect(uint32_t a, uint32_t b) { asm volatile("mbarrier.arrive.expect_tx.shared::cta.b64 _, [%0], %1;" :: "r"(a), "r"(b) : "memory"); }
DEVI void mbar_arrive(uint32_t a) { asm volatile("mbarrier.arrive.shared::cta.b64 _, [%0];" :: "r"(a) : "memory"); }
DEVI void mbar_arrive_if(uint32_t a, bool pred) {
  asm volatile("{\n.reg .pred p;\nsetp.ne.b32 p, %1, 0;\n@p mbarrier.arrive.shared::cta.b64 _, [%0];\n}" :: "r"(a), "r"((int)pred) : "memory");
}
DEVI void mbar_wait(uint32_t a, uint32_t parity) {
  asm volatile("{\n.reg .pred p;\n.reg .u32 n;\nmov.u32 n, 0;\nW_LOOP:\n"
               "mbarrier.try_wait.parity.shared::cta.b64 p, [%0], %1;\n@p bra W_DONE;\n"
               "add.u32 n, n, 1;\nsetp.lt.u32 p, n, %2;\n@p bra W_LOOP;\nW_DONE:\n}"
               :: "r"(a), "r"(parity), "n"(kSpinLimit) : "memory");
  JIT();
}
DEVI void mbar_wait_long(uint32_t a, uint32_t parity) {
  asm volatile("{\n.reg .pred p;\n.reg .u32 n;\nmov.u32 n, 0;\nW_LOOP:\n"
               "mbarrier.try_wait.parity.shared::cta.b64 p, [%0], %1, %3;\n@p bra W_DONE;\n"
               "add.u32 n, n, 1;\nsetp.lt.u32 p, n, %2;\n@p bra W_LOOP;\nW_DONE:\n}"
               :: "r"(a), "r"(parity), "n"(kSpinLimit), "r"(4000) : "memory");
  JIT();
}
DEVI void flag_wait(const unsigned* p, unsigned target) {
  int n = 0; unsigned v;
  do {
    asm volatile("ld.relaxed.gpu.global.u32 %0, [%1];" : "=r"(v) : "l"(p) : "memory");
  } while ((int)(v - target) < 0 && ++n < kSpinLimit);
  asm volatile("fence.acquire.gpu;" ::: "memory");
}
DEVI unsigned ld_relaxed(const unsigned* p) { unsigned v; asm volatile("ld.relaxed.gpu.global.u32 %0, [%1];" : "=r"(v) : "l"(p) : "memory"); return v; }
DEVI uint32_t clock32() { uint32_t t; asm volatile("mov.u32 %0, %%clock;" : "=r"(t)); return t; }
DEVI void pace(uint32_t t0, uint32_t n) { while (clock32() - t0 < n) __nanosleep(20); }
DEVI bool elect() { uint32_t p; asm volatile("{\n.reg .pred p;\nelect.sync _|p, 0xffffffff;\nselp.u32 %0, 1, 0, p;\n}" : "=r"(p)); return p; }
DEVI void fence_async_smem() { asm volatile("fence.proxy.async.shared::cta;" ::: "memory"); }
DEVI void bar_sync(int id, int n) { asm volatile("bar.sync %0, %1;" :: "r"(id), "r"(n) : "memory"); }
DEVI void cluster_sync() { asm volatile("barrier.cluster.arrive.relaxed.aligned;\nbarrier.cluster.wait.aligned;" ::: "memory"); }
DEVI void wg_fence() { asm volatile("wgmma.fence.sync.aligned;" ::: "memory"); }
DEVI void wg_commit() { asm volatile("wgmma.commit_group.sync.aligned;" ::: "memory"); }
template <int N> DEVI void wg_wait() { asm volatile("wgmma.wait_group.sync.aligned %0;" :: "n"(N) : "memory"); }
template <int N> DEVI void pin(uint32_t* r) {
#pragma unroll
  for (int i = 0; i < N; i++) asm volatile("" : "+r"(r[i]));
}
template <int N> DEVI void pin(float* r) {
#pragma unroll
  for (int i = 0; i < N; i++) asm volatile("" : "+f"(r[i]));
}

DEVI void tma2d(uint32_t dst, const CUtensorMap* m, int c0, int c1, uint32_t bar) {
  asm volatile("cp.async.bulk.tensor.2d.shared::cluster.global.mbarrier::complete_tx::bytes [%0], [%1, {%3, %4}], [%2];"
               :: "r"(dst), "l"(m), "r"(bar), "r"(c0), "r"(c1) : "memory");
}
DEVI void tma2d_mc(uint32_t dst, const CUtensorMap* m, int c0, int c1, uint32_t bar) {
  asm volatile("cp.async.bulk.tensor.2d.shared::cluster.global.mbarrier::complete_tx::bytes.multicast::cluster [%0], [%1, {%3, %4}], [%2], %5;"
               :: "r"(dst), "l"(m), "r"(bar), "r"(c0), "r"(c1), "h"((uint16_t)3) : "memory");
}
DEVI void tma3d(uint32_t dst, const CUtensorMap* m, int c0, int c1, int c2, uint32_t bar) {
  asm volatile("cp.async.bulk.tensor.3d.shared::cluster.global.mbarrier::complete_tx::bytes [%0], [%1, {%3, %4, %5}], [%2];"
               :: "r"(dst), "l"(m), "r"(bar), "r"(c0), "r"(c1), "r"(c2) : "memory");
}
DEVI void tma4d(uint32_t dst, const CUtensorMap* m, int c1, int c2, int c3, uint32_t bar) {
  asm volatile("cp.async.bulk.tensor.4d.shared::cluster.global.mbarrier::complete_tx::bytes [%0], [%1, {%3, %4, %5, %6}], [%2];"
               :: "r"(dst), "l"(m), "r"(bar), "r"(0), "r"(c1), "r"(c2), "r"(c3) : "memory");
}
DEVI void tma5d(uint32_t dst, const CUtensorMap* m, int c0, int c1, int c3, int c4, uint32_t bar) {
  asm volatile("cp.async.bulk.tensor.5d.shared::cluster.global.mbarrier::complete_tx::bytes [%0], [%1, {%3, %4, %5, %6, %7}], [%2];"
               :: "r"(dst), "l"(m), "r"(bar), "r"(c0), "r"(c1), "r"(0), "r"(c3), "r"(c4) : "memory");
}
DEVI void tma2d_store(const CUtensorMap* m, uint32_t src, int c0, int c1) {
  asm volatile("cp.async.bulk.tensor.2d.global.shared::cta.bulk_group [%0, {%2, %3}], [%1];" :: "l"(m), "r"(src), "r"(c0), "r"(c1) : "memory");
}
DEVI void tma2d_store_e(const CUtensorMap* m, uint32_t src, int c0, int c1) {
  asm volatile("{\n.reg .pred e;\nelect.sync _|e, 0xffffffff;\n@e cp.async.bulk.tensor.2d.global.shared::cta.bulk_group [%0, {%2, %3}], [%1];\n"
               "@e cp.async.bulk.commit_group;\n}" :: "l"(m), "r"(src), "r"(c0), "r"(c1) : "memory");
}
DEVI void tma5d_store(const CUtensorMap* m, uint32_t src, int c0, int c1, int c3, int c4) {
  asm volatile("cp.async.bulk.tensor.5d.global.shared::cta.bulk_group [%0, {%2, %3, %4, %5, %6}], [%1];\ncp.async.bulk.commit_group;"
               :: "l"(m), "r"(src), "r"(c0), "r"(c1), "r"(0), "r"(c3), "r"(c4) : "memory");
}
DEVI void bulk_load(uint32_t dst, const void* src, uint32_t bytes, uint32_t bar) {
  asm volatile("cp.async.bulk.shared::cluster.global.mbarrier::complete_tx::bytes [%0], [%1], %2, [%3];" :: "r"(dst), "l"(src), "r"(bytes), "r"(bar) : "memory");
}
DEVI uint32_t mapa(uint32_t a, int rank) { uint32_t r; asm("mapa.shared::cluster.u32 %0, %1, %2;" : "=r"(r) : "r"(a), "r"(rank)); return r; }
DEVI void st_async4(uint32_t dst, uint32_t a, uint32_t b, uint32_t c, uint32_t d, uint32_t bar) {
  asm volatile("st.async.weak.shared::cluster.mbarrier::complete_tx::bytes.v4.b32 [%0], {%1,%2,%3,%4}, [%5];"
               :: "r"(dst), "r"(a), "r"(b), "r"(c), "r"(d), "r"(bar) : "memory");
}
DEVI void st_either8(bool local, uint32_t dst, uint32_t bar, uint32_t a, uint32_t b, uint32_t c, uint32_t d, uint32_t e, uint32_t f, uint32_t g, uint32_t h) {
  asm volatile("{\n.reg .pred p;\nsetp.ne.b32 p, %10, 0;\n@p st.shared.v4.b32 [%0], {%2,%3,%4,%5};\n@p st.shared.v4.b32 [%0 + 4096], {%6,%7,%8,%9};\n@p bra.uni E_DONE;\n"
               "st.async.weak.shared::cluster.mbarrier::complete_tx::bytes.v4.b32 [%0], {%2,%3,%4,%5}, [%1];\n"
               "st.async.weak.shared::cluster.mbarrier::complete_tx::bytes.v4.b32 [%0 + 4096], {%6,%7,%8,%9}, [%1];\nE_DONE:\n}"
               :: "r"(dst), "r"(bar), "r"(a), "r"(b), "r"(c), "r"(d), "r"(e), "r"(f), "r"(g), "r"(h), "r"((int)local) : "memory");
}
DEVI void red_async_max(uint32_t dst, uint32_t a, uint32_t bar) {
  asm volatile("red.async.relaxed.cluster.shared::cluster.mbarrier::complete_tx::bytes.max.u32 [%0], %1, [%2];" :: "r"(dst), "r"(a), "r"(bar) : "memory");
}
DEVI void pf_line(const void* p) { asm volatile("prefetch.global.L2 [%0];" :: "l"(p) : "memory"); }
DEVI void bulk_commit() { asm volatile("cp.async.bulk.commit_group;" ::: "memory"); }
DEVI void bulk_wait_all() { asm volatile("cp.async.bulk.wait_group 0;" ::: "memory"); }
DEVI void bulk_wait_read() { asm volatile("cp.async.bulk.wait_group.read 0;" ::: "memory"); }
DEVI void prefetch_map(const CUtensorMap* m) { asm volatile("prefetch.tensormap [%0];" :: "l"(m) : "memory"); }

__host__ __device__ constexpr uint32_t dlo(uint32_t off, uint32_t lbo) { return (off >> 4) + ((lbo >> 4) << 16); }
struct Desc {
  uint64_t v;
  DEVI Desc(uint64_t z, uint32_t base, uint32_t sbo, uint32_t mode) : v(z + (base | (uint64_t)((sbo >> 4) | (mode << 30)) << 32)) { asm volatile("" : "+l"(v)); }
  DEVI void renew(uint64_t z) { asm volatile("add.s64 %0, %0, %1;" : "+l"(v) : "l"(z)); }
  DEVI uint64_t at(uint32_t lo) const { uint64_t r; asm volatile("add.s64 %0, %1, %2;" : "=l"(r) : "l"(v), "l"((int64_t)(int32_t)lo)); return r; }
};
DEVI uint32_t pack_bf16(float lo, float hi) { uint32_t r; asm("cvt.rn.bf16x2.f32 %0, %1, %2;" : "=r"(r) : "f"(hi), "f"(lo)); return r; }
DEVI uint32_t pack_f16(float lo, float hi) { uint32_t r; asm("cvt.rn.f16x2.f32 %0, %1, %2;" : "=r"(r) : "f"(hi), "f"(lo)); return r; }
DEVI void stsm4(uint32_t addr, uint32_t r0, uint32_t r1, uint32_t r2, uint32_t r3) {
  asm volatile("stmatrix.sync.aligned.m8n8.x4.shared.b16 [%0], {%1,%2,%3,%4};" :: "r"(addr), "r"(r0), "r"(r1), "r"(r2), "r"(r3) : "memory");
}
DEVI void stsm4_t(uint32_t addr, uint32_t r0, uint32_t r1, uint32_t r2, uint32_t r3) {
  asm volatile("stmatrix.sync.aligned.m8n8.x4.trans.shared.b16 [%0], {%1,%2,%3,%4};" :: "r"(addr), "r"(r0), "r"(r1), "r"(r2), "r"(r3) : "memory");
}
DEVI void sts128(uint32_t addr, uint32_t a, uint32_t b, uint32_t c, uint32_t d) {
  asm volatile("st.shared.v4.b32 [%0], {%1,%2,%3,%4};" :: "r"(addr), "r"(a), "r"(b), "r"(c), "r"(d) : "memory");
}
DEVI void sts32(uint32_t addr, uint32_t v) { asm volatile("st.shared.b32 [%0], %1;" :: "r"(addr), "r"(v) : "memory"); }
DEVI uint32_t lds32(uint32_t a) { uint32_t v; asm volatile("ld.shared.b32 %0, [%1];" : "=r"(v) : "r"(a)); return v; }
DEVI void lds128(uint32_t* v, uint32_t a) {
  asm volatile("ld.shared.v4.b32 {%0,%1,%2,%3}, [%4];" : "=r"(v[0]), "=r"(v[1]), "=r"(v[2]), "=r"(v[3]) : "r"(a));
}
DEVI void ldg128(uint32_t* v, const void* p) {
  asm volatile("ld.global.nc.L1::no_allocate.v4.b32 {%0,%1,%2,%3}, [%4];" : "=r"(v[0]), "=r"(v[1]), "=r"(v[2]), "=r"(v[3]) : "l"(p));
}
DEVI float rcp(float x) { float r; asm("rcp.approx.ftz.f32 %0, %1;" : "=f"(r) : "f"(x)); return r; }
DEVI float exp_sat(float t) {
  float e, s;
  asm("ex2.approx.ftz.f32 %0, %1;" : "=f"(e) : "f"(t * 1.4426950408889634f));
  asm("add.sat.f32 %0, %1, 0f358637BD;" : "=f"(s) : "f"(e));
  return s;
}
DEVI uint32_t phi2(float a, float b) {
  uint32_t r, o;
  asm("cvt.rn.relu.bf16x2.f32 %0, %1, %2;" : "=r"(r) : "f"(b), "f"(a));
  asm("add.rn.bf16x2 %0, %1, %2;" : "=r"(o) : "r"(r), "r"(pack_bf16(exp_sat(a), exp_sat(b))));
  return o;
}
DEVI void arrive_both(uint32_t bar, int lane, bool pred = true) {
  asm volatile("{\n.reg .pred p;\n.reg .b32 r;\nsetp.ne.b32 p, %2, 0;\nmapa.shared::cluster.u32 r, %0, %1;\n@p mbarrier.arrive.shared::cluster.b64 _, [r];\n}"
               :: "r"(bar), "r"(lane & 1), "r"((int)(pred && lane < 2)) : "memory");
}
DEVI uint32_t bmul2(uint32_t a, uint32_t b) { uint32_t r; asm("mul.rn.bf16x2 %0, %1, %2;" : "=r"(r) : "r"(a), "r"(b)); return r; }
DEVI uint32_t badd2(uint32_t a, uint32_t b) { uint32_t r; asm("add.rn.bf16x2 %0, %1, %2;" : "=r"(r) : "r"(a), "r"(b)); return r; }
DEVI uint32_t bamax2(uint32_t a, uint32_t b) { uint32_t r; asm("max.NaN.xorsign.abs.bf16x2 %0, %1, %2;" : "=r"(r) : "r"(a), "r"(b)); return r; }
DEVI uint32_t hmul2(uint32_t a, uint32_t b) { uint32_t r; asm("mul.rn.f16x2 %0, %1, %2;" : "=r"(r) : "r"(a), "r"(b)); return r; }
DEVI uint32_t hadd2(uint32_t a, uint32_t b) { uint32_t r; asm("add.rn.f16x2 %0, %1, %2;" : "=r"(r) : "r"(a), "r"(b)); return r; }
DEVI uint32_t hsub2(uint32_t a, uint32_t b) { uint32_t r; asm("sub.rn.f16x2 %0, %1, %2;" : "=r"(r) : "r"(a), "r"(b)); return r; }
DEVI uint32_t hfma2(uint32_t a, uint32_t b, uint32_t c) { uint32_t r; asm("fma.rn.f16x2 %0, %1, %2, %3;" : "=r"(r) : "r"(a), "r"(b), "r"(c)); return r; }
DEVI uint32_t hfnma2(uint32_t a, uint32_t b, uint32_t c) {
  uint32_t r; asm("{\n.reg .b32 n;\nneg.f16x2 n, %1;\nfma.rn.f16x2 %0, n, %2, %3;\n}" : "=r"(r) : "r"(a), "r"(b), "r"(c)); return r;
}
DEVI float bf_lo(uint32_t w) { return __uint_as_float(w << 16); }
DEVI float bf_hi(uint32_t w) { return __uint_as_float(w & 0xffff0000u); }

DEVI uint32_t chan_exponent(const uint32_t* w) {
  uint32_t m[4];
#pragma unroll
  for (int i = 0; i < 4; i++) m[i] = bamax2(w[i], w[i + 4]);
#pragma unroll
  for (int i = 8; i < 32; i++) m[i & 3] = bamax2(m[i & 3], w[i]);
  uint32_t x = bamax2(bamax2(m[0], m[1]), bamax2(m[2], m[3])) & 0x7fff7fffu;
  x = max(x >> 16, x & 0xffffu);
  x = __reduce_max_sync(0xffffffffu, x);
  return min(x >> 7, 251u);
}
DEVI uint32_t to_f16(uint32_t w, uint32_t mul) { const uint32_t y = bmul2(w, mul); return pack_f16(bf_lo(y), bf_hi(y)); }

struct Tile { int j, r; };
DEVI Tile tile_of() {
  int cta; asm volatile("mov.u32 %0, %%ctaid.x;" : "=r"(cta));
  const int cl = cta >> 1, lo = (cl - 4) >> 31, hi = (35 - cl) >> 31;
  const int p = cl - 4 + (lo & (36 + 7 * cl)) + (hi & ((((cl - 36) * 37) >> 8) + 1)), g = p & 7, rr = p >> 3;
  return Tile{(g & 6) | (cta & 1), 2 * rr + (g & 1)};
}

static_assert(TAIL <= 3, "stage 27 is released inside the loop");
__host__ __device__ constexpr bool prew(int it) { return it >= 28 && it < 31; }

DEVI void twiddle(uint32_t& ore, uint32_t& oim, uint32_t re, uint32_t im, uint32_t t, uint32_t s) {
  re = hfma2(t, im, re);
  oim = hfma2(s, re, im);
  ore = hfma2(t, oim, re);
}

__global__ void __cluster_dims__(2, 1, 1) __launch_bounds__(kThreads, 1)
fused_kernel(const __grid_constant__ Params P) {
  extern __shared__ __align__(1024) uint8_t smem[];
  const int tid = threadIdx.x, lane = tid & 31;
  const int warp = tid >> 5, warpu = __shfl_sync(0xffffffffu, tid >> 5, 0);
  const int cta = blockIdx.x, rho = cta & 1, cl = cta >> 1;
  const uint32_t sb = SM_BASE + (rho << 24);
  const uint32_t tstart = clock32();
  auto bar = [&](int i) INL { return sb + SM_BAR + 8u * i; };
  auto load1 = [&](int it, int s, int j, int r, bool mc) INL {
    const uint32_t fb = bar(B_F1 + s), xs = sb + x1_off(it);
    mbar_expect(fb, (it & 1) ? 16384 : 32768);
    tma4d(sb + w1_off(s), &P.w1, 32 * it, 2 * j, 1, fb);
    if (!(it & 1)) {
      if (mc) tma2d_mc(xs + rho * 8192, &P.x, 32 * it, 128 * r + 64 * rho, fb);
      else { tma2d(xs, &P.x, 32 * it, 128 * r, fb); tma2d(xs + 8192, &P.x, 32 * it, 128 * r + 64, fb); }
    }
  };
  TSTAMP(tid == 0, 0); GSTAMP(tid == 0, 62);

  if (warpu == 8 && elect()) {
    prefetch_map(&P.w1); prefetch_map(&P.x);
    for (int i = 0; i < EARLY; i++) mbar_init(bar(B_F1 + slot1(i)), 1);
    const Tile T = tile_of();
    for (int i = 0; i < EARLY; i++) load1(i, slot1(i), T.j, T.r, false);
    TSTAMP(true, 18);
    for (int i = EARLY; i < NS1; i++) mbar_init(bar(B_F1 + slot1(i)), 1);
    asm volatile("fence.mbarrier_init.release.cluster;" ::: "memory");
  }
  if (warpu == 9 && elect()) {
    if (sb != (uint32_t)__cvta_generic_to_shared(smem)) __trap();
#pragma unroll
    for (int i = B_F2; i < B_Q; i++) mbar_init(bar(i), 1);
    mbar_expect(bar(B_H), 32768);
    asm volatile("fence.mbarrier_init.release.cluster;" ::: "memory");
  }
  if (warpu == 10 && elect()) {
#pragma unroll
    for (int i = B_Q; i < B_KVE; i++) mbar_init(bar(i), i < B_E1 ? 1 : 16);
    mbar_expect(bar(B_Q), 32768); mbar_expect(bar(B_U), 16384); mbar_expect(bar(B_MAX), 1024);
    asm volatile("fence.mbarrier_init.release.cluster;" ::: "memory");
  }
  if (warpu == 11 && elect()) {
#pragma unroll
    for (int i = B_KVE; i < B_COUNT; i++) mbar_init(bar(i), i < B_OFREE ? 8 : i == B_F2M ? 3 : i < B_Y ? 4 : 9);
    mbar_expect(bar(B_Y), 8192); mbar_expect(bar(B_Y + 1), 8192);
    asm volatile("fence.mbarrier_init.release.cluster;" ::: "memory");
  }
  __syncwarp();
  cluster_sync();

  if (warpu < 8) {
    asm volatile("setmaxnreg.inc.sync.aligned.u32 %0;" :: "n"(232));
    const int wg = warp >> 2, wq = warp & 3, g = lane >> 2, q = lane & 3;
    constexpr uint32_t sbq = SM_BASE >> 4;
    const uint32_t wgu = warpu >> 2;
    const uint64_t z64 = P.zero;
    Desc dA(z64, sbq + wgu * 512, 1024, 1), dB(z64, sbq, 1024, 1);
    const int srow = wg * 64 + wq * 16 + (lane & 15);
    const uint32_t stm = srow * 128 + (((lane >> 4) ^ (srow & 7)) << 4);
    auto stage2 = [&](float* acc, int n, bool first) INL {
      const int s = slot2(n);
      mbar_wait(bar(B_F2 + s), par2(n));
      const uint32_t da = s * (ST2 >> 4) + dlo(0, 16), db = s * (ST2 >> 4) + dlo(16384, 8192);
      wg_fence();
      const uint64_t a0 = dA.at(da), b0 = dB.at(db);
      if (first) mma_n128_init(acc, a0, b0); else mma_n128(acc, a0, b0);
#pragma unroll
      for (int kk = 1; kk < 4; kk++) mma_n128(acc, a0 + 2 * kk, b0 + kk * (2048 >> 4));
      wg_commit();
    };
    auto release2 = [&](int n) INL { arrive_both(bar(B_E2 + slot2(n)), lane); };
    auto publish = [&](int b) INL { fence_async_smem(); __syncwarp(); mbar_arrive_if(bar(b), lane == 0); };

    float aq[64];
    uint32_t f1[8], tw[4];
    uint32_t su[2][32], sh[2][32];
    uint32_t x0[4][8], x1[4][8], p0[2][8], p1[2][8], z0[2][8], z1[2][8];
    auto s1 = [&](uint32_t* d, uint32_t base) INL {
      Desc db(z64, sbq + wgu * 1024 + dlo(base, 128), 512, 0);
      wg_fence();
      mma_s1_init(d, f1, db.v);
      mma_s1(d, f1 + 4, db.at(256 >> 4));
      wg_commit();
    };
    const uint64_t dre = Desc(z64, sbq + dlo(SM_F2 + 512, 128), 256, 0).v, dim = Desc(z64, sbq + dlo(SM_F2, 128), 256, 0).v;
    auto fwd2 = [&](uint32_t (*x)[8], int c) INL {
      uint32_t a[4][8];
#pragma unroll
      for (int t = 0; t < 4; t++) {
        uint32_t* s = (t < 2 ? sh[c >> 1] : su[c >> 1]) + 16 * (c & 1) + 8 * (t & 1);
        pin<8>(s);
#pragma unroll
        for (int i = 0; i < 4; i++) twiddle(a[t][i], a[t][4 + i], s[4 * (i & 1) + (i & 2)], s[4 * (i & 1) + (i & 2) + 1], tw[i & 2], tw[(i & 2) + 1]);
      }
      wg_fence();
#pragma unroll
      for (int t = 0; t < 4; t++) { mma_s2_init(x[t], a[t], dre); mma_s2(x[t], a[t] + 4, dim); }
      wg_commit();
    };
    auto half2 = [&](uint32_t (*x)[8], uint32_t* s) INL {
      uint32_t a[2][8];
      pin<16>(s);
#pragma unroll
      for (int t = 0; t < 2; t++)
#pragma unroll
        for (int i = 0; i < 4; i++) twiddle(a[t][i], a[t][4 + i], s[8 * t + 4 * (i & 1) + (i & 2)], s[8 * t + 4 * (i & 1) + (i & 2) + 1], tw[i & 2], tw[(i & 2) + 1]);
      wg_fence();
#pragma unroll
      for (int t = 0; t < 2; t++) { mma_s2_init(x[t], a[t], dre); mma_s2(x[t], a[t] + 4, dim); }
      wg_commit();
    };
    auto product = [&](uint32_t (*a)[8], uint32_t (*x)[8], int i) INL {
#pragma unroll
      for (int t = 0; t < 4; t++) { pin<2>(x[t] + i); pin<2>(x[t] + 4 + i); }
      auto hr = [&](int l) INL { return x[l >> 1][i + (l & 1)]; };
      auto hi = [&](int l) INL { return x[l >> 1][4 + i + (l & 1)]; };
      auto ur = [&](int l) INL { return x[2 + (l >> 1)][i + (l & 1)]; };
      auto ui = [&](int l) INL { return x[2 + (l >> 1)][4 + i + (l & 1)]; };
      uint32_t gr[4], gi[4];
      gr[0] = hr(0); gi[0] = hi(0);
#pragma unroll
      for (int l = 1; l < 4; l++) { gr[l] = hadd2(hr(l), hi(l - 1)); gi[l] = hsub2(hi(l), hr(l - 1)); }
#pragma unroll
      for (int p = 0; p < 4; p++) {
        uint32_t re = hfnma2(gi[0], ui(p), hmul2(gr[0], ur(p))), im = hfma2(gi[0], ur(p), hmul2(gr[0], ui(p)));
#pragma unroll
        for (int l = 1; l <= p; l++) {
          re = hfnma2(gi[l], ui(p - l), hfma2(gr[l], ur(p - l), re));
          im = hfma2(gi[l], ur(p - l), hfma2(gr[l], ui(p - l), im));
        }
        a[p >> 1][i + (p & 1)] = re; a[p >> 1][4 + i + (p & 1)] = im;
      }
#pragma unroll
      for (int t = 0; t < 2; t++) { pin<2>(a[t] + i); pin<2>(a[t] + 4 + i); }
    };
    auto inv1 = [&](uint32_t (*z)[8], uint32_t (*a)[8]) INL {
      wg_fence();
#pragma unroll
      for (int t = 0; t < 2; t++) { mma_s2_init(z[t], a[t], dre); mma_s2_neg(z[t], a[t] + 4, dim); }
      wg_commit();
    };
    auto zstore = [&](uint32_t (*z)[8], int c) INL {
      const uint32_t zoff = sb + RB + (q >> 1) * (RU + 16 - RB) + (8 * rho + 4 * wg) * 2048 + (4 * (8 * wq + g) + 2 * (q & 1)) * 16;
#pragma unroll
      for (int t = 0; t < 2; t++) {
        uint32_t a[8];
        pin<8>(z[t]);
#pragma unroll
        for (int i = 0; i < 4; i++) twiddle(a[i], a[4 + i], z[t][i], z[t][4 + i], tw[i & 2], tw[(i & 2) + 1]);
        const uint32_t dst = zoff + t * (16384 - rho * 32768) + c * 2048;
        sts128(dst, a[0], a[1], a[2], a[3]);
        sts128(dst + 16, a[4], a[5], a[6], a[7]);
      }
    };
    float kvr[18];
    auto kvstore = [&]() INL {
      const uint32_t dst = sb + kv_off(warp >> 1) + (warp & 1) * 256 + lane * 4;
      pin<18>(kvr);
#pragma unroll
      for (int b = 0; b < 4; b++) { sts32(dst + b * 512, pack_bf16(kvr[4 * b], kvr[4 * b + 1])); sts32(dst + b * 512 + 128, pack_bf16(kvr[4 * b + 2], kvr[4 * b + 3])); }
      sts32(dst + 2048, pack_bf16(kvr[16], kvr[16])); sts32(dst + 2176, pack_bf16(kvr[17], kvr[17]));
      publish(B_KVI);
    };
    {
      float ak[64], av[64];
      Desc dK(z64, sbq + wgu * 256, 1024, 1);
      auto kstep = [&](int c, int i) INL {
        const int s = slot1(c);
        if (!prew(c - 1)) mbar_wait(bar(B_F1 + s), (c / NS1 + i) & 1);
        TSTAMP(tid == 0 && c == 0, 1);
        const uint32_t dx = dlo(x1_off(c + 6 * i), 16), dk = dlo(w1_off(s), 16);
        const uint64_t xb = dB.at(dx) + (c & 1) * 4;
        wg_fence();
        if (c == 0) { mma_kt_init(ak, dK.at(dk), xb); mma_kt_init(av, dK.at(dk + 512), xb); }
        else { mma_kt(ak, dK.at(dk), xb); mma_kt(av, dK.at(dk + 512), xb); }
        mma_kt(ak, dK.at(dk + 128), xb + 2);
        mma_kt(av, dK.at(dk + 640), xb + 2);
        wg_commit();
        wg_wait<1>();
        if (c > 0) arrive_both(bar(B_E1 + (s + NS1 - 1) % NS1), lane);
        if (prew(c)) mbar_wait(bar(B_F1 + slot1(c + 1)), ((c + 1) / NS1) & 1);
        KSTAMP(c + 6 * i);
      };
      auto renew = [&]() INL { dK.renew(z64); dB.renew(z64); };
      uint32_t kk[7], u[36], sw[4], mx[2], um = 0, eu;
      unsigned short dskip;
      const int cp = 4 * (warp & 1) + (lane >> 3), run = 8 * (warp >> 1) + (lane & 7);
      const uint32_t ua = sb + RB + run * 32 + ((warp ^ (lane >> 2)) & 1) * 16 + (lane >> 3) * 4;
      sts32(sb + SM_MAX + (lane & 15) * 4, 0);
      ldg128(sw, P.shift_k + (cl * 16 + 2 * cp) * 4);
      asm volatile("ld.global.nc.b16 %0, [%1];" : "=h"(dskip) : "l"(P.ssm_d + 8 * cta + warp));
#pragma unroll
      for (int c = 0; c < L0; c++) kstep(c, 0);
      {
        pin<4>(sw);
        const uint32_t t0 = __byte_perm(sw[0], sw[2], 0x5410), t1 = __byte_perm(sw[0], sw[2], 0x7632), t2 = __byte_perm(sw[1], sw[3], 0x5410);
        sw[3] = __byte_perm(sw[1], sw[3], 0x7632); sw[0] = t0; sw[1] = t1; sw[2] = t2;
        pin<4>(sw);
      }
      float tap0 = lane == 0 ? bf_lo(dskip) : 0.f;
      pin<1>(&tap0);
#pragma unroll
      for (int e = 0; e < 36; e++) u[e] = 0;
#pragma unroll
      for (int e = 0; e < 7; e++) kk[e] = 0;
      renew();
#pragma unroll
      for (int c = L0; c < L0 + 6; c++) kstep(c, 0);
      renew();
#pragma unroll 1
      for (int i = 1; i < 4; i++) {
#pragma unroll
        for (int h = 0; h < 3; h++) {
          kstep(L0 + 2 * h, i);
          {
            const int slot = (3 * i + h + 4) & 7;
#pragma unroll
            for (int e = 4 * h; e < 4 * h + 4; e++) { u[e] = u[e + 12]; u[e + 12] = u[e + 24]; }
            pin<4>(u + 4 * h); pin<4>(u + 4 * h + 12);
            mbar_wait(bar(B_KVL + slot), h == 2 && i == 3);
#pragma unroll
            for (int e = 0; e < 4; e++) { kk[3 + e] = lds32(ua + slot * 8192 + e * 1024); u[24 + 4 * h + e] = lds32(ua + slot * 8192 + 4096 + e * 1024); }
          }
          kstep(L0 + 2 * h + 1, i);
          pin<7>(kk); pin<4>(u + 24 + 4 * h);
#pragma unroll
          for (int e = 0; e < 4; e++) {
            uint32_t& y = u[24 + 4 * h + e];
            y = bmul2(badd2(badd2(badd2(bmul2(kk[e], sw[3]), bmul2(kk[1 + e], sw[2])), bmul2(kk[2 + e], sw[1])), bmul2(kk[3 + e], sw[0])), y);
            um = bamax2(um, y);
          }
          if (h == 0) um = i == 1 ? 0 : um;
          kk[0] = kk[4]; kk[1] = kk[5]; kk[2] = kk[6];
          pin<4>(u + 24 + 4 * h); pin<1>(&um);
          if (h == 1) mbar_arrive_if(bar(B_KVE), lane == 0 && i == 2);
        }
      }
      um = bamax2(um, __shfl_xor_sync(0xffffffffu, um, 1));
      um = bamax2(um, __shfl_xor_sync(0xffffffffu, um, 2));
      red_async_max(mapa(sb + SM_MAX + cp * 8 + (q & 1) * 4, q >> 1), min((um >> (7 + 16 * (q & 1))) & 0xffu, 251u), mapa(bar(B_MAX), q >> 1));
      renew();
#pragma unroll
      for (int c = L0 + 24; c < 28; c++) {
        kstep(c, 0);
        if (c == L0 + 24) { ldg128(f1, P.tab + (tid & 127) * 4); ldg128(f1 + 4, P.tab + 512 + (tid & 127) * 4); ldg128(tw, P.tab + 1024 + (tid & 127) * 4); }
      }
      mbar_wait(bar(B_MAX), 0);
      TSTAMP(tid == 0, 5);
      asm volatile("ld.shared.v2.b32 {%0,%1}, [%2];" : "=r"(mx[0]), "=r"(mx[1]) : "r"(sb + SM_MAX + cp * 8));
      eu = lds32(sb + SM_MAX + (8 * rho + warp) * 4);
      const uint32_t ud = mapa(sb + RU + (lane >> 3) * 8192 + (2 * rho + wg) * 1024 + (run & 15) * 16, warp & 1), ub = mapa(bar(B_U), rho ^ 1);
#pragma unroll
      for (int i = 0; i < 4; i++) {
        kstep(28 + i, 0);
        if (i == 0) { pin<2>(mx); mx[0] = (0x00fd00fdu - (mx[0] | mx[1] << 16)) << 7; }
        uint32_t* y = u + 4 + 8 * i;
        pin<8>(y);
#pragma unroll
        for (int e = 0; e < 8; e++) y[e] = bmul2(y[e], mx[0]);
        st_either8((warpu & 1) == rho, ud + (i & 1) * 512 + (i >> 1) * 256, ub,
                   pack_f16(bf_lo(y[0]), bf_lo(y[1])), pack_f16(bf_lo(y[2]), bf_lo(y[3])), pack_f16(bf_lo(y[4]), bf_lo(y[5])), pack_f16(bf_lo(y[6]), bf_lo(y[7])),
                   pack_f16(bf_hi(y[0]), bf_hi(y[1])), pack_f16(bf_hi(y[2]), bf_hi(y[3])), pack_f16(bf_hi(y[4]), bf_hi(y[5])), pack_f16(bf_hi(y[6]), bf_hi(y[7])));
      }
      auto qstep = [&](int n) INL {
        if ((n & 3) == 0) { dA.renew(z64); dB.renew(z64); }
        stage2(aq, n, n == 0);
        wg_wait<1>();
        if (n == 0) arrive_both(bar(B_E1 + NS1 - 1), lane); else release2(n - 1);
        QSTAMP(n);
      };
      uint32_t pk[32];
      auto phik = [&](int i0, int i1) INL {
#pragma unroll
        for (int i = i0; i < i1; i++) { pin<2>(ak + 2 * i); pk[i] = phi2(ak[2 * i], ak[2 * i + 1]); pin<1>(pk + i); }
      };
      const uint32_t rot = tile_of().r & 3;
      const uint32_t stt = sb + RA + wg * 16384 + ((lane >> 4) * 8 + (lane & 7)) * 128 + (((2 * wq + ((lane >> 3) & 1)) ^ rot ^ (lane & 7)) << 4);
      auto vst = [&](int k0, int k1) INL {
#pragma unroll
        for (int kt = k0; kt < k1; kt++) {
          float* a = av + 8 * kt;
          pin<8>(a);
          stsm4_t(stt + kt * 2048, pack_bf16(a[0], a[1]), pack_bf16(a[2], a[3]), pack_bf16(a[4], a[5]), pack_bf16(a[6], a[7]));
        }
      };
      float dkv[36];
      Desc dV(z64, sbq + wgu * (1024u - (1024u << 16)) + dlo(RA, SM_ONES - RA), 1024, 1);
      auto kvmma = [&](int k0, int k1) INL {
        wg_fence();
#pragma unroll
        for (int ks = k0; ks < k1; ks++) {
          const uint64_t db = dV.at(ks * (128u - (128u << 16)));
          if (ks == 0) mma_kv_init(dkv, pk, db); else mma_kv(dkv, pk + 4 * ks, db);
        }
        wg_commit();
      };
      float* gacc;
      auto kvred = [&](int b) INL {
        const bool hh = wq >> 1;
        asm volatile("red.relaxed.gpu.global.add.v4.f32 [%0], {%1,%2,%3,%4};" :: "l"(gacc + (b ^ rot) * 128), "f"(hh ? dkv[16 + 4 * b] : dkv[4 * b]),
                     "f"(hh ? dkv[17 + 4 * b] : dkv[1 + 4 * b]), "f"(hh ? dkv[18 + 4 * b] : dkv[2 + 4 * b]), "f"(hh ? dkv[19 + 4 * b] : dkv[3 + 4 * b]) : "memory");
        if (b == 3) {
          asm volatile("{\n.reg .pred p;\nsetp.eq.s32 p, %3, 0;\n@p red.relaxed.gpu.global.add.v2.f32 [%0], {%1,%2};\n}"
                       :: "l"(gacc + 4096 - warp * 496 - g * 14), "f"(dkv[32]), "f"(dkv[34]), "r"(q) : "memory");
          __syncwarp();
          mbar_arrive_if(bar(B_KVP), lane == 0);
          TSTAMP(tid == 0, 4);
        }
      };
      uint32_t w[32], hmul;
      auto hload = [&](int i0, int i1) INL {
        const uint32_t a = sb + RB + warp * 4096 + (((lane >> 2) & 1) + (lane & 2) + 4 * (lane & 1) + (((lane << 2) ^ lane) & 24)) * 16;
#pragma unroll
        for (int i = i0; i < i1; i++) lds128(w + 4 * i, a + i * 512);
      };
      auto hmax = [&]() INL {
        pin<32>(w);
        tap0 += bf_lo(w[0]);
        w[0] = pack_bf16(tap0, bf_hi(w[0]));
        hmul = (252u - chan_exponent(w)) * 0x00800080u;
        const int e = min(max((int)(eu + 128 - (hmul >> 23)), 0), 254);
        asm volatile("st.shared.b16 [%0], %1;" :: "r"(sb + SM_SCALE + 2 * warp), "h"((unsigned short)(e << 7)) : "memory");
      };
      auto hstore = [&](int i0, int i1) INL {
        const uint32_t dst = sb + RB + warp * 4096 + (lane & 6) * 128 + ((lane ^ ((lane >> 2) & 6)) & 7) * 16;
#pragma unroll
        for (int i = i0; i < i1; i++) {
          pin<4>(w + 4 * i);
          const uint32_t w0 = i == 0 ? pack_f16(tap0 * bf_lo(hmul), bf_hi(w[0]) * bf_lo(hmul)) : to_f16(w[4 * i], hmul);
          sts128(dst + (i >> 1) * 1024 + (i & 1) * 128, w0, to_f16(w[4 * i + 1], hmul), to_f16(w[4 * i + 2], hmul), to_f16(w[4 * i + 3], hmul));
        }
      };
      auto kvload = [&]() INL {
        mbar_wait(bar(B_KV), 0);
        TSTAMP(tid == 0, 7);
#pragma unroll
        for (int b = 0; b < 4; b++)
          asm volatile("ld.global.cg.v4.f32 {%0,%1,%2,%3}, [%4];" : "=f"(kvr[4 * b]), "=f"(kvr[4 * b + 1]), "=f"(kvr[4 * b + 2]), "=f"(kvr[4 * b + 3]) : "l"(gacc + b * 128) : "memory");
        asm volatile("ld.global.cg.v2.f32 {%0,%1}, [%2];" : "=f"(kvr[16]), "=f"(kvr[17]) : "l"(gacc + 4096 - warp * 496 - g * 14 - q * 4) : "memory");
      };
      qstep(0);
      TSTAMP(tid == 0, 2);
      phik(0, 7);
      qstep(1);
      mbar_wait(bar(B_E1 + NS1 - 1), 1);
      vst(0, 4); phik(7, 10);
      qstep(2);
      vst(4, 8);
      publish(B_VST);
      phik(10, 13);
      qstep(3);
      mbar_wait(bar(B_ZERO), 0);
      mbar_wait(bar(B_VST), 0);
      kvmma(0, 3); phik(13, 20);
      qstep(4);
      kvmma(3, 5);
      mbar_wait(bar(B_H), 0);
      hload(0, 3); phik(20, 26);
      gacc = &P.g->kv[tile_of().j][warp * 512 + lane * 4];
      qstep(5);
      hload(3, 5); phik(26, 32); kvmma(5, 8); hload(5, 8);
      qstep(6);
      pin<36>(dkv);
      mbar_arrive_if(bar(B_KVM), lane == 0);
      kvred(0);
      mbar_wait(bar(B_U2), 1);
      s1(su[0], RU);
      hmax(); hstore(0, 1); kvred(1);
      qstep(7);
      hstore(1, 4); kvred(2);
      qstep(8);
      hstore(4, 6); kvred(3);
      qstep(9);
      hstore(6, 8);
      publish(B_VST);
      mbar_wait(bar(B_F2M), 0);
      half2(x0 + 2, su[0]);
      qstep(10);
      mbar_wait(bar(B_VST), 1);
      s1(sh[0], RB);
      half2(x1 + 2, su[0] + 16);
      qstep(11);
      half2(x0, sh[0]); half2(x1, sh[0] + 16);
      qstep(12);
      product(p0, x0, 0);
      qstep(13);
      product(p0, x0, 2);
      kvload();
      qstep(14);
      product(p1, x1, 0);
      qstep(15);
      product(p1, x1, 2);
    }

    float acc[64];
    {
      uint32_t pq[4][8];
      float dn[4][20];
      Desc dO(z64, sbq + dlo(0, 128), 512, 0);
      auto phiq = [&](int h) INL {
        pin<16>(aq + 16 * h);
#pragma unroll
        for (int i = 0; i < 8; i++) pq[h][i] = phi2(aq[16 * h + 2 * i], aq[16 * h + 2 * i + 1]);
        pin<8>(pq[h]);
      };
      auto omma = [&](int h) INL {
        wg_fence();
        mma_o_init(dn[h], pq[h], dO.at(kv_off(h) >> 4));
        mma_o(dn[h], pq[h] + 4, dO.at((kv_off(h) + 256) >> 4));
        wg_commit();
      };
      auto onorm = [&](int h) INL {
        pin<20>(dn[h]);
        const float i0 = rcp(dn[h][16] + 1e-6f), i1 = rcp(dn[h][18] + 1e-6f);
#pragma unroll
        for (int hf = 0; hf < 2; hf++) {
          const float* a = dn[h] + 8 * hf;
          stsm4(sb + (h >> 1) * ST2 + (stm ^ (((h & 1) * 2 + hf) << 5)), pack_bf16(a[0] * i0, a[1] * i0), pack_bf16(a[2] * i1, a[3] * i1),
                pack_bf16(a[4] * i0, a[5] * i0), pack_bf16(a[6] * i1, a[7] * i1));
        }
        if (h & 1) publish(B_OW + (h >> 1));
      };
      s1(su[1], RU + 8192);
      kvstore();
      wg_wait<1>();
      release2(15);
      TSTAMP(tid == 0, 6);
      uint32_t gf[4][4];
      auto gdup = [&]() INL {
#pragma unroll
        for (int i = 0; i < 4; i += 2) {
          pin<4>(gf[i + 1]);
          gf[i][0] = gf[i][1] = gf[i + 1][0]; gf[i][2] = gf[i][3] = gf[i + 1][1];
          gf[i + 1][0] = gf[i + 1][1] = gf[i + 1][2]; gf[i + 1][2] = gf[i + 1][3];
          pin<4>(gf[i]); pin<4>(gf[i + 1]);
        }
      };
      const uint32_t qa = sb + RA + warp * 4096 + lane * 32 + ((rho ^ g) & 1) * 16;
      uint32_t qv[4][4];
      auto qload = [&]() INL {
        mbar_wait(bar(B_Q), 0);
#pragma unroll
        for (int i = 0; i < 4; i++) lds128(qv[i], qa + i * 1024);
      };
      phiq(0); phiq(1);
      mbar_wait(bar(B_KVI), 0);
      omma(0); omma(1);
      wg_wait<1>(); onorm(0);
      wg_wait<0>(); onorm(1);
      TSTAMP(tid == 0, 8);
      s1(sh[1], RB + 8192);
      phiq(2); omma(2); phiq(3);
      wg_wait<0>(); onorm(2);
      omma(3); inv1(z0, p0);
      wg_wait<1>(); onorm(3);
      TSTAMP(tid == 0, 9);
      inv1(z1, p1); fwd2(x0, 2);
      wg_wait<1>();
      mbar_wait(bar(B_OW + 1), 0);
      zstore(z0, 0); zstore(z1, 1);
      wg_wait<0>();
      dA.renew(z64); dB.renew(z64);
      stage2(acc, 16, true);
      fwd2(x1, 3);
      product(p0, x0, 0); product(p0, x0, 2);
      inv1(z0, p0);
      stage2(acc, 17, false);
      wg_wait<2>();
      release2(16);
      ldg128(gf[1], P.tab + 1536 + (tid & 127) * 4); ldg128(gf[3], P.tab + 2048 + (tid & 127) * 4);
      product(p1, x1, 0); product(p1, x1, 2);
      inv1(z1, p1);
      wg_wait<2>();
      zstore(z0, 2);
      gdup();
      wg_wait<0>();
      release2(17);
      zstore(z1, 3);
      publish(B_ZST);
      TSTAMP(tid == 0, 10);
      qload();
      mbar_wait(bar(B_ZST), 0);
      float y[64];
      {
        Desc db(z64, sbq + wgu * ((RU + 16 - RB) >> 4) + dlo(RB, 128), 2048, 0);
        wg_fence();
        mma_i2_init(y, gf[0], db.v, 0xEEEE4444u);
#pragma unroll
        for (int i = 1; i < 4; i++) mma_i2(y, gf[i], db.at(i * (512 >> 4)), 0xEEEE4444u);
        wg_commit();
      }
      uint32_t sc[4];
      lds128(sc, sb + SM_SCALE);
      TSTAMP(tid == 0, 11);
      stage2(acc, 18, false);
      TSTAMP(tid == 0, 13);
      wg_wait<1>();
      QSTAMP(18);
      arrive_both(bar(B_I2), lane);
      pin<64>(y);
      uint32_t yv[8][4];
#pragma unroll
      for (int i = 0; i < 8; i++)
#pragma unroll
        for (int m = 0; m < 4; m++) yv[i][m] = bmul2(pack_bf16(y[32 * (i >> 2) + (i & 3) + 8 * m], y[32 * (i >> 2) + (i & 3) + 8 * m + 4]), sc[m]);
      pin<32>(&yv[0][0]);
      stage2(acc, 19, false);
      wg_wait<1>();
      QSTAMP(19);
      release2(18);
      mbar_wait(bar(B_I2), 0);
      const uint32_t yr = mapa(sb + Y_IN + tid * 16 + warp * 1536, rho ^ 1), yb = mapa(bar(B_Y), rho ^ 1);
      dA.renew(z64); dB.renew(z64);
#pragma unroll
      for (int i = 0; i < 4; i++) {
        if (i) { stage2(acc, 19 + i, false); wg_wait<1>(); QSTAMP(19 + i); release2(18 + i); }
        pin<4>(qv[i]);
        sts128(qa + i * 1024, bmul2(yv[i][0], qv[i][0]), bmul2(yv[i][1], qv[i][1]), bmul2(yv[i][2], qv[i][2]), bmul2(yv[i][3], qv[i][3]));
        st_async4(yr + i * 512, yv[4 + i][0], yv[4 + i][1], yv[4 + i][2], yv[4 + i][3], yb + 8 * (i >> 1));
        if (i & 1) { __syncwarp(); mbar_arrive_if(bar(B_Y + (i >> 1)), lane == 0); }
      }
      TSTAMP(tid == 0, 12);
    }
#pragma unroll 1
    for (int n = 23; n < 32 - TAIL; n++) {
      stage2(acc, n, false);
      TSTAMP(tid == 0 && n == 26, 14);
      wg_wait<1>();
      release2(n - 1);
      QSTAMP(n);
    }
    {
      const Tile T = tile_of();
      dA.renew(z64); dB.renew(z64);
      mbar_wait(bar(B_STG), wgu ^ 1);
#pragma unroll
      for (int n = 32 - TAIL; n < 32; n++) stage2(acc, n, false);
      mbar_arrive_if(bar(B_STG), wgu == 0 && lane == 0);
      mbar_wait(bar(B_E2 + 5), 1);
      wg_wait<0>();
      TSTAMP(tid == 0, 17); TSTAMP(tid == 128, 15);
      pin<64>(acc);
#pragma unroll
      for (int c = 0; c < 2; c++) {
#pragma unroll
        for (int t = 0; t < 4; t++) {
          const float* a = acc + 32 * c + 8 * t;
          stsm4(sb + RB + c * 16384 + (stm ^ (t << 5)), pack_bf16(a[0], a[1]), pack_bf16(a[2], a[3]), pack_bf16(a[4], a[5]), pack_bf16(a[6], a[7]));
        }
        fence_async_smem();
        __syncwarp();
        tma2d_store_e(&P.outa, sb + RB + c * 16384 + warpu * 2048, 128 * T.j + 64 * c, 128 * T.r + 16 * warpu);
      }
      bulk_wait_read();
      TSTAMP(tid == 128, 16);
    }
  } else {
    asm volatile("setmaxnreg.dec.sync.aligned.u32 %0;" :: "n"(40));
    const Tile T = tile_of();
    const int j = T.j, r = T.r;
    auto kcol = [&](int n) INL {
      return n < 20 ? 128 * (j ^ ((n >> 1) & 1)) + 64 * (n & 1) : 128 * (((j & 6) + n - (n < 26 ? 18 : 24)) & 7) + (n < 26 ? 0 : 64);
    };
    if (warpu == 8) {
      uint32_t ph = 0;
      int s = slot1(EARLY);
#pragma unroll 1
      for (int it = EARLY; it < 32; ++it, s = s + 1 == NS1 ? 0 : s + 1) {
        if (it >= NS1) { mbar_wait(bar(B_E1 + s), (ph >> s) & 1); ph ^= 1u << s; }
        if (elect()) load1(it, s, j, r, true);
      }
      int qn = 0;
      auto loadq = [&](int n) INL {
        if ((0x9c000 >> n) & 1) { if (elect()) tma5d(sb + RA + qn * 8192, &P.q, 16 * cl, 2 * rho, 2 * (qn & 2), 2 * (qn & 1), bar(B_Q)); qn++; }
      };
#pragma unroll 1
      for (int n = 0; n < 16; ++n) {
        const int s = n & 3, i = n + (n >> 1);
        mbar_wait(bar(n < 4 ? B_E1 + i : B_E2 + s), n < 4 ? (ph >> i) & 1 : ((n >> 2) - 1) & 1);
        const uint32_t st = sb + s * ST2, fb = bar(B_F2 + s);
        if (elect()) {
          mbar_expect(fb, ST2);
          tma4d(st + 16384, &P.w2, 64 * n, 2 * j, 0, fb);
          tma2d_mc(st + rho * 8192, &P.x, 64 * n, 128 * r + 64 * rho, fb);
        }
        loadq(n);
      }
      auto loadw = [&](int n) INL {
        const int s = n & 3;
        mbar_wait(bar(B_E2 + s), ((n >> 2) - 1) & 1);
        if (elect()) { mbar_expect(bar(B_F2 + s), n < 18 ? 16384 : ST2); tma4d(sb + s * ST2 + 16384, &P.wo, kcol(n), 2 * j, 0, bar(B_F2 + s)); }
      };
#pragma unroll 1
      for (int n = 16; n < 20; ++n) {
        loadw(n);
        loadq(n);
      }
#pragma unroll 1
      for (int n = 18; n < 20; ++n) {
        const uint32_t st = sb + (n & 3) * ST2, fb = bar(B_F2 + (n & 3));
        mbar_wait(bar(B_RDY + n - 18), 0);
        asm volatile("fence.proxy.async.global;" ::: "memory");
        if (elect()) { tma2d(st, &P.o, kcol(n), 128 * r, fb); tma2d(st + 8192, &P.o, kcol(n), 128 * r + 64, fb); }
      }
      mbar_wait(bar(B_OFREE), 0);
      uint64_t slots = 0x103251032510ull, frees = 0x103251032410ull;
      uint32_t pars = 0xc9f, kc = 128 * (j & 6) + 256;
#pragma unroll 1
      for (int n = 20; n < 32; ++n, slots >>= 4, frees >>= 4, pars >>= 1, kc += n == 26 ? 448 : 128) {
        const uint32_t s = slots & 7, st = sb + s * ST2, fb = bar(B_F2 + s);
        mbar_wait(bar(B_RDY + n - 18), 0);
        mbar_wait(bar(B_E2 + (frees & 7)), ~pars & 1);
        if (elect()) {
          mbar_expect(fb, ST2);
          tma4d(st + 16384, &P.wo, kc & 1023, 2 * j, 0, fb);
          tma2d_mc(st + rho * 8192, &P.o, kc & 1023, 128 * r + 64 * rho, fb);
        }
      }
    } else {
      const int at = tid - 288, aw = warpu - 9;
      const unsigned epoch = ld_relaxed(&P.g->epoch[cta]);
      if (aw < 2) {
        float4* zp = reinterpret_cast<float4*>(&P.g->kv[j][r * (KV_WORDS / 16)]) + at;
        zp[0] = zp[2] = make_float4(0.f, 0.f, 0.f, 0.f);
        sts128(sb + SM_ONES + (at & 15) * 128 + (at & 7) * 16, 0x3f803f80u, 0x3f803f80u, 0x3f803f80u, 0x3f803f80u);
        fence_async_smem();
        bar_sync(4, 64);
        if (at == 0) {
          asm volatile("fence.release.gpu;\nred.relaxed.gpu.global.add.u32 [%0], 1;" :: "l"(&P.g->zflag[j * 32]) : "memory");
          flag_wait(&P.g->zflag[j * 32], 16u * (epoch + 1));
          mbar_arrive(bar(B_ZERO));
        }
        __syncwarp();
      } else {
#pragma unroll 1
        for (int m = -1; m < 16; m++) {
          const int s = (m >> 1) & 7;
          pace(tstart, PREP0 + (m + 1) * PREPGAP);
          if (m == 14) mbar_wait(bar(B_KVE), 0);
          if (elect()) {
            if (m < 0 || !(m & 1)) mbar_expect(bar(B_KVL + s), m < 0 ? 4096 : 8192);
            tma3d(sb + RB + (m < 0 ? 14 : m) * 4096, m > 0 && (m & 1) ? &P.v : &P.k, 16 * cl, 32 * rho + (m >> 31), 2 * (m & 14), bar(B_KVL + s));
          }
        }
#pragma unroll 1
        for (int m = 0; m < 8; m++) {
          pace(tstart, HT0 + m * HGAP);
          if (elect()) bulk_load(sb + RB + m * 4096, P.ssm_k + (size_t)(8 * cta + m) * 2048, 4096, bar(B_H));
        }
      }
      if (aw == 1) {
        if (cta < 3) pf_line(P.tab + cta * 768 + lane * 32);
#pragma unroll 1
        for (int m = 0; m < 16; m++) {
          pace(tstart, m < 4 ? WQT + m * 500 : QT + (m - 4) * QGAP);
          pf_line(m < 4 ? P.w_ptr + (size_t)(cta + (2 * m + (lane >> 4)) * 128) * 3072 + (lane & 15) * 64
                        : (m < 12 ? P.q_ptr + cta * 16384 - 8192 : P.wo_ptr + cta * 8192 - 24576) + m * 2048 + lane * 64);
        }
      }
      uint32_t f2[4];
      ldg128(f2, P.tab + 2560 + at * 4);
      if (at == 0) { mbar_wait_long(bar(B_U), 0); fence_async_smem(); mbar_arrive(bar(B_U2)); }
      mbar_wait_long(bar(B_KVM), 0);
      sts128(sb + SM_F2 + at * 16, f2[0], f2[1], f2[2], f2[3]);
      fence_async_smem();
      __syncwarp();
      mbar_arrive_if(bar(B_F2M), lane == 0);
      if (aw == 2 && elect()) {
        mbar_wait(bar(B_KVP), 0);
        asm volatile("fence.release.gpu;\nred.relaxed.gpu.global.add.u32 [%0], 1;" :: "l"(&P.g->kvflag[j * 32]) : "memory");
        flag_wait(&P.g->kvflag[j * 32], 16u * (epoch + 1));
        mbar_arrive(bar(B_KV));
        TSTAMP(true, 19);
      }
      __syncwarp();
      if (aw < 2) {
        {
          const int c = aw;
          if (c == 1) {
            mbar_wait_long(bar(B_KVI), 0);
            if (elect()) { prefetch_map(&P.o); prefetch_map(&P.outb); prefetch_map(&P.outa); }
          }
          mbar_wait_long(bar(B_OW + c), 0);
          if (c == 1) mbar_wait(bar(B_ZERO), 1);
          if (elect()) {
            const uint32_t src = sb + c * ST2;
            tma2d_store(&P.o, src, 128 * j + 64 * c, 128 * r);
            tma2d_store(&P.o, src + 8192, 128 * j + 64 * c, 128 * r + 64);
            bulk_commit();
            bulk_wait_all();
            TSTAMP(c == 0, 21); TSTAMP(c == 1, 26);
            if (c == 0) mbar_arrive(bar(B_ZERO));
            asm volatile("mbarrier.arrive.shared::cluster.b64 _, [%0];\nmbarrier.arrive.shared::cluster.b64 _, [%1];"
                         :: "r"(mapa(bar(B_OFREE), 0)), "r"(mapa(bar(B_OFREE), 1)) : "memory");
            asm volatile("fence.release.gpu;\nst.relaxed.gpu.global.u32 [%0], %1;\nmbarrier.arrive.shared::cluster.b64 _, [%2];"
                         :: "l"(&P.g->oflag[r * 32 + 2 * j + c]), "r"(epoch + 1), "r"(mapa(bar(B_RDY + c), rho ^ 1)) : "memory");
            TSTAMP(c == 0, 22); TSTAMP(c == 1, 23);
          }
          __syncwarp();
        }
      } else {
        const unsigned* fp = &P.g->oflag[r * 32 + (kcol(18 + min(lane, 13)) >> 6)];
        bool done = lane > 13 || lane < 2;
        mbar_wait_long(bar(B_OW), 0);
        for (int i = 0; !__all_sync(0xffffffffu, done) && i < kSpinLimit; i++) {
          const bool now = !done && (int)(ld_relaxed(fp) - epoch) > 0;
          if (__any_sync(0xffffffffu, now)) {
            asm volatile("fence.acquire.gpu;\nfence.proxy.async.global;" ::: "memory");
            mbar_arrive_if(bar(B_RDY + lane), now);
            TSTAMP(lane == 2 && now, 24);
          }
          done |= now;
        }
        if (lane == 0) P.g->epoch[cta] = epoch + 1;
        TSTAMP(lane == 0, 25);
      }
#pragma unroll 1
      for (int m = aw; m < 16; m += 3) {
        const int u = 4 * (m & 7) + 2 * (m >> 3);
        mbar_wait_long(bar(B_Y + (m >> 3)), 0);
        TSTAMP(at == 0 && m == 0, 20);
        const uint32_t t0 = clock32();
        const uint32_t qa = sb + RA + u * 1024 + lane * 32 + ((rho ^ 1 ^ (lane >> 2)) & 1) * 16, ya = sb + Y_IN + u * 512 + lane * 16;
        uint32_t qv[2][4], yv[2][4];
#pragma unroll
        for (int h = 0; h < 2; h++) { lds128(qv[h], qa + h * 1024); lds128(yv[h], ya + h * 512); }
#pragma unroll
        for (int h = 0; h < 2; h++) sts128(qa + h * 1024, bmul2(qv[h][0], yv[h][0]), bmul2(qv[h][1], yv[h][1]), bmul2(qv[h][2], yv[h][2]), bmul2(qv[h][3], yv[h][3]));
        fence_async_smem();
        __syncwarp();
        if (elect()) tma5d_store(&P.outb, sb + RA + u * 1024, 1024 + 16 * cl, 2 * rho, (u >> 4) * 4 + (u & 3), (u >> 2) & 3);
        if (m < 6) pace(t0, POSTGAP);
      }
      bulk_wait_read();
      TSTAMP(at == 0, 27);
    }
  }
  TSTAMP(tid == 128, 61); GSTAMP(tid == 128, 63);
}

typedef CUresult (*EncodeFn)(CUtensorMap*, CUtensorMapDataType, cuuint32_t, void*, const cuuint64_t*, const cuuint64_t*,
                             const cuuint32_t*, const cuuint32_t*, CUtensorMapInterleave, CUtensorMapSwizzle,
                             CUtensorMapL2promotion, CUtensorMapFloatOOBfill);

void encode(EncodeFn fn, CUtensorMap* m, const void* p, int rank, const cuuint64_t* dims, const cuuint64_t* strides,
            const cuuint32_t* box, CUtensorMapSwizzle sw) {
  const cuuint32_t es[5] = {1, 1, 1, 1, 1};
  fn(m, CU_TENSOR_MAP_DATA_TYPE_BFLOAT16, rank, const_cast<void*>(p), dims, strides, box, es, CU_TENSOR_MAP_INTERLEAVE_NONE, sw,
     CU_TENSOR_MAP_L2_PROMOTION_NONE, CU_TENSOR_MAP_FLOAT_OOB_FILL_NONE);
}
void encode2d(EncodeFn fn, CUtensorMap* m, const void* p, uint64_t cols, uint64_t rows, uint32_t bc, uint32_t br, CUtensorMapSwizzle sw) {
  const cuuint64_t dims[2] = {cols, rows}, strides[1] = {cols * 2};
  const cuuint32_t box[2] = {bc, br};
  encode(fn, m, p, 2, dims, strides, box, sw);
}
void encode3d(EncodeFn fn, CUtensorMap* m, const void* p) {
  const cuuint64_t dims[3] = {1024, 64, 32}, strides[2] = {2048 * 32, 2048};
  const cuuint32_t box[3] = {16, 32, 4};
  encode(fn, m, p, 3, dims, strides, box, CU_TENSOR_MAP_SWIZZLE_32B);
}
void encode4d(EncodeFn fn, CUtensorMap* m, const void* p, uint64_t cols, uint32_t rows, uint32_t nmat) {
  const cuuint64_t dims[4] = {64, 1024, 16, cols / 1024}, strides[3] = {cols * 2, 128, 2048};
  const cuuint32_t box[4] = {64, rows, 2, nmat};
  encode(fn, m, p, 4, dims, strides, box, CU_TENSOR_MAP_SWIZZLE_128B);
}
void encode5d(EncodeFn fn, CUtensorMap* m, const void* p, uint64_t cols, uint32_t n, uint32_t nw) {
  const cuuint64_t dims[5] = {cols, 4, 16, 8, 4}, strides[4] = {cols * 2 * 512, cols * 2 * 8, cols * 2, cols * 2 * 128};
  const cuuint32_t box[5] = {16, 2, 16, n, nw};
  encode(fn, m, p, 5, dims, strides, box, CU_TENSOR_MAP_SWIZZLE_32B);
}

}

extern "C" void kernel_launch(void* const* d_in, const int* in_sizes, int n_in, void* d_out, int out_size) {
  static EncodeFn fn = nullptr;
  static void *o_ptr = nullptr, *g_ptr = nullptr, *tab_ptr = nullptr;
  if (!fn) {
    cudaDriverEntryPointQueryResult qr;
    cudaGetDriverEntryPoint("cuTensorMapEncodeTiled", (void**)&fn, cudaEnableDefault, &qr);
    cudaGetSymbolAddress(&o_ptr, g_o);
    cudaGetSymbolAddress(&g_ptr, g_scratch);
    cudaGetSymbolAddress(&tab_ptr, d_tab);
    cudaFuncSetAttribute(fused_kernel, cudaFuncAttributeMaxDynamicSharedMemorySize, SM_TOTAL);
  }
  Params P;
  encode4d(fn, &P.w1, d_in[1], 3072, 32, 2);
  encode2d(fn, &P.x, d_in[0], 1024, 2048, 64, 64, CU_TENSOR_MAP_SWIZZLE_128B);
  encode4d(fn, &P.w2, d_in[1], 3072, 64, 1);
  encode4d(fn, &P.wo, d_in[2], 1024, 64, 1);
  encode2d(fn, &P.o, o_ptr, 1024, 2048, 64, 64, CU_TENSOR_MAP_SWIZZLE_128B);
  encode2d(fn, &P.outa, d_out, 2048, 2048, 64, 16, CU_TENSOR_MAP_SWIZZLE_128B);
  encode3d(fn, &P.k, d_in[4]);
  encode3d(fn, &P.v, d_in[5]);
  encode5d(fn, &P.q, d_in[3], 1024, 4, 2);
  encode5d(fn, &P.outb, d_out, 2048, 2, 1);
  P.shift_k = (const __nv_bfloat16*)d_in[6];
  P.ssm_k = (const __nv_bfloat16*)d_in[7];
  P.ssm_d = (const __nv_bfloat16*)d_in[8];
  P.q_ptr = (const __nv_bfloat16*)d_in[3];
  P.w_ptr = (const __nv_bfloat16*)d_in[1];
  P.wo_ptr = (const __nv_bfloat16*)d_in[2];
  P.zero = 0;
  P.g = (Scratch*)g_ptr;
  P.tab = (const uint32_t*)tab_ptr;
  fused_kernel<<<kCtas, kThreads, SM_TOTAL>>>(P);
}
```

```cpp
#include <cuda.h>
#include <cuda_runtime.h>
#include <cuda_bf16.h>
#include <stdint.h>

#define DEVI __device__ __forceinline__
#define INL __attribute__((always_inline))

namespace {

DEVI void mma_kt_init(float* d, uint64_t da, uint64_t db) {
  asm volatile("{\nwgmma.mma_async.sync.aligned.m64n128k16.f32.bf16.bf16 {%0, %1, %2, %3, %4, %5, %6, %7, %8, %9, %10, %11, %12, %13, %14, %15, %16, %17, %18, %19, %20, %21, %22, %23, %24, %25, %26, %27, %28, %29, %30, %31, %32, %33, %34, %35, %36, %37, %38, %39, %40, %41, %42, %43, %44, %45, %46, %47, %48, %49, %50, %51, %52, %53, %54, %55, %56, %57, %58, %59, %60, %61, %62, %63}, %64, %65, 0, 1, 1, 1, 0;\n}\n"
    : "=f"(d[0]), "=f"(d[1]), "=f"(d[2]), "=f"(d[3]), "=f"(d[4]), "=f"(d[5]), "=f"(d[6]), "=f"(d[7]), "=f"(d[8]), "=f"(d[9]), "=f"(d[10]), "=f"(d[11]), "=f"(d[12]), "=f"(d[13]), "=f"(d[14]), "=f"(d[15]), "=f"(d[16]), "=f"(d[17]), "=f"(d[18]), "=f"(d[19]), "=f"(d[20]), "=f"(d[21]), "=f"(d[22]), "=f"(d[23]), "=f"(d[24]), "=f"(d[25]), "=f"(d[26]), "=f"(d[27]), "=f"(d[28]), "=f"(d[29]), "=f"(d[30]), "=f"(d[31]), "=f"(d[32]), "=f"(d[33]), "=f"(d[34]), "=f"(d[35]), "=f"(d[36]), "=f"(d[37]), "=f"(d[38]), "=f"(d[39]), "=f"(d[40]), "=f"(d[41]), "=f"(d[42]), "=f"(d[43]), "=f"(d[44]), "=f"(d[45]), "=f"(d[46]), "=f"(d[47]), "=f"(d[48]), "=f"(d[49]), "=f"(d[50]), "=f"(d[51]), "=f"(d[52]), "=f"(d[53]), "=f"(d[54]), "=f"(d[55]), "=f"(d[56]), "=f"(d[57]), "=f"(d[58]), "=f"(d[59]), "=f"(d[60]), "=f"(d[61]), "=f"(d[62]), "=f"(d[63])
    : "l"(da), "l"(db));
}
DEVI void mma_kt(float* d, uint64_t da, uint64_t db) {
  asm volatile("{\nwgmma.mma_async.sync.aligned.m64n128k16.f32.bf16.bf16 {%0, %1, %2, %3, %4, %5, %6, %7, %8, %9, %10, %11, %12, %13, %14, %15, %16, %17, %18, %19, %20, %21, %22, %23, %24, %25, %26, %27, %28, %29, %30, %31, %32, %33, %34, %35, %36, %37, %38, %39, %40, %41, %42, %43, %44, %45, %46, %47, %48, %49, %50, %51, %52, %53, %54, %55, %56, %57, %58, %59, %60, %61, %62, %63}, %64, %65, 1, 1, 1, 1, 0;\n}\n"
    : "+f"(d[0]), "+f"(d[1]), "+f"(d[2]), "+f"(d[3]), "+f"(d[4]), "+f"(d[5]), "+f"(d[6]), "+f"(d[7]), "+f"(d[8]), "+f"(d[9]), "+f"(d[10]), "+f"(d[11]), "+f"(d[12]), "+f"(d[13]), "+f"(d[14]), "+f"(d[15]), "+f"(d[16]), "+f"(d[17]), "+f"(d[18]), "+f"(d[19]), "+f"(d[20]), "+f"(d[21]), "+f"(d[22]), "+f"(d[23]), "+f"(d[24]), "+f"(d[25]), "+f"(d[26]), "+f"(d[27]), "+f"(d[28]), "+f"(d[29]), "+f"(d[30]), "+f"(d[31]), "+f"(d[32]), "+f"(d[33]), "+f"(d[34]), "+f"(d[35]), "+f"(d[36]), "+f"(d[37]), "+f"(d[38]), "+f"(d[39]), "+f"(d[40]), "+f"(d[41]), "+f"(d[42]), "+f"(d[43]), "+f"(d[44]), "+f"(d[45]), "+f"(d[46]), "+f"(d[47]), "+f"(d[48]), "+f"(d[49]), "+f"(d[50]), "+f"(d[51]), "+f"(d[52]), "+f"(d[53]), "+f"(d[54]), "+f"(d[55]), "+f"(d[56]), "+f"(d[57]), "+f"(d[58]), "+f"(d[59]), "+f"(d[60]), "+f"(d[61]), "+f"(d[62]), "+f"(d[63])
    : "l"(da), "l"(db));
}
DEVI void mma_n128_init(float* d, uint64_t da, uint64_t db) {
  asm volatile("{\nwgmma.mma_async.sync.aligned.m64n128k16.f32.bf16.bf16 {%0, %1, %2, %3, %4, %5, %6, %7, %8, %9, %10, %11, %12, %13, %14, %15, %16, %17, %18, %19, %20, %21, %22, %23, %24, %25, %26, %27, %28, %29, %30, %31, %32, %33, %34, %35, %36, %37, %38, %39, %40, %41, %42, %43, %44, %45, %46, %47, %48, %49, %50, %51, %52, %53, %54, %55, %56, %57, %58, %59, %60, %61, %62, %63}, %64, %65, 0, 1, 1, 0, 1;\n}\n"
    : "=f"(d[0]), "=f"(d[1]), "=f"(d[2]), "=f"(d[3]), "=f"(d[4]), "=f"(d[5]), "=f"(d[6]), "=f"(d[7]), "=f"(d[8]), "=f"(d[9]), "=f"(d[10]), "=f"(d[11]), "=f"(d[12]), "=f"(d[13]), "=f"(d[14]), "=f"(d[15]), "=f"(d[16]), "=f"(d[17]), "=f"(d[18]), "=f"(d[19]), "=f"(d[20]), "=f"(d[21]), "=f"(d[22]), "=f"(d[23]), "=f"(d[24]), "=f"(d[25]), "=f"(d[26]), "=f"(d[27]), "=f"(d[28]), "=f"(d[29]), "=f"(d[30]), "=f"(d[31]), "=f"(d[32]), "=f"(d[33]), "=f"(d[34]), "=f"(d[35]), "=f"(d[36]), "=f"(d[37]), "=f"(d[38]), "=f"(d[39]), "=f"(d[40]), "=f"(d[41]), "=f"(d[42]), "=f"(d[43]), "=f"(d[44]), "=f"(d[45]), "=f"(d[46]), "=f"(d[47]), "=f"(d[48]), "=f"(d[49]), "=f"(d[50]), "=f"(d[51]), "=f"(d[52]), "=f"(d[53]), "=f"(d[54]), "=f"(d[55]), "=f"(d[56]), "=f"(d[57]), "=f"(d[58]), "=f"(d[59]), "=f"(d[60]), "=f"(d[61]), "=f"(d[62]), "=f"(d[63])
    : "l"(da), "l"(db));
}
DEVI void mma_n128(float* d, uint64_t da, uint64_t db) {
  asm volatile("{\nwgmma.mma_async.sync.aligned.m64n128k16.f32.bf16.bf16 {%0, %1, %2, %3, %4, %5, %6, %7, %8, %9, %10, %11, %12, %13, %14, %15, %16, %17, %18, %19, %20, %21, %22, %23, %24, %25, %26, %27, %28, %29, %30, %31, %32, %33, %34, %35, %36, %37, %38, %39, %40, %41, %42, %43, %44, %45, %46, %47, %48, %49, %50, %51, %52, %53, %54, %55, %56, %57, %58, %59, %60, %61, %62, %63}, %64, %65, 1, 1, 1, 0, 1;\n}\n"
    : "+f"(d[0]), "+f"(d[1]), "+f"(d[2]), "+f"(d[3]), "+f"(d[4]), "+f"(d[5]), "+f"(d[6]), "+f"(d[7]), "+f"(d[8]), "+f"(d[9]), "+f"(d[10]), "+f"(d[11]), "+f"(d[12]), "+f"(d[13]), "+f"(d[14]), "+f"(d[15]), "+f"(d[16]), "+f"(d[17]), "+f"(d[18]), "+f"(d[19]), "+f"(d[20]), "+f"(d[21]), "+f"(d[22]), "+f"(d[23]), "+f"(d[24]), "+f"(d[25]), "+f"(d[26]), "+f"(d[27]), "+f"(d[28]), "+f"(d[29]), "+f"(d[30]), "+f"(d[31]), "+f"(d[32]), "+f"(d[33]), "+f"(d[34]), "+f"(d[35]), "+f"(d[36]), "+f"(d[37]), "+f"(d[38]), "+f"(d[39]), "+f"(d[40]), "+f"(d[41]), "+f"(d[42]), "+f"(d[43]), "+f"(d[44]), "+f"(d[45]), "+f"(d[46]), "+f"(d[47]), "+f"(d[48]), "+f"(d[49]), "+f"(d[50]), "+f"(d[51]), "+f"(d[52]), "+f"(d[53]), "+f"(d[54]), "+f"(d[55]), "+f"(d[56]), "+f"(d[57]), "+f"(d[58]), "+f"(d[59]), "+f"(d[60]), "+f"(d[61]), "+f"(d[62]), "+f"(d[63])
    : "l"(da), "l"(db));
}
DEVI void mma_kv_init(float* d, const uint32_t* a, uint64_t db) {
  asm volatile("{\nwgmma.mma_async.sync.aligned.m64n72k16.f32.bf16.bf16 {%0, %1, %2, %3, %4, %5, %6, %7, %8, %9, %10, %11, %12, %13, %14, %15, %16, %17, %18, %19, %20, %21, %22, %23, %24, %25, %26, %27, %28, %29, %30, %31, %32, %33, %34, %35}, {%36,%37,%38,%39}, %40, 0, 1, 1, 1;\n}\n"
    : "=f"(d[0]), "=f"(d[1]), "=f"(d[2]), "=f"(d[3]), "=f"(d[4]), "=f"(d[5]), "=f"(d[6]), "=f"(d[7]), "=f"(d[8]), "=f"(d[9]), "=f"(d[10]), "=f"(d[11]), "=f"(d[12]), "=f"(d[13]), "=f"(d[14]), "=f"(d[15]), "=f"(d[16]), "=f"(d[17]), "=f"(d[18]), "=f"(d[19]), "=f"(d[20]), "=f"(d[21]), "=f"(d[22]), "=f"(d[23]), "=f"(d[24]), "=f"(d[25]), "=f"(d[26]), "=f"(d[27]), "=f"(d[28]), "=f"(d[29]), "=f"(d[30]), "=f"(d[31]), "=f"(d[32]), "=f"(d[33]), "=f"(d[34]), "=f"(d[35])
    : "r"(a[0]), "r"(a[1]), "r"(a[2]), "r"(a[3]), "l"(db));
}
DEVI void mma_kv(float* d, const uint32_t* a, uint64_t db) {
  asm volatile("{\nwgmma.mma_async.sync.aligned.m64n72k16.f32.bf16.bf16 {%0, %1, %2, %3, %4, %5, %6, %7, %8, %9, %10, %11, %12, %13, %14, %15, %16, %17, %18, %19, %20, %21, %22, %23, %24, %25, %26, %27, %28, %29, %30, %31, %32, %33, %34, %35}, {%36,%37,%38,%39}, %40, 1, 1, 1, 1;\n}\n"
    : "+f"(d[0]), "+f"(d[1]), "+f"(d[2]), "+f"(d[3]), "+f"(d[4]), "+f"(d[5]), "+f"(d[6]), "+f"(d[7]), "+f"(d[8]), "+f"(d[9]), "+f"(d[10]), "+f"(d[11]), "+f"(d[12]), "+f"(d[13]), "+f"(d[14]), "+f"(d[15]), "+f"(d[16]), "+f"(d[17]), "+f"(d[18]), "+f"(d[19]), "+f"(d[20]), "+f"(d[21]), "+f"(d[22]), "+f"(d[23]), "+f"(d[24]), "+f"(d[25]), "+f"(d[26]), "+f"(d[27]), "+f"(d[28]), "+f"(d[29]), "+f"(d[30]), "+f"(d[31]), "+f"(d[32]), "+f"(d[33]), "+f"(d[34]), "+f"(d[35])
    : "r"(a[0]), "r"(a[1]), "r"(a[2]), "r"(a[3]), "l"(db));
}
DEVI void mma_o_init(float* d, const uint32_t* a, uint64_t db) {
  asm volatile("{\nwgmma.mma_async.sync.aligned.m64n40k16.f32.bf16.bf16 {%0, %1, %2, %3, %4, %5, %6, %7, %8, %9, %10, %11, %12, %13, %14, %15, %16, %17, %18, %19}, {%20,%21,%22,%23}, %24, 0, 1, 1, 1;\n}\n"
    : "=f"(d[0]), "=f"(d[1]), "=f"(d[2]), "=f"(d[3]), "=f"(d[4]), "=f"(d[5]), "=f"(d[6]), "=f"(d[7]), "=f"(d[8]), "=f"(d[9]), "=f"(d[10]), "=f"(d[11]), "=f"(d[12]), "=f"(d[13]), "=f"(d[14]), "=f"(d[15]), "=f"(d[16]), "=f"(d[17]), "=f"(d[18]), "=f"(d[19])
    : "r"(a[0]), "r"(a[1]), "r"(a[2]), "r"(a[3]), "l"(db));
}
DEVI void mma_o(float* d, const uint32_t* a, uint64_t db) {
  asm volatile("{\nwgmma.mma_async.sync.aligned.m64n40k16.f32.bf16.bf16 {%0, %1, %2, %3, %4, %5, %6, %7, %8, %9, %10, %11, %12, %13, %14, %15, %16, %17, %18, %19}, {%20,%21,%22,%23}, %24, 1, 1, 1, 1;\n}\n"
    : "+f"(d[0]), "+f"(d[1]), "+f"(d[2]), "+f"(d[3]), "+f"(d[4]), "+f"(d[5]), "+f"(d[6]), "+f"(d[7]), "+f"(d[8]), "+f"(d[9]), "+f"(d[10]), "+f"(d[11]), "+f"(d[12]), "+f"(d[13]), "+f"(d[14]), "+f"(d[15]), "+f"(d[16]), "+f"(d[17]), "+f"(d[18]), "+f"(d[19])
    : "r"(a[0]), "r"(a[1]), "r"(a[2]), "r"(a[3]), "l"(db));
}
DEVI void mma_s1_init(uint32_t* d, const uint32_t* a, uint64_t db) {
  asm volatile("{\nwgmma.mma_async.sync.aligned.m64n128k16.f16.f16.f16 {%0, %1, %2, %3, %4, %5, %6, %7, %8, %9, %10, %11, %12, %13, %14, %15, %16, %17, %18, %19, %20, %21, %22, %23, %24, %25, %26, %27, %28, %29, %30, %31}, {%32,%33,%34,%35}, %36, 0, 1, 1, 1;\n}\n"
    : "=r"(d[0]), "=r"(d[1]), "=r"(d[2]), "=r"(d[3]), "=r"(d[4]), "=r"(d[5]), "=r"(d[6]), "=r"(d[7]), "=r"(d[8]), "=r"(d[9]), "=r"(d[10]), "=r"(d[11]), "=r"(d[12]), "=r"(d[13]), "=r"(d[14]), "=r"(d[15]), "=r"(d[16]), "=r"(d[17]), "=r"(d[18]), "=r"(d[19]), "=r"(d[20]), "=r"(d[21]), "=r"(d[22]), "=r"(d[23]), "=r"(d[24]), "=r"(d[25]), "=r"(d[26]), "=r"(d[27]), "=r"(d[28]), "=r"(d[29]), "=r"(d[30]), "=r"(d[31])
    : "r"(a[0]), "r"(a[1]), "r"(a[2]), "r"(a[3]), "l"(db));
}
DEVI void mma_s1(uint32_t* d, const uint32_t* a, uint64_t db) {
  asm volatile("{\nwgmma.mma_async.sync.aligned.m64n128k16.f16.f16.f16 {%0, %1, %2, %3, %4, %5, %6, %7, %8, %9, %10, %11, %12, %13, %14, %15, %16, %17, %18, %19, %20, %21, %22, %23, %24, %25, %26, %27, %28, %29, %30, %31}, {%32,%33,%34,%35}, %36, 1, 1, 1, 1;\n}\n"
    : "+r"(d[0]), "+r"(d[1]), "+r"(d[2]), "+r"(d[3]), "+r"(d[4]), "+r"(d[5]), "+r"(d[6]), "+r"(d[7]), "+r"(d[8]), "+r"(d[9]), "+r"(d[10]), "+r"(d[11]), "+r"(d[12]), "+r"(d[13]), "+r"(d[14]), "+r"(d[15]), "+r"(d[16]), "+r"(d[17]), "+r"(d[18]), "+r"(d[19]), "+r"(d[20]), "+r"(d[21]), "+r"(d[22]), "+r"(d[23]), "+r"(d[24]), "+r"(d[25]), "+r"(d[26]), "+r"(d[27]), "+r"(d[28]), "+r"(d[29]), "+r"(d[30]), "+r"(d[31])
    : "r"(a[0]), "r"(a[1]), "r"(a[2]), "r"(a[3]), "l"(db));
}
DEVI void mma_s2_init(uint32_t* d, const uint32_t* a, uint64_t db) {
  asm volatile("{\nwgmma.mma_async.sync.aligned.m64n32k16.f16.f16.f16 {%0, %1, %2, %3, %4, %5, %6, %7}, {%8,%9,%10,%11}, %12, 0, 1, 1, 0;\n}\n"
    : "=r"(d[0]), "=r"(d[1]), "=r"(d[2]), "=r"(d[3]), "=r"(d[4]), "=r"(d[5]), "=r"(d[6]), "=r"(d[7])
    : "r"(a[0]), "r"(a[1]), "r"(a[2]), "r"(a[3]), "l"(db));
}
DEVI void mma_s2(uint32_t* d, const uint32_t* a, uint64_t db) {
  asm volatile("{\nwgmma.mma_async.sync.aligned.m64n32k16.f16.f16.f16 {%0, %1, %2, %3, %4, %5, %6, %7}, {%8,%9,%10,%11}, %12, 1, 1, 1, 0;\n}\n"
    : "+r"(d[0]), "+r"(d[1]), "+r"(d[2]), "+r"(d[3]), "+r"(d[4]), "+r"(d[5]), "+r"(d[6]), "+r"(d[7])
    : "r"(a[0]), "r"(a[1]), "r"(a[2]), "r"(a[3]), "l"(db));
}
DEVI void mma_s2_neg(uint32_t* d, const uint32_t* a, uint64_t db) {
  asm volatile("{\nwgmma.mma_async.sync.aligned.m64n32k16.f16.f16.f16 {%0, %1, %2, %3, %4, %5, %6, %7}, {%8,%9,%10,%11}, %12, 1, -1, 1, 0;\n}\n"
    : "+r"(d[0]), "+r"(d[1]), "+r"(d[2]), "+r"(d[3]), "+r"(d[4]), "+r"(d[5]), "+r"(d[6]), "+r"(d[7])
    : "r"(a[0]), "r"(a[1]), "r"(a[2]), "r"(a[3]), "l"(db));
}
DEVI void mma_i2_init(float* d, const uint32_t* a, uint64_t db, uint32_t meta) {
  asm volatile("{\nwgmma.mma_async.sp.sync.aligned.m64n128k32.f32.f16.f16 {%0, %1, %2, %3, %4, %5, %6, %7, %8, %9, %10, %11, %12, %13, %14, %15, %16, %17, %18, %19, %20, %21, %22, %23, %24, %25, %26, %27, %28, %29, %30, %31, %32, %33, %34, %35, %36, %37, %38, %39, %40, %41, %42, %43, %44, %45, %46, %47, %48, %49, %50, %51, %52, %53, %54, %55, %56, %57, %58, %59, %60, %61, %62, %63}, {%64,%65,%66,%67}, %68, %69, 0, 0, 1, 1, 1;\n}\n"
    : "=f"(d[0]), "=f"(d[1]), "=f"(d[2]), "=f"(d[3]), "=f"(d[4]), "=f"(d[5]), "=f"(d[6]), "=f"(d[7]), "=f"(d[8]), "=f"(d[9]), "=f"(d[10]), "=f"(d[11]), "=f"(d[12]), "=f"(d[13]), "=f"(d[14]), "=f"(d[15]), "=f"(d[16]), "=f"(d[17]), "=f"(d[18]), "=f"(d[19]), "=f"(d[20]), "=f"(d[21]), "=f"(d[22]), "=f"(d[23]), "=f"(d[24]), "=f"(d[25]), "=f"(d[26]), "=f"(d[27]), "=f"(d[28]), "=f"(d[29]), "=f"(d[30]), "=f"(d[31]), "=f"(d[32]), "=f"(d[33]), "=f"(d[34]), "=f"(d[35]), "=f"(d[36]), "=f"(d[37]), "=f"(d[38]), "=f"(d[39]), "=f"(d[40]), "=f"(d[41]), "=f"(d[42]), "=f"(d[43]), "=f"(d[44]), "=f"(d[45]), "=f"(d[46]), "=f"(d[47]), "=f"(d[48]), "=f"(d[49]), "=f"(d[50]), "=f"(d[51]), "=f"(d[52]), "=f"(d[53]), "=f"(d[54]), "=f"(d[55]), "=f"(d[56]), "=f"(d[57]), "=f"(d[58]), "=f"(d[59]), "=f"(d[60]), "=f"(d[61]), "=f"(d[62]), "=f"(d[63])
    : "r"(a[0]), "r"(a[1]), "r"(a[2]), "r"(a[3]), "l"(db), "r"(meta));
}
DEVI void mma_i2(float* d, const uint32_t* a, uint64_t db, uint32_t meta) {
  asm volatile("{\nwgmma.mma_async.sp.sync.aligned.m64n128k32.f32.f16.f16 {%0, %1, %2, %3, %4, %5, %6, %7, %8, %9, %10, %11, %12, %13, %14, %15, %16, %17, %18, %19, %20, %21, %22, %23, %24, %25, %26, %27, %28, %29, %30, %31, %32, %33, %34, %35, %36, %37, %38, %39, %40, %41, %42, %43, %44, %45, %46, %47, %48, %49, %50, %51, %52, %53, %54, %55, %56, %57, %58, %59, %60, %61, %62, %63}, {%64,%65,%66,%67}, %68, %69, 0, 1, 1, 1, 1;\n}\n"
    : "+f"(d[0]), "+f"(d[1]), "+f"(d[2]), "+f"(d[3]), "+f"(d[4]), "+f"(d[5]), "+f"(d[6]), "+f"(d[7]), "+f"(d[8]), "+f"(d[9]), "+f"(d[10]), "+f"(d[11]), "+f"(d[12]), "+f"(d[13]), "+f"(d[14]), "+f"(d[15]), "+f"(d[16]), "+f"(d[17]), "+f"(d[18]), "+f"(d[19]), "+f"(d[20]), "+f"(d[21]), "+f"(d[22]), "+f"(d[23]), "+f"(d[24]), "+f"(d[25]), "+f"(d[26]), "+f"(d[27]), "+f"(d[28]), "+f"(d[29]), "+f"(d[30]), "+f"(d[31]), "+f"(d[32]), "+f"(d[33]), "+f"(d[34]), "+f"(d[35]), "+f"(d[36]), "+f"(d[37]), "+f"(d[38]), "+f"(d[39]), "+f"(d[40]), "+f"(d[41]), "+f"(d[42]), "+f"(d[43]), "+f"(d[44]), "+f"(d[45]), "+f"(d[46]), "+f"(d[47]), "+f"(d[48]), "+f"(d[49]), "+f"(d[50]), "+f"(d[51]), "+f"(d[52]), "+f"(d[53]), "+f"(d[54]), "+f"(d[55]), "+f"(d[56]), "+f"(d[57]), "+f"(d[58]), "+f"(d[59]), "+f"(d[60]), "+f"(d[61]), "+f"(d[62]), "+f"(d[63])
    : "r"(a[0]), "r"(a[1]), "r"(a[2]), "r"(a[3]), "l"(db), "r"(meta));
}
__device__ const __align__(128) uint32_t d_tab[2944] = {
  0x3bf13bff,0x2fbd25e4,0x38ee3986,0x3a4d39c9,0x3b9a3bcf,0x34ff32f7,0x3737384a,0x3b243ac1,0x3af73b52,0x37dd3676,0x344b35c8,0x3bb53b76,
  0x3a113a8c,0x39373899,0x2cce3185,0x3bfa3be1,0x3a933bf2,0x388e2f59,0xb1b6b8f8,0xbbdfba45,0xa452374e,0x3c003b1e,0x39c034e7,0xb990bb9e,
  0xbabab7c8,0x38553afe,0x3bd23bb2,0x32c6b463,0xbb57bbf9,0xb65f2d33,0x35df3a19,0x3b71392e,0x37643bd4,0x3b183294,0xb4cf385f,0x3ba13ab3,
  0xbbaeb648,0x347b3b5c,0xbb04bb6c,0xb7b235f7,0xad97ba9b,0xbbf8b884,0x3924b1e8,0xba21bbdd,0x3bf439b8,0x2ef5b999,0x39023c00,0x3a3d217f,
  0x9cb63ba5,0x3c0034b7,0x39afb77a,0xb9a1bb13,0xb86abbab,0xbaac3493,0xb2633b0a,0x3bd7379b,0x3b60391b,0x3631ba29,0xb60ebbf7,0xbb682dfb,
  0xbbdaae91,0x32193bf5,0x3aa23a35,0x387ab90c,0xb7853b65,0x3b10361a,0xbba73625,0x34ab3b63,0x3911baa9,0xba31b86f,0x3bf6b24b,0xae5fbbd8,
  0xba2d39aa,0x391639a6,0xbbf61648,0xae2d3c00,0x3b0db874,0xb790baa5,0x3ba93232,0x349fbbd9,0xba9e3b16,0x387f376f,0x3bdcb4c3,0x3201bba3,
  0x3b6aaec3,0x3602bbf5,0xb63cb907,0xbb5e3a39,0xb27cba25,0xbbd6391f,0xb8653bf8,0x3ab02dc9,0xb99d3bac,0x39b33487,0x3c00b7a6,0x9fdbbb07,
  0xbbf33ab6,0x2f27385a,0xba4132ad,0xb8fd3bd3,0xad653994,0x3bf9b9bc,0xba1d3c00,0x3929a311,0x3bb0b889,0x346fba97,0x37bd31cf,0x3b01bbde,
  0x3759bb59,0xbb1b3654,0x3b9fbb6f,0xb4dbb5eb,0xbb733a49,0xb5d438f3,0x366baf8b,0x3b54bbf2,0xbbd03bfa,0x32de2d00,0x3abdb933,0x3850ba15,
  0xb98b3afb,0x39c5b7d2,0x3c00bbb3,0xa51bb457,0xb19e3742,0x3be0bb21,0x3a90bb9c,0xb89434f3,0xb93c39cd,0xba0d3982,0x2c9c26ad,0xbbfb3bff,
  0xb7e8389e,0xbaf43a89,0x343eb16c,0xbbb73be2,0xb50b3682,0xbb983b4f,0x372cb5bc,0xbb273b78,0xafef330f,0xbbf03bce,0x38eab845,0xba503ac4,
  0xb3403946,0xbbcb3a04,0xb83a2c38,0x3acbbbfc,0x3979b426,0xb9d63bba,0xbbff3aee,0x281fb7fe,0x3be4bb94,0x313b3523,0xb8a83b2c,0xba813715,
  0x3699ba58,0x3b4ab8e0,0x35a53029,0xbb7c3bef,0x340e38b2,0xbbbd3a7a,0x3ae8b109,0xb80a3be6,0x3b32bb45,0x36ff36af,0x353abb81,0x3b90b58d,
  0xb8d6b371,0x3a60bbc8,0xbbed3830,0x305bbad1,0xb94f3bfe,0xb9fca8e8,0x2ba739df,0xbbfc3970,0x39663815,0xb9e73ae1,0xbbfe33eb,0x29b1bbc0,
  0xb0d7bb37,0x3be8b6e8,0x3a733552,0xb8bc3b8b,0xb6c63beb,0xbb3fb08d,0xb576ba67,0x3b85b8cc,0x3ad8b9f4,0x38253958,0xb3a23bfd,0xbbc52ade,
  0x3b8736dd,0xb56a3b3a,0x3b3db55e,0x36d23b89,0xbbe9b3d3,0x30bebbc2,0xba6f381a,0xb8c1bade,0x3bfe2a7a,0x2a163bfd,0x3962b95d,0x39eb39f0,
  0xbbc330a6,0xb3babbea,0xb8203a6b,0xbadbb8c7,0x3bec3581,0x30743b83,0xb8d136bb,0xba64bb42,0xb6f438b7,0xbb35ba76,0xb546bbe7,0x3b8e30f0,
  0xb80fbbfe,0x3ae5a94d,0x3bbf396b,0xb40239e3,0x3bfd382a,0xab433ad5,0xb9f83389,0xb954bbc6,0x3a7e341a,0x38ad3bbc,0x3122b805,0x3be53aeb,
  0x39da3bfc,0xb974ac06,0x3bff3a00,0x2884394a,0xb8353042,0xbacebbee,0x33593a5c,0xbbc9b8db,0xbb7fbb92,0x3599b52f,0xbb47b70a,0xb6a4bb2f,
  0x37213153,0x3b2a3be3,0x351738a3,0xbb96ba85,0x3af1397d,0x37f339d2,0xb4322776,0xbbb8bbff,0x3bfb3bcc,0xac6a3328,0xba09b840,0xb941bac7,
  0x3a543b7a,0xb8e5b5b1,0xbbefbb4c,0xb010b68d,0x32f72fbd,0xbbcfbbf1,0x3ac13a4d,0xb84ab8ee,0x367634ff,0xbb52bb9a,0x3b763b24,0xb5c8b737,
  0x389937dd,0xba8cbaf7,0x3be13bb5,0xb185b44b,0x39c93937,0xb986ba11,0x3bff3bfa,0x25e4acce,0x392e32c6,0xba19bbd2,0xbbf9baba,0x2d333855,
  0x3bf23b71,0x2f59b5df,0xb8f8bb57,0xba45b65f,0x374e3a93,0x3b1e388e,0x34e7b1b6,0xbb9ebbdf,0xb7c8a452,0x3afe3c00,0x3bb239c0,0xb463b990,
  0x3b6c34cf,0xb5f7bba1,0x3b5c3b18,0x3648b764,0x31e83b04,0x3bdd37b2,0xb884347b,0x3a9b3bae,0xbc00b924,0xa17f3a21,0xb999bbf8,0xb9b82d97,
  0x3294b902,0xbbd4ba3d,0x3ab32ef5,0xb85fbbf4,0x3bf53631,0x2e91bb60,0xb90cbb68,0xba35360e,0xbb133219,0x377a3bda,0x3ba5387a,0x34b7baa2,
  0x379bb9a1,0xbb0ab9af,0xbbab9cb6,0x34933c00,0x2dfb3bd7,0x3bf73263,0x391bb86a,0xba29baac,0x3aa93785,0x386fbb10,0x324b3ba7,0x3bd8b4ab,
  0xb9aab911,0xb9a63a31,0x9648bbf6,0xbc002e5f,0x38743a2d,0x3aa5b916,0xb2323bf6,0x3bd92e2d,0xb625bb0d,0xbb633790,0x361abba9,0xbb65b49f,
  0x37a63865,0x3b07bab0,0x3487bbd6,0xbbac327c,0x376fbc00,0xbb161fdb,0xbba339b3,0x34c3399d,0xbbf5387f,0x2ec33a9e,0x3a393201,0x3907bbdc,
  0x391f3602,0x3a25bb6a,0x2dc9bb5e,0xbbf8363c,0x231138fd,0x3c00ba41,0xb9943bf3,0x39bcaf27,0x3bdeb929,0x31cfba1d,0x38892d65,0x3a97bbf9,
  0x35ebbb01,0xbb6f37bd,0x3b59bbb0,0xb654b46f,0xbab634db,0xb85a3b9f,0xb2adb759,0xbbd33b1b,0xb742398b,0x3b21b9c5,0x3b9cbc00,0xb4f3251b,
  0x2f8b319e,0x3bf2bbe0,0x38f3ba90,0xba493894,0x3933b66b,0x3a15bb54,0x2d00b5d4,0xbbfa3b73,0x3bb3babd,0x3457b850,0xb7d232de,0xbafb3bd0,
  0xba893a0d,0x389eb93c,0xbbe23bfb,0xb16c2c9c,0xbb4f3af4,0x3682b7e8,0xbb783bb7,0xb5bc343e,0xbbce3b98,0x330fb50b,0xbac43b27,0xb845372c,
  0xbbff3bf0,0x26adafef,0xb9cd3a50,0xb98238ea,0xbbef3a81,0x3029b8a8,0x3a58bbe4,0x38e0b13b,0xb9463b7c,0xba0435a5,0xac38b699,0x3bfcbb4a,
  0x34263340,0xbbba3bcb,0xbaee383a,0x37febacb,0x3b94b979,0xb52339d6,0xbb2c3bff,0xb715a81f,0xbb813ae8,0xb58db80a,0xb6af3bbd,0xbb45340e,
  0x3830353a,0xbad13b90,0x3bc8b6ff,0xb3713b32,0x39dfbbed,0x3970305b,0x28e8ba60,0x3bfeb8d6,0xba7a2ba7,0x38b2bbfc,0xbbe639fc,0xb109b94f,
  0xb9583b3f,0xb9f4b6c6,0xaadebb85,0x3bfdb576,0x3bc0b825,0x33eb3ad8,0xb8153bc5,0xbae1b3a2,0xbb8ba9b1,0x3552bbfe,0x3b37b966,0x36e839e7,
  0x38cc38bc,0xba673a73,0xbbeb30d7,0x308dbbe8,0xb3d33b87,0xbbc2b56a,0x381a3b3d,0xbade36d2,0x2a7abbe9,0x3bfd30be,0xb95dba6f,0x39f0b8c1,
  0x30a63bfe,0xbbea2a16,0x3a6b3962,0xb8c739eb,0xb55ebbc3,0x3b89b3ba,0xbb3ab820,0x36ddbadb,0x33893bbf,0xbbc6b402,0xbad5bae5,0x382ab80f,
  0xbb83b9f8,0x3581b954,0x3b422b43,0x36bb3bfd,0x3a76b074,0x38b73bec,0xb0f03a64,0xbbe7b8d1,0x294d3b35,0xbbfeb6f4,0xb9e3bb8e,0x396bb546,
  0x394a3be5,0xba00b122,0x3bfc3a7e,0xac0638ad,0xb8db2884,0xba5cbbff,0x304239da,0xbbeeb974,0xbb2fbbc9,0x370ab359,0xbb92b835,0xb52fbace,
  0x341ab6a4,0x3bbc3b47,0xb805bb7f,0x3aeb3599,0x3b7a3bfb,0xb5b1ac6a,0xbb4cba09,0xb68db941,0x38a33a54,0xba85b8e5,0xbbe3bbef,0x3153b010,
  0x27763517,0xbbffbb96,0xb9d2bb2a,0x397d3721,0xb840b432,0xbac7bbb8,0xb328b7f3,0x3bcc3af1,0x3be23bfb,0x316c2c9c,0x389e393c,0x3a893a0d,
  0x3b783bb7,0x35bc343e,0x368237e8,0x3b4f3af4,0x3ac43b27,0x3845372c,0x330f350b,0x3bce3b98,0x39cd3a50,0x398238ea,0x26ad2fef,0x3bff3bf0,
  0x39463b7c,0x3a0435a5,0x2c38b699,0xbbfcbb4a,0xb4263340,0x3bba3bcb,0x3aee383a,0xb7febacb,0xbb94b979,0x352339d6,0x3b2c3bff,0x3715a81f,
  0xba58bbe4,0xb8e0b13b,0x302938a8,0x3bef3a81,0x28e83a60,0x3bfe38d6,0xb970305b,0x39df3bed,0xbbe6b9fc,0xb109394f,0xb8b2bbfc,0xba7aaba7,
  0x358db80a,0xbb81bae8,0x3b45340e,0xb6afbbbd,0x3ad13b90,0x3830b53a,0x33713b32,0x3bc836ff,0xb8cc38bc,0x3a673a73,0x3beb30d7,0xb08dbbe8,
  0x2adebb85,0xbbfdb576,0xb9f436c6,0x39583b3f,0x38153bc5,0x3ae1b3a2,0x33ebbad8,0xbbc0b825,0xbb37b966,0xb6e839e7,0x35523bfe,0x3b8ba9b1,
  0xbbc2356a,0x33d33b87,0xbadeb6d2,0xb81a3b3d,0x3bfdb0be,0xaa7abbe9,0x39f038c1,0x395dba6f,0xbbeaaa16,0xb0a63bfe,0xb8c7b9eb,0xba6b3962,
  0x3b8933ba,0x355ebbc3,0x36dd3adb,0x3b3ab820,0xbb422b43,0xb6bb3bfd,0x35813954,0x3b83b9f8,0x30f03a64,0x3be7b8d1,0x38b7bbec,0xba76b074,
  0x39e3bb8e,0xb96bb546,0xbbfe36f4,0xa94d3b35,0xbbc63402,0xb3893bbf,0x382a380f,0x3ad5bae5,0xb70ab359,0xbb2f3bc9,0x352fbace,0xbb923835,
  0xbbbc3b47,0x341a36a4,0xbaeb3599,0xb8053b7f,0x2c0638ad,0x3bfcba7e,0xb94a3be5,0x3a00b122,0x3beeb974,0x3042b9da,0x38db2884,0x3a5cbbff,
  0x3328b7f3,0xbbcc3af1,0xbac73bb8,0x3840b432,0xb5b12c6a,0xbb7a3bfb,0xb68d3941,0x3b4cba09,0xba8538e5,0xb8a33a54,0x31533010,0x3be3bbef,
  0xbbff3b96,0xa7763517,0x397db721,0x39d2bb2a,0x3a4db9c9,0xb8ee3986,0x3bf1bbff,0x2fbda5e4,0x3b24bac1,0xb737384a,0x3b9abbcf,0x34ffb2f7,
  0x3bb5bb76,0xb44b35c8,0x3af7bb52,0x37ddb676,0x3bfabbe1,0xacce3185,0x3a11ba8c,0x3937b899,0x3c00bb1e,0x2452374e,0xb9903b9e,0xb9c034e7,
  0x3855bafe,0x3abab7c8,0x32c63463,0xbbd23bb2,0xb65fad33,0x3b57bbf9,0x3b71b92e,0xb5df3a19,0xbbdf3a45,0x31b6b8f8,0x3a93bbf2,0x388eaf59,
  0x3a21bbdd,0x392431e8,0x2d97ba9b,0x3bf8b884,0xba3d217f,0x3902bc00,0xbbf439b8,0xaef5b999,0xb7643bd4,0xbb183294,0x34cf385f,0xbba13ab3,
  0x3baeb648,0xb47b3b5c,0x3b04bb6c,0x37b235f7,0x3219bbf5,0x3bdaae91,0x387a390c,0xbaa23a35,0xb9a13b13,0xb9afb77a,0x9cb6bba5,0x3c00b4b7,
  0x3bd7b79b,0x32633b0a,0xb86a3bab,0xbaacb493,0xbb68adfb,0x360ebbf7,0x3b60b91b,0x36313a29,0xb785bb65,0x3b10b61a,0xbba7b625,0x34abbb63,
  0x39113aa9,0xba31386f,0x3bf6324b,0xae5f3bd8,0xba2db9aa,0x3916b9a6,0xbbf69648,0xae2dbc00,0x3b0d3874,0xb7903aa5,0x3ba9b232,0x349f3bd9,
  0xbb5eba39,0x363cb907,0x3b6a2ec3,0x36023bf5,0x3ab0adc9,0x38653bf8,0xb27c3a25,0xbbd6b91f,0x9fdb3b07,0xbc00b7a6,0xb99dbbac,0x39b3b487,
  0xba9ebb16,0x387fb76f,0x3bdc34c3,0x32013ba3,0xbbb0b889,0xb46fba97,0xb7bd31cf,0xbb01bbde,0xb759bb59,0x3b1b3654,0xbb9fbb6f,0x34dbb5eb,
  0x3a4132ad,0x38fd3bd3,0x2f27b85a,0x3bf33ab6,0x3a1d3c00,0xb929a311,0x3bf939bc,0x2d653994,0xb894b4f3,0xba90bb9c,0xb19eb742,0x3be03b21,
  0xbb73ba49,0xb5d4b8f3,0x366b2f8b,0x3b543bf2,0xbbd0bbfa,0x32dead00,0x3abd3933,0x38503a15,0xb98bbafb,0x39c537d2,0x3c003bb3,0xa51b3457,
  0xb43eb16c,0x3bb73be2,0xbaf4ba89,0x37e8389e,0xb72cb5bc,0x3b273b78,0xbb98bb4f,0x350b3682,0xb8eab845,0x3a503ac4,0xbbf0bbce,0x2fef330f,
  0xba0db982,0x393c39cd,0xbbfbbbff,0xac9c26ad,0xba81b715,0x38a83b2c,0x3be43b94,0x313bb523,0xbb7cbbef,0xb5a53029,0x36993a58,0x3b4a38e0,
  0xb340b946,0xbbcbba04,0xb83aac38,0x3acb3bfc,0x39793426,0xb9d6bbba,0xbbffbaee,0x281f37fe,0xbbfcb970,0xaba739df,0xb94fbbfe,0xb9fc28e8,
  0x340eb8b2,0xbbbdba7a,0x3ae83109,0xb80abbe6,0x3b323b45,0x36ffb6af,0x353a3b81,0x3b90358d,0xb8d63371,0x3a603bc8,0xbbedb830,0x305b3ad1,
  0xb9e7bae1,0xb9663815,0x29b13bc0,0x3bfe33eb,0x3be836e8,0x30d7bb37,0xb8bcbb8b,0xba733552,0xbb3f308d,0x36c63beb,0x3b8538cc,0x3576ba67,
  0x3825b958,0xbad8b9f4,0xbbc5aade,0x33a23bfd,0xb0bebbc2,0xbbe933d3,0x38c1bade,0xba6fb81a,0xaa163bfd,0x3bfeaa7a,0xb9eb39f0,0x3962395d,
  0x33babbea,0xbbc3b0a6,0x3adbb8c7,0xb820ba6b,0xb6d23b89,0x3b3d355e,0xbb8736dd,0x356a3b3a,0x380fbbfe,0xbae5a94d,0xbbbf396b,0x340239e3,
  0xbbfd382a,0x2b433ad5,0x39f83389,0x3954bbc6,0x38d136bb,0x3a64bb42,0x3074bb83,0xbbec3581,0x3546bbe7,0xbb8e30f0,0xbb353a76,0x36f438b7,
  0x3b7fbb92,0xb599b52f,0x3b47b70a,0x36a4bb2f,0xb122b805,0xbbe53aeb,0x38adbbbc,0xba7e341a,0xbbff3a00,0xa884394a,0xb9742c06,0xb9da3bfc,
  0xb3593a5c,0x3bc9b8db,0xbace3bee,0x38353042,0x3b96ba85,0x3517b8a3,0xb7213153,0xbb2a3be3,0x3bb8bbff,0xb432a776,0xbaf1397d,0xb7f339d2,
  0x3941bac7,0xba093840,0xbbfb3bcc,0x2c6a3328,0x3010b68d,0xbbef3b4c,0xba543b7a,0x38e5b5b1,0x384ab8ee,0x3ac1ba4d,0xb2f72fbd,0x3bcfbbf1,
  0x35c8b737,0x3b76bb24,0xb67634ff,0x3b52bb9a,0x3185b44b,0x3be1bbb5,0xb89937dd,0x3a8cbaf7,0xa5e4acce,0x3bffbbfa,0xb9c93937,0x3986ba11,
  0xaf59b5df,0x3bf2bb71,0x3a45b65f,0xb8f83b57,0xbb1e388e,0x374eba93,0x3b9ebbdf,0x34e731b6,0xbafe3c00,0xb7c82452,0x3463b990,0x3bb2b9c0,
  0xad333855,0xbbf93aba,0xb92e32c6,0x3a19bbd2,0xb9b8ad97,0x3999bbf8,0xbc003924,0xa17fba21,0xb85f3bf4,0xbab32ef5,0x32943902,0xbbd43a3d,
  0x3b6cb4cf,0xb5f73ba1,0x3b5cbb18,0x36483764,0x31e8bb04,0x3bddb7b2,0xb884b47b,0x3a9bbbae,0xbbf73263,0x2dfbbbd7,0x3a29baac,0x391b386a,
  0x3a35360e,0xb90c3b68,0xbbf53631,0xae91bb60,0xb4b7baa2,0x3ba5b87a,0x3b133219,0xb77a3bda,0xb4933c00,0xbbab1cb6,0xb79bb9a1,0x3b0ab9af,
  0xbaa93785,0xb86fbb10,0xb24b3ba7,0xbbd8b4ab,0x39aab911,0x39a63a31,0x1648bbf6,0x3c002e5f,0xb8743a2d,0xbaa5b916,0x32323bf6,0xbbd92e2d,
  0x3625bb0d,0x3b633790,0xb61abba9,0x3b65b49f,0xb4c3399d,0xbba3b9b3,0xb76fbc00,0x3b161fdb,0xb907bbdc,0x3a39b201,0x3bf5387f,0xaec33a9e,
  0x3bf8363c,0x2dc93b5e,0xb91f3602,0xba25bb6a,0xb7a63865,0xbb07bab0,0xb487bbd6,0x3bac327c,0x35eb3b01,0xbb6fb7bd,0x3b593bb0,0xb654346f,
  0xbab6b4db,0xb85abb9f,0xb2ad3759,0xbbd3bb1b,0xb994bbf3,0x39bc2f27,0xbc00ba41,0x2311b8fd,0x3889ad65,0x3a973bf9,0xb1cfba1d,0x3bde3929,
  0x3afb3bd0,0xb7d2b2de,0xbbb3babd,0xb457b850,0x3742398b,0xbb21b9c5,0xbb9cbc00,0x34f3251b,0xaf8b319e,0xbbf2bbe0,0xb8f3ba90,0x3a493894,
  0xb933b66b,0xba15bb54,0xad00b5d4,0x3bfa3b73,0x211b21e4,0xa51ba5e4,0x98b69248,0x1cb61648,0x1f122052,0xa311a452,0x9d7f9bdb,0x217f1fdb,
  0x1bdb1d7f,0x9fdba17f,0xa0529f12,0x24522311,0x124818b6,0x96489cb6,0xa1e4a11b,0x25e4251b,0x2a632b5f,0xae5faf59,0xa1e49bdb,0x25e41fdb,
  0x286b2967,0xac6aad65,0xa6e0a4e9,0x2ade28e8,0x24e926e0,0xa8e8aade,0xa967a86b,0x2d652c6a,0x1bdb21e4,0x9fdba5e4,0xab5faa63,0x2f592e5f,
  0x2dc22ea7,0xb1b6b294,0xa54d9f12,0x294d2311,0x2bf62cde,0xafefb0d7,0xaa31a86b,0x2e2d2c6a,0x286b2a31,0xac6aae2d,0xacdeabf6,0x30d72fef,
  0x1f12254d,0xa311a94d,0xaea7adc2,0x329431b6,0x302c30d2,0xb41ab4b7,0xa7a9a11b,0x2ba7251b,0x2dc22f0c,0xb1b6b2f7,0xac79aa63,0x30742e5f,
  0x2a632c79,0xae5fb074,0xaf0cadc2,0x32f731b6,0x211b27a9,0xa51baba7,0xb0d2b02c,0x34b7341a,0x317a3257,0xb552b61a,0xa902a2ad,0x2d0026ad,
  0x2f8c309f,0xb371b487,0xaddcac2e,0x31cf3029,0x2c2e2ddc,0xb029b1cf,0xb09faf8c,0x34873371,0x22ad2902,0xa6adad00,0xb257b17a,0x361a3552,
  0x32cd33e3,0xb682b76f,0xaa31a420,0x2e2d281f,0x30ac31bb,0xb493b58d,0xaf3fad2a,0x33283122,0x2d2a2f3f,0xb122b328,0xb1bbb0ac,0x358d3493,
  0x24202a31,0xa81fae2d,0xb3e3b2cd,0x376f3682,0x341334bc,0xb7a6b85a,0xab5fa4e9,0x2f5928e8,0x319432da,0xb56ab68d,0xb052ae28,0x343e3219,
  0x2e283052,0xb219b43e,0xb2dab194,0x368d356a,0x24e92b5f,0xa8e8af59,0xb4bcb413,0x385a37a6,0x34c3358c,0xb85fb8f3,0xac47a5b2,0x304229b1,
  0x327e33fd,0xb63cb785,0xb106af26,0x34e7330f,0x2f263106,0xb30fb4e7,0xb3fdb27e,0x3785363c,0x25b22c47,0xa9b1b042,0xb58cb4c3,0x38f3385f,
  0x35773662,0xb8e5b982,0xacdea67b,0x30d72a7a,0x336b3493,0xb70ab83a,0xb1bbb012,0x358d3402,0x301231bb,0xb402b58d,0xb493b36b,0x383a370a,
  0x267b2cde,0xaa7ab0d7,0xb662b577,0x398238e5,0x36303741,0xb962ba04,0xad76a744,0x316c2b43,0x342e352a,0xb7d2b8ad,0xb271b092,0x3631347b,
  0x30923271,0xb47bb631,0xb52ab42e,0x38ad37d2,0x27442d76,0xab43b16c,0xb741b630,0x3a043962,0x36ee3815,0xb9d6ba7a,0xae0ea807,0x32012c06,
  0x34a735c4,0xb84ab91b,0xb329b113,0x36d234f3,0x31133329,0xb4f3b6d2,0xb5c4b4a7,0x391b384a,0x28072e0e,0xac06b201,0xb815b6ee,0x3a7a39d6,
  0x37b4388e,0xba41bae1,0xaea7a86b,0x32942c6a,0x35233662,0xb8a8b982,0xb3e3b194,0x376f356a,0x319433e3,0xb56ab76f,0xb662b523,0x398238a8,
  0x286b2ea7,0xac6ab294,0xb88eb7b4,0x3ae13a41,0x3841390f,0xbaa2bb3a,0xaf3fa8d0,0x33282cce,0x35a13705,0xb902b9e3,0xb44fb216,0x380535df,
  0x3216344f,0xb5dfb805,0xb705b5a1,0x39e33902,0x28d02f3f,0xacceb328,0xb90fb841,0x3b3a3aa2,0x38ac3997,0xbaf7bb83,0xafd8a935,0x33ba2d33,
  0x362137ac,0xb958ba3d,0xb4aeb298,0x38503654,0x329834ae,0xb654b850,0xb7acb621,0x3a3d3958,0x29352fd8,0xad33b3ba,0xb997b8ac,0x3b833af7,
  0x391c3a28,0xbb42bbbc,0xb039a999,0x34262d97,0x36a4382d,0xb9aaba90,0xb50eb31c,0x389936c6,0x331c350e,0xb6c6b899,0xb82db6a4,0x3a9039aa,
  0x29993039,0xad97b426,0xba28b91c,0x3bbc3b42,0x39923ac3,0xbb81bbe3,0xb085a9fe,0x346f2dfb,0x372a3886,0xb9f8badb,0xb570b3a0,0x38e03737,
  0x33a03570,0xb737b8e0,0xb886b72a,0x3adb39f8,0x29fe3085,0xadfbb46f,0xbac3b992,0x3be33b81,0xb9cfbb16,0x3b9c3bf1,0x30ac2a31,0xb493ae2d,
  0xb76fb8b4,0x3a1d3afe,0x35a133e3,0xb902b76f,0xb3e3b5a1,0x376f3902,0x38b4376f,0xbafeba1d,0xaa31b0ac,0x2e2d3493,0x3b1639cf,0xbbf1bb9c,
  0xb956ba74,0x3b633bd2,0x305f29cc,0xb44badc9,0xb6e7b859,0x39d23ab6,0x353f335e,0xb8bcb6ff,0xb35eb53f,0x36ff38bc,0x385936e7,0xbab6b9d2,
  0xa9ccb05f,0x2dc9344b,0x3a743956,0xbbd2bb63,0xb8e3b9de,0x3b1e3ba1,0x30122967,0xb402ad65,0xb662b801,0x39823a67,0x34de32da,0xb874b68d,
  0xb2dab4de,0x368d3874,0x38013662,0xba67b982,0xa967b012,0x2d653402,0x39de38e3,0xbba1bb1e,0xb876b952,0x3ace3b60,0x2f8c2902,0xb371ad00,
  0xb5e1b758,0x392e3a11,0x347e3257,0xb82ab61a,0xb257b47e,0x361a382a,0x375835e1,0xba11b92e,0xa902af8c,0x2d003371,0x39523876,0xbb60bace,
  0xb80db8ce,0x3a733b10,0x2ef3289e,0xb2deac9c,0xb562b6b3,0x38d639b3,0x342031d5,0xb7bdb5a5,0xb1d5b420,0x35a537bd,0x36b33562,0xb9b3b8d6,
  0xa89eaef3,0x2c9c32de,0x38ce380d,0xbb10ba73,0xb750b851,0x3a0d3ab0,0x2e5a2839,0xb24bac38,0xb4e5b613,0x387a394f,0x33863153,0xb721b52f,
  0xb153b386,0x352f3721,0x361334e5,0xb94fb87a,0xa839ae5a,0x2c38324b,0x38513750,0xbab0ba0d,0xb68eb7b4,0x399d3a41,0x2dc227a9,0xb1b6aba7,
  0xb46ab577,0x381a38e5,0x32cd30d2,0xb682b4b7,0xb0d2b2cd,0x34b73682,0x3577346a,0xb8e5b81a,0xa7a9adc2,0x2ba731b6,0x37b4368e,0xba41b99d,
  0xb5d2b6d1,0x392439c5,0x2d2a26e0,0xb122aade,0xb3e3b4de,0x376f3874,0x32163052,0xb5dfb43e,0xb052b216,0x343e35df,0x34de33e3,0xb874b76f,
  0xa6e0ad2a,0x2ade3122,0x36d135d2,0xb9c5b924,0xb51cb5f6,0x38a3393c,0x2c932617,0xb08daa16,0xb2f4b448,0x36a437fe,0x31602fa5,0xb53ab389,
  0xafa5b160,0x3389353a,0x344832f4,0xb7feb6a4,0xa617ac93,0x2a16308d,0x35f6351c,0xb93cb8a3,0xb46ab523,0x381a38a8,0x2bf6254d,0xafefa94d,
  0xb209b36b,0x35d4370a,0x30ac2ea7,0xb493b294,0xaea7b0ac,0x32943493,0x336b3209,0xb70ab5d4,0xa54dabf6,0x294d2fef,0x3523346a,0xb8a8b81a,
  0xb378b456,0x3715380a,0x2ac82484,0xaec3a884,0xb120b24a,0x34ff360e,0x2ff22da9,0xb3d3b19e,0xada9aff2,0x319e33d3,0x324a3120,0xb60eb4ff,
  0xa484aac8,0x28842ec3,0x34563378,0xb80ab715,0xb223b31c,0x35eb36c6,0x29992376,0xad97a776,0xb039b12d,0x3426350b,0x2e8d2cac,0xb27cb0a6,
  0xacacae8d,0x30a6327c,0x312d3039,0xb50bb426,0xa376a999,0x27762d97,0x331c3223,0xb6c6b5eb,0xb0d2b194,0x34b7356a,0x286b21e4,0xac6aa5e4,
  0xaea7b012,0x32943402,0x2d2a2b5f,0xb122af59,0xab5fad2a,0x2f593122,0x30122ea7,0xb402b294,0xa1e4a86b,0x25e42c6a,0x319430d2,0xb56ab4b7,
  0xaf0cb012,0x32f73402,0x267b2052,0xaa7aa452,0xacdeadf5,0x30d731e8,0x2b912967,0xaf8bad65,0xa967ab91,0x2d652f8b,0x2df52cde,0xb1e8b0d7,
  0xa052a67b,0x24522a7a,0x30122f0c,0xb402b2f7,0xac79ad2a,0x30743122,0x24201d7f,0xa81fa17f,0xaa31ab91,0x2e2d2f8b,0x28d026e0,0xacceaade,
  0xa6e0a8d0,0x2ade2cce,0x2b912a31,0xaf8bae2d,0x9d7fa420,0x217f281f,0x2d2a2c79,0xb122b074,0xa7a9a86b,0x2ba72c6a,0x1f1218b6,0xa3119cb6,
  0xa54da67b,0x294d2a7a,0x242021e4,0xa81fa5e4,0xa1e4a420,0x25e4281f,0x267b254d,0xaa7aa94d,0x98b69f12,0x1cb62311,0x286b27a9,0xac6aaba7,
  0xa5e43bff,0xb61a3b65,0xb98239cd,0xbb3a36dd,0xaf593bf2,0xb76f3b16,0xba043946,0xbb833581,0xb2943bd4,0xb85a3ab6,0xba7a38b2,0xbbbc341a,
  0xb4b73ba5,0xb8f33a49,0xbae13815,0xbbe33153,0xac9c3bfb,0xbb87356a,0xb986b9c9,0x361abb65,0xb5a53b7c,0xbbfd2b43,0xb74ebb1e,0x3907ba39,
  0xb8d63a60,0xbbc9b359,0xb1e8bbdd,0x3a97b889,0xba7338bc,0xbaf1b7f3,0x2e91bbf5,0x3b9cb4f3,0xafbd3bf1,0xbb10b785,0x3a0db93c,0x356a3b87,
  0xb88e3a93,0xb87fba9e,0x3bcbb340,0xb0743bec,0xbb183764,0xaf27bbf3,0x3bbd340e,0xb8ad3a7e,0xbc009cb6,0x35d4bb73,0x39e73966,0xbb2a3721,
  0xb16c3be2,0xb3d3bbc2,0x38ee3a4d,0xbb10b785,0xba043946,0x36bbbb42,0xa4523c00,0xb63cbb5e,0xbbfe28e8,0x3b2fb70a,0xb9243a21,0x346fbbb0,
  0xba67b8cc,0x3bcc3328,0xbbda3219,0x3a90b894,0xb2f73bcf,0x386fbaa9,0xba89389e,0x3bc2b3d3,0xbb1e374e,0x3bf5aec3,0xbbbab426,0x3a7638b7,
  0xbb5cb648,0x39bc3994,0xb6afbb45,0x2c063bfc,0xb493bbab,0xad003bfa,0x36e8bb37,0xb9d2397d,0xb43e3bb7,0x3be9b0be,0xb84abac1,0xb86f3aa9,
  0xbbcb3340,0x38d13a64,0x37c8bafe,0xbbf8adc9,0xb94fb9fc,0xb6a43b47,0x3c00217f,0xb654bb59,0x3576bb85,0xbbfb2c6a,0x377a3b13,0x38f3ba49,
  0xb4ff3b9a,0x3a313911,0x3af4b7e8,0xb0bebbe9,0xbc00a452,0xb6023b6a,0x39d63979,0x3b35b6f4,0xb47bbbae,0xbbf9ad65,0xb6ff3b32,0x397439da,
  0x3aacb86a,0xb2debbd0,0xbbe8b0d7,0xb7f33af1,0xb5bc3b78,0x2a7a3bfd,0x37373b24,0x3a313911,0xbbbab426,0xbbe730f0,0xbaba3855,0xb8653ab0,
  0x3109bbe6,0xb41abbbc,0xb902ba3d,0xbb1bb759,0x3bfd2ade,0x3b7ab5b1,0x39afb9a1,0x35d4bb73,0xb6763b52,0xb9a639aa,0xbb4f3682,0xbbfd2a7a,
  0xbafeb7c8,0xb91fba25,0xb523bb94,0x294dbbfe,0x3884ba9b,0x3a97b889,0x3bc8b371,0x3bee3042,0x3a29391b,0x37d23afb,0x308d3beb,0xb3283bcc,
  0xb72c3b27,0xbbfeaa16,0xb5c8bb76,0x39a6b9aa,0xb9d6b979,0x3546bb8e,0x3bf9ad33,0x37a63b07,0x3ae8b80a,0x3a7e38ad,0xb2943bd4,0xbbd332ad,
  0x33a23bc5,0xba5438e5,0xbb0ab79b,0x2d00bbfa,0xb7dd3af7,0xb916ba2d,0x3b98b50b,0xaa163bfe,0xb855baba,0x3bd6b27c,0xb13b3be4,0xbae5b80f,
  0x3bf8ad97,0xb46f3bb0,0xba60b8d6,0x3aceb835,0xb6313b60,0xb9c5b98b,0x3b3fb6c6,0x2c6a3bfb,0xb8453ac4,0x30a6bbea,0x344b3bb5,0xb916ba2d,
  0xb523bb94,0x396b39e3,0xbb57b65f,0x3c009fdb,0x3b81358d,0xbbfc2c06,0x3b18b764,0xb8fd3a41,0xbae13815,0x38a3ba85,0xb2633bd7,0xb2debbd0,
  0xb8993a8c,0x3aa5b874,0xbbce330f,0x3bea30a6,0xad33bbf9,0xb4873bac,0x38e0ba58,0xbad5382a,0x399939b8,0xb654bb59,0x28e83bfe,0x352fbb92,
  0xbbf5ae91,0x3b213742,0xb958b9f4,0x35b13b7a,0xb8ea3a50,0x3bc333ba,0xb185bbe1,0xbaa53874,0x313bbbe4,0xbbbf3402,0x38f83a45,0x376fbb16,
  0x353a3b90,0x39dab974,0xbb5cb648,0x23113c00,0xb9e7b966,0xb5173b96,0x3bf7adfb,0xb7d2bafb,0xb9373a11,0x37903b0d,0x3bf0afef,0x33babbc3,
  0x365fbb57,0xb9b3b99d,0xbb4a3699,0x2b433bfd,0xaef53bf4,0x3b1b3759,0x39fcb94f,0xb599bb7f,0xb219bbda,0xbbe0b19e,0xb8253ad8,0x38e53a54,
  0xb98239cd,0xb55e3b89,0x2cce3bfa,0x37903b0d,0x38e0ba58,0x3389bbc6,0xb1b6bbdf,0xb87fba9e,0xb8303ad1,0xb0423bee,0x347b3bae,0x39293a1d,
  0x36e8bb37,0x2776bbff,0xb60ebb68,0xb9c5b98b,0xb9c93986,0xbb633625,0xbbff26ad,0xbb89b55e,0x3a45b8f8,0x3ba3b4c3,0x3bfc2c38,0x3b4236bb,
  0xbab3385f,0xbbd332ad,0xbbe6b109,0xbaebb805,0x3b13b77a,0x3bf2af8b,0x3bc033eb,0x3a8538a3,0xba0d393c,0xbb3db6d2,0x25e4bbff,0x3b63b625,
  0x3b4ab699,0x39f83954,0xb4e73b9e,0xbbf52ec3,0xbbed305b,0xb835bace,0x3884ba9b,0x3bde31cf,0x3be830d7,0x34323bb8,0xba35390c,0xbb21b742,
  0xba4d38ee,0xb4abbba7,0x3bfb2c9c,0xb6d23b3d,0x3bdfb1b6,0xb2013bdc,0xbacbb83a,0x3a64b8d1,0xbba1b4cf,0x38fdba41,0x380a3ae8,0xbbe53122,
  0x39a139af,0xbb54366b,0xa9b1bbfe,0x3b963517,0xba89389e,0x381abade,0xafbd3bf1,0xb4abbba7,0x3bfc2c38,0xbb833581,0x39c0b990,0xb6023b6a,
  0xb9dfb970,0x3b92352f,0xbbf82d97,0x3b01b7bd,0x308d3beb,0xb840bac7,0x3aa2387a,0xbbe0b19e,0xbac1384a,0x3bd8b24b,0xbbe2b16c,0x3ade381a,
  0x3b9e34e7,0xba39b907,0x37fe3aee,0xb0f0bbe7,0xb5f7bb6c,0x23113c00,0x358dbb81,0xb94a3a00,0xb79b3b0a,0x3a15b933,0xbb8b3552,0x3bff2776,
  0xbaf437e8,0x3a6f38c1,0x32f7bbcf,0xbbd8324b,0x3acb383a,0x3074bbec,0xbbb23463,0x391f3a25,0x2ba7bbfc,0xbb7f3599,0x399939b8,0x35ebbb6f,
  0xbb3f36c6,0x3a093941,0x34b7bba5,0xbbf22f8b,0xbb243737,0x2e5f3bf6,0x3bb7343e,0x38c1ba6f,0x399039c0,0x3b5eb63c,0xa81fbbff,0xbb8eb546,
  0x37b2bb04,0xb929ba1d,0xbb90353a,0xa8843bff,0xbbd7b263,0xb8503abd,0x38bc3a73,0x3bb8b432,0xbb4f3682,0xb95d39f0,0xb4ff3b9a,0x2e5f3bf6,
  0x37fe3aee,0x3a7638b7,0x3bd232c6,0x3bd6b27c,0x3a7ab8b2,0x3805baeb,0x2ef5bbf4,0xb4dbbb9f,0xb958b9f4,0xbb4cb68d,0xbc009cb6,0xbb54366b,
  0xbb7635c8,0xbc001648,0xbb78b5bc,0xb9f0b95d,0x34633bb2,0xadc93bf8,0xb7153b2c,0xb9e3396b,0x3bddb1e8,0x3bde31cf,0x3ad13830,0x38db3a5c,
  0xadfbbbf7,0x3457bbb3,0x38ccba67,0x3ac7b840,0xbb98350b,0xb962b9eb,0x3676bb52,0x3c009648,0x281f3bff,0xbb3536f4,0xba19b92e,0x3487bbac,
  0x3bbd340e,0x31223be5,0xbab3385f,0xbab6b85a,0x3825bad8,0x3bef3010,0x34933bab,0xba153933,0xbbb5344b,0x2e2dbbf6,0x3b27372c,0xb9eb3962,
  0xb2c63bd2,0xbab0b865,0x3a81b8a8,0x34023bbf,0x3a213924,0xbb0137bd,0xb05bbbed,0x3bc93359,0x3b68b60e,0x251b3c00,0xbb85b576,0x3941ba09,
  0xbbce330f,0x3a6bb8c7,0xb7dd3af7,0x2e2dbbf6,0xb7153b2c,0x294dbbfe,0x35df3b71,0xb9b3b99d,0x36af3b45,0xba00b94a,0x3ba134cf,0xbbf32f27,
  0x3bc033eb,0xbbe33153,0x3aacb86a,0xb8503abd,0xbbe13185,0x3bd93232,0xbac4b845,0x38c73a6b,0xb92e3a19,0x3b07b7a6,0xbbef3029,0x3bc63389,
  0xa17f3c00,0x35ebbb6f,0xb97039df,0x3b2fb70a,0x390c3a35,0xb4f3bb9c,0xaade3bfd,0x368dbb4c,0xbbf02fef,0x38203adb,0x3899ba8c,0xbbd9b232,
  0xba8138a8,0x3ae5380f,0x2f59bbf2,0xbba334c3,0xb6ff3b32,0x3bff2884,0xb5f7bb6c,0xb99439bc,0x29b13bfe,0x3b2ab721,0xba29b91b,0xb4573bb3,
  0xbbfa2cce,0xb49f3ba9,0x3a5038ea,0x3adbb820,0xbb7135df,0x1fdb3c00,0x3b7c35a5,0x3954b9f8,0xba3d3902,0x34db3b9f,0x3bfc2ba7,0x36a4bb47,
  0xb87a3aa2,0x38943a90,0x3bc5b3a2,0x3010bbef,0xbbff26ad,0xbb3a36dd,0xb9373a11,0xb49f3ba9,0xbbef3029,0xbad5382a,0xb88e3a93,0xb2013bdc,
  0xbbc83371,0xba5c38db,0xb7b23b04,0xad653bf9,0xbb8b3552,0xb9d2397d,0xb6313b60,0x251b3c00,0x3bf12fbd,0x3b103785,0x393c3a0d,0x356a3b87,
  0x3bd232c6,0x3ab03865,0x38a83a81,0x34023bbf,0x3ba134cf,0x3a4138fd,0x380a3ae8,0x31223be5,0x3b603631,0x39c5398b,0x36c63b3f,0x2c6a3bfb,
  0xbbe2b16c,0xb3d3bbc2,0x3a4db8ee,0x3b103785,0xbb2cb715,0x294dbbfe,0x3b71b5df,0x39b3399d,0xb9dfb970,0x352fbb92,0x3bf8ad97,0x37bd3b01,
  0xb815bae1,0x38a3ba85,0x3bd73263,0x32de3bd0,0x3bcf32f7,0xb86f3aa9,0xb89eba89,0x3bc2b3d3,0x3a19392e,0xbb0737a6,0xb029bbef,0x3bc63389,
  0x35f73b6c,0xbc002311,0x358dbb81,0x3a00394a,0xae913bf5,0xbb21b742,0x39f4b958,0x35b13b7a,0xbbb7b43e,0x3be9b0be,0xbac1384a,0x386fbaa9,
  0xb8a8ba81,0x3ae5380f,0xbbf2af59,0x3ba3b4c3,0x2ba7bbfc,0x35993b7f,0xb999b9b8,0x3b6f35eb,0x3966b9e7,0xb5173b96,0xadfbbbf7,0x37d23afb,
  0x3b9a34ff,0xba31b911,0x37e83af4,0xb0bebbe9,0x35df3b71,0x9fdbbc00,0xb5a53b7c,0x3954b9f8,0xb7b23b04,0x3a1db929,0xbb90353a,0x3bff2884,
  0xbbda3219,0x3be0319e,0xbad8b825,0x38e53a54,0xbb78b5bc,0x2a7a3bfd,0x3b24b737,0xba31b911,0xb029bbef,0xbad5382a,0x3a93388e,0x3201bbdc,
  0x3a7ab8b2,0xbaebb805,0xaef53bf4,0x3b9fb4db,0x3b3736e8,0x2776bbff,0xbb68360e,0x39c5398b,0x3b523676,0x39a6b9aa,0xb682bb4f,0xbbfd2a7a,
  0xaf593bf2,0x3b16376f,0x3a04b946,0xb581bb83,0xbbdd31e8,0xb1cf3bde,0x3ad13830,0x3a5cb8db,0xb77abb13,0xbbf22f8b,0xb3eb3bc0,0x3a8538a3,
  0xbb27b72c,0xbbfeaa16,0xbb7635c8,0xb9a639aa,0x35a5bb7c,0xab43bbfd,0xb74ebb1e,0xba39b907,0x3bbd340e,0x3be5b122,0x3ab3b85f,0x385abab6,
  0xb0d73be8,0x34323bb8,0x390c3a35,0x3b213742,0x3af737dd,0x39163a2d,0x350b3b98,0xaa163bfe,0xb88e3a93,0xba9e387f,0xbbcb3340,0xbbecb074,
  0xba21b924,0xb7bdbb01,0xb05bbbed,0x3359bbc9,0x39afb9a1,0x3b54b66b,0x3bfea9b1,0x3b963517,0xbac4b845,0x30a6bbea,0x3bb5b44b,0x39163a2d,
  0x3a04b946,0x3b4236bb,0xa4523c00,0xbb5e363c,0x36af3b45,0xb94a3a00,0xbba1b4cf,0xaf27bbf3,0xbbeb308d,0xb840bac7,0x387abaa2,0x3be0319e,
  0x3a8c3899,0xbaa53874,0xb30fbbce,0x3bea30a6,0xbb1e374e,0xaec3bbf5,0x3bba3426,0xb8b73a76,0x217fbc00,0x3b6f35eb,0xb97039df,0xb70abb2f,
  0x3b0a379b,0xba153933,0xb552bb8b,0x3bff2776,0xba50b8ea,0x3bc333ba,0xbbe13185,0x3aa5b874,0x3bcbb340,0xba6438d1,0x37c8bafe,0xadc93bf8,
  0xb6ff3b32,0x2884bbff,0x35f73b6c,0xb9bcb994,0xb6c6bb3f,0x3a093941,0xbba5b4b7,0x3bf2af8b,0x3a113937,0xb790bb0d,0x2fef3bf0,0x33babbc3,
  0xbc00a452,0x3b6a3602,0xb9d6b979,0x36f43b35,0x3a3db902,0xbb9f34db,0x3bfc2ba7,0xbb47b6a4,0xb2633bd7,0x3850babd,0xba7338bc,0x3bb8b432,
  0xb9cdb982,0xb55e3b89,0x3bfaacce,0xb790bb0d,0x3bba3426,0xb0f0bbe7,0xbaba3855,0x3ab03865,0xbbc83371,0x38db3a5c,0x37b2bb04,0xbbf9ad65,
  0x39f4b958,0xbb4cb68d,0x9cb63c00,0x3b54b66b,0x398639c9,0x3b63b625,0xa6adbbff,0xbb89b55e,0xbafeb7c8,0xba25391f,0x35233b94,0x3bfe294d,
  0x3bd43294,0x385abab6,0xb8b2ba7a,0xbbbc341a,0xbbf72dfb,0xb4573bb3,0x3a6738cc,0x3ac7b840,0xb93cba0d,0xbb3db6d2,0xbbffa5e4,0xbb633625,
  0x39d63979,0x3b8e3546,0x3bf9ad33,0x3b07b7a6,0xba60b8d6,0xbbc9b359,0xbbdd31e8,0xba973889,0x3ad83825,0x3bef3010,0x3babb493,0x3a15b933,
  0x38ee3a4d,0x34ab3ba7,0xac9c3bfb,0xb6d23b3d,0xb855baba,0xb27cbbd6,0x313bbbe4,0x380fbae5,0x37643b18,0x2f273bf3,0xb40e3bbd,0xb8ad3a7e,
  0xb60ebb68,0xa51bbc00,0x3576bb85,0x3941ba09,0xb89eba89,0x381abade,0x3bf12fbd,0x34ab3ba7,0x35233b94,0xb9e3396b,0xbb57b65f,0x9fdbbc00,
  0xa8e8bbfe,0x3b2fb70a,0x3a213924,0xb46f3bb0,0xb3eb3bc0,0xbbe33153,0xb86abaac,0x3850babd,0x384a3ac1,0xbbd8324b,0x316cbbe2,0x3ade381a,
  0xad33bbf9,0x3bac3487,0xb8e03a58,0xb82abad5,0xb6483b5c,0xb9bcb994,0x3b45b6af,0x2c063bfc,0x3a35b90c,0x34f33b9c,0xbbfdaade,0x368dbb4c,
  0xb7e8baf4,0x3a6f38c1,0xbbcfb2f7,0x3bd8b24b,0xb13b3be4,0xb402bbbf,0x38f83a45,0xbb16b76f,0x39fcb94f,0xb6a43b47,0x217fbc00,0x36543b59,
  0xbbfe29b1,0x3b2ab721,0xb91b3a29,0x3457bbb3,0x37373b24,0xae5fbbf6,0xb43e3bb7,0x38c1ba6f,0x365fbb57,0xb99d39b3,0x3b4ab699,0xbbfd2b43,
  0xbbae347b,0x3bf92d65,0xbb32b6ff,0x397439da,0x3aa2387a,0xb894ba90,0x33a23bc5,0x3010bbef,0xb682bb4f,0xb95d39f0,0x3b9a34ff,0xae5fbbf6,
  0xb8e03a58,0x3bc63389,0xb1b6bbdf,0xba9e387f,0x3be63109,0xb41abbbc,0xba3d3902,0x3b1b3759,0xb552bb8b,0xb9d2397d,0x3b603631,0xa51bbc00,
  0x35c83b76,0x3c009648,0x35bcbb78,0xb9f0b95d,0x3a45b8f8,0xb4c3bba3,0xbbfcac38,0xb6bb3b42,0xba9bb884,0xba973889,0x33713bc8,0x3bee3042,
  0xb4b73ba5,0x3a4938f3,0x3ae1b815,0xb153bbe3,0xb50bbb98,0xb962b9eb,0xbb52b676,0xbc001648,0xbb4a3699,0xb95439f8,0xb4e73b9e,0x2ec33bf5,
  0x380a3ae8,0x3a7e38ad,0x3bd43294,0x3bd3b2ad,0x3a73b8bc,0x37f3baf1,0x2e91bbf5,0xb4f3bb9c,0x344b3bb5,0xae2d3bf6,0xb72c3b27,0xb9eb3962,
  0x3bdfb1b6,0x3bdc3201,0x3acb383a,0x38d13a64,0xad97bbf8,0x346fbbb0,0x38d6ba60,0x3aceb835,0xbc009cb6,0xbb73b5d4,0xb9e7b966,0xb721bb2a,
  0xb30fbbce,0x3a6bb8c7,0x3af737dd,0xae2d3bf6,0xbbfcac38,0xb581bb83,0x39c0b990,0x3b6a3602,0xb58d3b81,0xbbfc2c06,0xb764bb18,0x38fdba41,
  0x3a6738cc,0xb3283bcc,0xbbda3219,0xb894ba90,0x31853be1,0xbbd9b232,0x3845bac4,0x38c73a6b,0x3b9e34e7,0xb9073a39,0xb7febaee,0x3be7b0f0,
  0x39b8b999,0x36543b59,0xbbfe28e8,0x352fbb92,0xb493bbab,0x3bfa2d00,0xb6e83b37,0xb97db9d2,0xafefbbf0,0x38203adb,0xba8cb899,0x3bd93232,
  0xbacbb83a,0x3bec3074,0xbbb23463,0x3a25b91f,0xbb90353a,0x39dab974,0xb6483b5c,0xa311bc00,0xb5763b85,0xac6abbfb,0x377a3b13,0xba49b8f3,
  0x2cce3bfa,0x349fbba9,0xb8ea3a50,0x3adbb820,0x399039c0,0xb63cbb5e,0x281f3bff,0x3546bb8e,0x3bf42ef5,0xbb1bb759,0x394f39fc,0xb599bb7f,
  0x3aacb86a,0xbbd032de,0x3be830d7,0xbaf1b7f3,0xa6adbbff,0xbb3a36dd,0x3a113937,0x349fbba9,0xb7febaee,0xb8b73a76,0x3bd232c6,0xb27cbbd6,
  0xbad1b830,0xb0423bee,0x3baeb47b,0xb929ba1d,0xbbfdaade,0x35b13b7a,0x39afb9a1,0xbb73b5d4,0xa5e43bff,0x3b65361a,0x3982b9cd,0xb6ddbb3a,
  0x34633bb2,0x3bf82dc9,0x3715bb2c,0xb96bb9e3,0x385f3ab3,0x3bd3b2ad,0x3109bbe6,0xbaebb805,0x3a29391b,0x3afbb7d2,0xb08dbbeb,0xbbccb328,
  0x2c9cbbfb,0xb56abb87,0xb986b9c9,0xbb65b61a,0xa81fbbff,0xb6f4bb35,0xba19b92e,0xbbacb487,0xb05bbbed,0xb835bace,0xba9bb884,0xbbdeb1cf,
  0xb3a2bbc5,0xb8e5ba54,0xbb0ab79b,0xbbfaad00,0x00000000,0x00000000,0x00000000,0x00000000,0xaa1f0000,0xaf64ada8,0xaf64b000,0xaa1fada8,
  0xada80000,0xada8b000,0x2da88000,0x2da83000,0xaf640000,0x2a1fada8,0x2a1f3000,0xaf64ada8,0xb0000000,0x30008000,0xb0000000,0x30008000,
  0xaf640000,0x2a1f2da8,0x2a1fb000,0xaf642da8,0xada80000,0xada83000,0x2da88000,0x2da8b000,0xaa1f0000,0xaf642da8,0xaf643000,0xaa1f2da8,
  0x00000000,0x00000000,0x00000000,0x00000000,0x2a1f8000,0x2f642da8,0x2f643000,0x2a1f2da8,0xada80000,0xada8b000,0x2da88000,0x2da83000,
  0x2f648000,0xaa1f2da8,0xaa1fb000,0x2f642da8,0xb0000000,0x30008000,0xb0000000,0x30008000,0x2f648000,0xaa1fada8,0xaa1f3000,0x2f64ada8,
  0xada80000,0xada83000,0x2da88000,0x2da8b000,0x2a1f8000,0x2f64ada8,0x2f64b000,0x2a1fada8,0x80000000,0x80000000,0x80000000,0x80000000,
  0x2a1f0000,0x2f64ada8,0x2f64b000,0x2a1fada8,0x2da80000,0x2da8b000,0xada88000,0xada83000,0x2f640000,0xaa1fada8,0xaa1f3000,0x2f64ada8,
  0x30000000,0xb0008000,0x30000000,0xb0008000,0x2f640000,0xaa1f2da8,0xaa1fb000,0x2f642da8,0x2da80000,0x2da83000,0xada88000,0xada8b000,
  0x2a1f0000,0x2f642da8,0x2f643000,0x2a1f2da8,0x80000000,0x80000000,0x80000000,0x80000000,0xaa1f8000,0xaf642da8,0xaf643000,0xaa1f2da8,
  0x2da80000,0x2da8b000,0xada88000,0xada83000,0xaf648000,0x2a1f2da8,0x2a1fb000,0xaf642da8,0x30000000,0xb0008000,0x30000000,0xb0008000,
  0xaf648000,0x2a1fada8,0x2a1f3000,0xaf64ada8,0x2da80000,0x2da83000,0xada88000,0xada8b000,0xaa1f8000,0xaf64ada8,0xaf64b000,0xaa1fada8,
  0x30003000,0x30003000,0x30003000,0x30003000,0x2f643000,0x2a1f2da8,0xaa1f0000,0xaf64ada8,0x2da83000,0xada80000,0xada8b000,0x2da88000,
  0x2a1f3000,0xaf64ada8,0x2f648000,0xaa1f2da8,0x00003000,0x8000b000,0x00003000,0x8000b000,0xaa1f3000,0x2f64ada8,0xaf640000,0x2a1f2da8,
  0xada83000,0x2da88000,0x2da8b000,0xada80000,0xaf643000,0xaa1f2da8,0x2a1f8000,0x2f64ada8,0x30003000,0x30003000,0x30003000,0x30003000,
  0xaf64b000,0xaa1fada8,0x2a1f8000,0x2f642da8,0x2da83000,0xada80000,0xada8b000,0x2da88000,0xaa1fb000,0x2f642da8,0xaf640000,0x2a1fada8,
  0x00003000,0x8000b000,0x00003000,0x8000b000,0x2a1fb000,0xaf642da8,0x2f648000,0xaa1fada8,0xada83000,0x2da88000,0x2da8b000,0xada80000,
  0x2f64b000,0x2a1fada8,0xaa1f0000,0xaf642da8,0xb0003000,0xb0003000,0xb0003000,0xb0003000,0xaf643000,0xaa1f2da8,0x2a1f0000,0x2f64ada8,
  0xada83000,0x2da80000,0x2da8b000,0xada88000,0xaa1f3000,0x2f64ada8,0xaf648000,0x2a1f2da8,0x80003000,0x0000b000,0x80003000,0x0000b000,
  0x2a1f3000,0xaf64ada8,0x2f640000,0xaa1f2da8,0x2da83000,0xada88000,0xada8b000,0x2da80000,0x2f643000,0x2a1f2da8,0xaa1f8000,0xaf64ada8,
  0xb0003000,0xb0003000,0xb0003000,0xb0003000,0x2f64b000,0x2a1fada8,0xaa1f8000,0xaf642da8,0xada83000,0x2da80000,0x2da8b000,0xada88000,
  0x2a1fb000,0xaf642da8,0x2f640000,0xaa1fada8,0x80003000,0x0000b000,0x80003000,0x0000b000,0xaa1fb000,0x2f642da8,0xaf648000,0x2a1fada8,
  0x2da83000,0xada88000,0xada8b000,0x2da80000,0xaf64b000,0xaa1fada8,0x2a1f0000,0x2f642da8,0x80008000,0x80008000,0x80008000,0x80008000,
  0x2a1f8000,0x2f642da8,0x2f643000,0x2a1f2da8,0x2da88000,0x2da83000,0xada80000,0xada8b000,0x2f648000,0xaa1f2da8,0xaa1fb000,0x2f642da8,
  0x30008000,0xb0000000,0x30008000,0xb0000000,0x2f648000,0xaa1fada8,0xaa1f3000,0x2f64ada8,0x2da88000,0x2da8b000,0xada80000,0xada83000,
  0x2a1f8000,0x2f64ada8,0x2f64b000,0x2a1fada8,0x80008000,0x80008000,0x80008000,0x80008000,0xaa1f0000,0xaf64ada8,0xaf64b000,0xaa1fada8,
  0x2da88000,0x2da83000,0xada80000,0xada8b000,0xaf640000,0x2a1fada8,0x2a1f3000,0xaf64ada8,0x30008000,0xb0000000,0x30008000,0xb0000000,
  0xaf640000,0x2a1f2da8,0x2a1fb000,0xaf642da8,0x2da88000,0x2da8b000,0xada80000,0xada83000,0xaa1f0000,0xaf642da8,0xaf643000,0xaa1f2da8,
  0x00008000,0x00008000,0x00008000,0x00008000,0xaa1f8000,0xaf642da8,0xaf643000,0xaa1f2da8,0xada88000,0xada83000,0x2da80000,0x2da8b000,
  0xaf648000,0x2a1f2da8,0x2a1fb000,0xaf642da8,0xb0008000,0x30000000,0xb0008000,0x30000000,0xaf648000,0x2a1fada8,0x2a1f3000,0xaf64ada8,
  0xada88000,0xada8b000,0x2da80000,0x2da83000,0xaa1f8000,0xaf64ada8,0xaf64b000,0xaa1fada8,0x00008000,0x00008000,0x00008000,0x00008000,
  0x2a1f0000,0x2f64ada8,0x2f64b000,0x2a1fada8,0xada88000,0xada83000,0x2da80000,0x2da8b000,0x2f640000,0xaa1fada8,0xaa1f3000,0x2f64ada8,
  0xb0008000,0x30000000,0xb0008000,0x30000000,0x2f640000,0xaa1f2da8,0xaa1fb000,0x2f642da8,0xada88000,0xada8b000,0x2da80000,0x2da83000,
  0x2a1f0000,0x2f642da8,0x2f643000,0x2a1f2da8,
};

constexpr int kThreads = 384;
constexpr int kCtas = 128;

#define PREP0 1600
#define PREPGAP 650
#define HT0 13800
#define HGAP 500
#define WQT 11800
#define QT 17800
#define QGAP 400
#define POSTGAP 1000
#define TAIL 3
#define PSW 6
constexpr int EARLY = 2, L0 = 2;

constexpr int NS1 = 6;
__host__ __device__ constexpr int slot1(int it) { return (it + 4) % NS1; }
__host__ __device__ constexpr uint32_t w1_off(int s) { return (1 + s + (s >> 1)) * 16384; }
__host__ __device__ constexpr uint32_t x1_off(int it) { return ((it >> 1) & 3) * 49152; }
constexpr uint32_t ST2 = 32768;
constexpr uint32_t RA = 131072;
constexpr uint32_t RB = 163840;
constexpr uint32_t RU = 196608;
constexpr uint32_t Y_IN = RU;
constexpr uint32_t SM_ONES = 229376;
constexpr uint32_t SM_F2 = SM_ONES + 128;
constexpr uint32_t SM_BAR = 231424;
constexpr uint32_t SM_SCALE = SM_ONES + 1792;
constexpr uint32_t SM_MAX = SM_BAR + 512;
constexpr uint32_t SM_TOTAL = 232448;
constexpr uint32_t SM_BASE = 1024;
__host__ __device__ constexpr uint32_t kv_off(int h) { return RB + (h >> 1) * 16384 + (h & 1) * 2560; }

enum Bar { B_F1 = 0, B_F2 = 6, B_H = B_F2 + 4, B_KVL = 12, B_RDY = 20, B_Q = 34, B_MAX, B_ZERO, B_U, B_KV,
           B_E1 = 39, B_E2 = 45, B_I2 = B_E2 + 4,
           B_KVE = 51, B_VST, B_KVM, B_KVP, B_KVI, B_OW, B_ZST = 58,
           B_OFREE = 59, B_F2M, B_STG, B_Y, B_COUNT = 64, B_U2 = B_KVL };
__host__ __device__ constexpr int slot2(int n) { return n < 22 ? n & 3 : (0x1032510325ull >> (4 * (n - 22))) & 7; }
__host__ __device__ constexpr int par2(int n) { return n < 22 ? (n >> 2) & 1 : (0x326 >> (n - 22)) & 1; }

constexpr int KV_WORDS = 4096 + 128;
struct Scratch {
  float kv[8][KV_WORDS];
  unsigned kvflag[8 * 32], zflag[8 * 32], oflag[16 * 32], epoch[kCtas];
};
struct Params {
  CUtensorMap w1, x, k, v, w2, wo, o, outa, q, outb;
  const __nv_bfloat16* shift_k;
  const __nv_bfloat16* ssm_k;
  const __nv_bfloat16* ssm_d;
  const __nv_bfloat16* q_ptr;
  const __nv_bfloat16* w_ptr;
  const __nv_bfloat16* wo_ptr;
  uint64_t zero;
  Scratch* g;
  const uint32_t* tab;
};

__device__ __align__(128) Scratch g_scratch;
__device__ __align__(128) __nv_bfloat16 g_o[2048 * 1024];

#define TSTAMP(cond, i) do { } while (0)
#define GSTAMP(cond, i) do { } while (0)
#define KSTAMP(n) do { } while (0)
#define QSTAMP(n) do { } while (0)

#define JIT() do { } while (0)
constexpr int kSpinLimit = 1 << 16;

DEVI void mbar_init(uint32_t a, uint32_t c) { asm volatile("mbarrier.init.shared::cta.b64 [%0], %1;" :: "r"(a), "r"(c) : "memory"); }
DEVI void mbar_expect(uint32_t a, uint32_t b) { asm volatile("mbarrier.arrive.expect_tx.shared::cta.b64 _, [%0], %1;" :: "r"(a), "r"(b) : "memory"); }
DEVI void mbar_arrive(uint32_t a) { asm volatile("mbarrier.arrive.shared::cta.b64 _, [%0];" :: "r"(a) : "memory"); }
DEVI void mbar_arrive_if(uint32_t a, bool pred) {
  asm volatile("{\n.reg .pred p;\nsetp.ne.b32 p, %1, 0;\n@p mbarrier.arrive.shared::cta.b64 _, [%0];\n}" :: "r"(a), "r"((int)pred) : "memory");
}
DEVI void mbar_wait(uint32_t a, uint32_t parity) {
  asm volatile("{\n.reg .pred p;\n.reg .u32 n;\nmov.u32 n, 0;\nW_LOOP:\n"
               "mbarrier.try_wait.parity.shared::cta.b64 p, [%0], %1;\n@p bra W_DONE;\n"
               "add.u32 n, n, 1;\nsetp.lt.u32 p, n, %2;\n@p bra W_LOOP;\nW_DONE:\n}"
               :: "r"(a), "r"(parity), "n"(kSpinLimit) : "memory");
  JIT();
}
DEVI void mbar_wait_long(uint32_t a, uint32_t parity) {
  asm volatile("{\n.reg .pred p;\n.reg .u32 n;\nmov.u32 n, 0;\nW_LOOP:\n"
               "mbarrier.try_wait.parity.shared::cta.b64 p, [%0], %1, %3;\n@p bra W_DONE;\n"
               "add.u32 n, n, 1;\nsetp.lt.u32 p, n, %2;\n@p bra W_LOOP;\nW_DONE:\n}"
               :: "r"(a), "r"(parity), "n"(kSpinLimit), "r"(4000) : "memory");
  JIT();
}
DEVI void flag_wait(const unsigned* p, unsigned target) {
  int n = 0; unsigned v;
  do {
    asm volatile("ld.relaxed.gpu.global.u32 %0, [%1];" : "=r"(v) : "l"(p) : "memory");
  } while ((int)(v - target) < 0 && ++n < kSpinLimit);
  asm volatile("fence.acquire.gpu;" ::: "memory");
}
DEVI unsigned ld_relaxed(const unsigned* p) { unsigned v; asm volatile("ld.relaxed.gpu.global.u32 %0, [%1];" : "=r"(v) : "l"(p) : "memory"); return v; }
DEVI uint32_t clock32() { uint32_t t; asm volatile("mov.u32 %0, %%clock;" : "=r"(t)); return t; }
DEVI void pace(uint32_t t0, uint32_t n) { while (clock32() - t0 < n) __nanosleep(20); }
DEVI bool elect() { uint32_t p; asm volatile("{\n.reg .pred p;\nelect.sync _|p, 0xffffffff;\nselp.u32 %0, 1, 0, p;\n}" : "=r"(p)); return p; }
DEVI void fence_async_smem() { asm volatile("fence.proxy.async.shared::cta;" ::: "memory"); }
DEVI void bar_sync(int id, int n) { asm volatile("bar.sync %0, %1;" :: "r"(id), "r"(n) : "memory"); }
DEVI void cluster_sync() { asm volatile("barrier.cluster.arrive.relaxed.aligned;\nbarrier.cluster.wait.aligned;" ::: "memory"); }
DEVI void wg_fence() { asm volatile("wgmma.fence.sync.aligned;" ::: "memory"); }
DEVI void wg_commit() { asm volatile("wgmma.commit_group.sync.aligned;" ::: "memory"); }
template <int N> DEVI void wg_wait() { asm volatile("wgmma.wait_group.sync.aligned %0;" :: "n"(N) : "memory"); }
template <int N> DEVI void pin(uint32_t* r) {
#pragma unroll
  for (int i = 0; i < N; i++) asm volatile("" : "+r"(r[i]));
}
template <int N> DEVI void pin(float* r) {
#pragma unroll
  for (int i = 0; i < N; i++) asm volatile("" : "+f"(r[i]));
}

DEVI void tma2d(uint32_t dst, const CUtensorMap* m, int c0, int c1, uint32_t bar) {
  asm volatile("cp.async.bulk.tensor.2d.shared::cluster.global.mbarrier::complete_tx::bytes [%0], [%1, {%3, %4}], [%2];"
               :: "r"(dst), "l"(m), "r"(bar), "r"(c0), "r"(c1) : "memory");
}
DEVI void tma2d_mc(uint32_t dst, const CUtensorMap* m, int c0, int c1, uint32_t bar) {
  asm volatile("cp.async.bulk.tensor.2d.shared::cluster.global.mbarrier::complete_tx::bytes.multicast::cluster [%0], [%1, {%3, %4}], [%2], %5;"
               :: "r"(dst), "l"(m), "r"(bar), "r"(c0), "r"(c1), "h"((uint16_t)3) : "memory");
}
DEVI void tma3d(uint32_t dst, const CUtensorMap* m, int c0, int c1, int c2, uint32_t bar) {
  asm volatile("cp.async.bulk.tensor.3d.shared::cluster.global.mbarrier::complete_tx::bytes [%0], [%1, {%3, %4, %5}], [%2];"
               :: "r"(dst), "l"(m), "r"(bar), "r"(c0), "r"(c1), "r"(c2) : "memory");
}
DEVI void tma4d(uint32_t dst, const CUtensorMap* m, int c1, int c2, int c3, uint32_t bar) {
  asm volatile("cp.async.bulk.tensor.4d.shared::cluster.global.mbarrier::complete_tx::bytes [%0], [%1, {%3, %4, %5, %6}], [%2];"
               :: "r"(dst), "l"(m), "r"(bar), "r"(0), "r"(c1), "r"(c2), "r"(c3) : "memory");
}
DEVI void tma5d(uint32_t dst, const CUtensorMap* m, int c0, int c1, int c3, int c4, uint32_t bar) {
  asm volatile("cp.async.bulk.tensor.5d.shared::cluster.global.mbarrier::complete_tx::bytes [%0], [%1, {%3, %4, %5, %6, %7}], [%2];"
               :: "r"(dst), "l"(m), "r"(bar), "r"(c0), "r"(c1), "r"(0), "r"(c3), "r"(c4) : "memory");
}
DEVI void tma2d_store(const CUtensorMap* m, uint32_t src, int c0, int c1) {
  asm volatile("cp.async.bulk.tensor.2d.global.shared::cta.bulk_group [%0, {%2, %3}], [%1];" :: "l"(m), "r"(src), "r"(c0), "r"(c1) : "memory");
}
DEVI void tma2d_store_e(const CUtensorMap* m, uint32_t src, int c0, int c1) {
  asm volatile("{\n.reg .pred e;\nelect.sync _|e, 0xffffffff;\n@e cp.async.bulk.tensor.2d.global.shared::cta.bulk_group [%0, {%2, %3}], [%1];\n"
               "@e cp.async.bulk.commit_group;\n}" :: "l"(m), "r"(src), "r"(c0), "r"(c1) : "memory");
}
DEVI void tma5d_store(const CUtensorMap* m, uint32_t src, int c0, int c1, int c3, int c4) {
  asm volatile("cp.async.bulk.tensor.5d.global.shared::cta.bulk_group [%0, {%2, %3, %4, %5, %6}], [%1];\ncp.async.bulk.commit_group;"
               :: "l"(m), "r"(src), "r"(c0), "r"(c1), "r"(0), "r"(c3), "r"(c4) : "memory");
}
DEVI void bulk_load(uint32_t dst, const void* src, uint32_t bytes, uint32_t bar) {
  asm volatile("cp.async.bulk.shared::cluster.global.mbarrier::complete_tx::bytes [%0], [%1], %2, [%3];" :: "r"(dst), "l"(src), "r"(bytes), "r"(bar) : "memory");
}
DEVI uint32_t mapa(uint32_t a, int rank) { uint32_t r; asm("mapa.shared::cluster.u32 %0, %1, %2;" : "=r"(r) : "r"(a), "r"(rank)); return r; }
DEVI void st_async4(uint32_t dst, uint32_t a, uint32_t b, uint32_t c, uint32_t d, uint32_t bar) {
  asm volatile("st.async.weak.shared::cluster.mbarrier::complete_tx::bytes.v4.b32 [%0], {%1,%2,%3,%4}, [%5];"
               :: "r"(dst), "r"(a), "r"(b), "r"(c), "r"(d), "r"(bar) : "memory");
}
DEVI void st_either8(bool local, uint32_t dst, uint32_t bar, uint32_t a, uint32_t b, uint32_t c, uint32_t d, uint32_t e, uint32_t f, uint32_t g, uint32_t h) {
  asm volatile("{\n.reg .pred p;\nsetp.ne.b32 p, %10, 0;\n@p st.shared.v4.b32 [%0], {%2,%3,%4,%5};\n@p st.shared.v4.b32 [%0 + 4096], {%6,%7,%8,%9};\n@p bra.uni E_DONE;\n"
               "st.async.weak.shared::cluster.mbarrier::complete_tx::bytes.v4.b32 [%0], {%2,%3,%4,%5}, [%1];\n"
               "st.async.weak.shared::cluster.mbarrier::complete_tx::bytes.v4.b32 [%0 + 4096], {%6,%7,%8,%9}, [%1];\nE_DONE:\n}"
               :: "r"(dst), "r"(bar), "r"(a), "r"(b), "r"(c), "r"(d), "r"(e), "r"(f), "r"(g), "r"(h), "r"((int)local) : "memory");
}
DEVI void red_async_max(uint32_t dst, uint32_t a, uint32_t bar) {
  asm volatile("red.async.relaxed.cluster.shared::cluster.mbarrier::complete_tx::bytes.max.u32 [%0], %1, [%2];" :: "r"(dst), "r"(a), "r"(bar) : "memory");
}
DEVI void pf_line(const void* p) { asm volatile("prefetch.global.L2 [%0];" :: "l"(p) : "memory"); }
DEVI void bulk_commit() { asm volatile("cp.async.bulk.commit_group;" ::: "memory"); }
DEVI void bulk_wait_all() { asm volatile("cp.async.bulk.wait_group 0;" ::: "memory"); }
DEVI void bulk_wait_read() { asm volatile("cp.async.bulk.wait_group.read 0;" ::: "memory"); }
DEVI void prefetch_map(const CUtensorMap* m) { asm volatile("prefetch.tensormap [%0];" :: "l"(m) : "memory"); }

__host__ __device__ constexpr uint32_t dlo(uint32_t off, uint32_t lbo) { return (off >> 4) + ((lbo >> 4) << 16); }
struct Desc {
  uint64_t v;
  DEVI Desc(uint64_t z, uint32_t base, uint32_t sbo, uint32_t mode) : v(z + (base | (uint64_t)((sbo >> 4) | (mode << 30)) << 32)) { asm volatile("" : "+l"(v)); }
  DEVI void renew(uint64_t z) { asm volatile("add.s64 %0, %0, %1;" : "+l"(v) : "l"(z)); }
  DEVI uint64_t at(uint32_t lo) const { uint64_t r; asm volatile("add.s64 %0, %1, %2;" : "=l"(r) : "l"(v), "l"((int64_t)(int32_t)lo)); return r; }
};
DEVI uint32_t pack_bf16(float lo, float hi) { uint32_t r; asm("cvt.rn.bf16x2.f32 %0, %1, %2;" : "=r"(r) : "f"(hi), "f"(lo)); return r; }
DEVI uint32_t pack_f16(float lo, float hi) { uint32_t r; asm("cvt.rn.f16x2.f32 %0, %1, %2;" : "=r"(r) : "f"(hi), "f"(lo)); return r; }
DEVI void stsm4(uint32_t addr, uint32_t r0, uint32_t r1, uint32_t r2, uint32_t r3) {
  asm volatile("stmatrix.sync.aligned.m8n8.x4.shared.b16 [%0], {%1,%2,%3,%4};" :: "r"(addr), "r"(r0), "r"(r1), "r"(r2), "r"(r3) : "memory");
}
DEVI void stsm4_t(uint32_t addr, uint32_t r0, uint32_t r1, uint32_t r2, uint32_t r3) {
  asm volatile("stmatrix.sync.aligned.m8n8.x4.trans.shared.b16 [%0], {%1,%2,%3,%4};" :: "r"(addr), "r"(r0), "r"(r1), "r"(r2), "r"(r3) : "memory");
}
DEVI void sts128(uint32_t addr, uint32_t a, uint32_t b, uint32_t c, uint32_t d) {
  asm volatile("st.shared.v4.b32 [%0], {%1,%2,%3,%4};" :: "r"(addr), "r"(a), "r"(b), "r"(c), "r"(d) : "memory");
}
DEVI void sts32(uint32_t addr, uint32_t v) { asm volatile("st.shared.b32 [%0], %1;" :: "r"(addr), "r"(v) : "memory"); }
DEVI uint32_t lds32(uint32_t a) { uint32_t v; asm volatile("ld.shared.b32 %0, [%1];" : "=r"(v) : "r"(a)); return v; }
DEVI void lds128(uint32_t* v, uint32_t a) {
  asm volatile("ld.shared.v4.b32 {%0,%1,%2,%3}, [%4];" : "=r"(v[0]), "=r"(v[1]), "=r"(v[2]), "=r"(v[3]) : "r"(a));
}
DEVI void ldg128(uint32_t* v, const void* p) {
  asm volatile("ld.global.nc.L1::no_allocate.v4.b32 {%0,%1,%2,%3}, [%4];" : "=r"(v[0]), "=r"(v[1]), "=r"(v[2]), "=r"(v[3]) : "l"(p));
}
DEVI float rcp(float x) { float r; asm("rcp.approx.ftz.f32 %0, %1;" : "=f"(r) : "f"(x)); return r; }
DEVI float exp_sat(float t) {
  float e, s;
  asm("ex2.approx.ftz.f32 %0, %1;" : "=f"(e) : "f"(t * 1.4426950408889634f));
  asm("add.sat.f32 %0, %1, 0f358637BD;" : "=f"(s) : "f"(e));
  return s;
}
DEVI uint32_t phi2(float a, float b) {
  uint32_t r, o;
  asm("cvt.rn.relu.bf16x2.f32 %0, %1, %2;" : "=r"(r) : "f"(b), "f"(a));
  asm("add.rn.bf16x2 %0, %1, %2;" : "=r"(o) : "r"(r), "r"(pack_bf16(exp_sat(a), exp_sat(b))));
  return o;
}
DEVI void arrive_both(uint32_t bar, int lane, bool pred = true) {
  asm volatile("{\n.reg .pred p;\n.reg .b32 r;\nsetp.ne.b32 p, %2, 0;\nmapa.shared::cluster.u32 r, %0, %1;\n@p mbarrier.arrive.shared::cluster.b64 _, [r];\n}"
               :: "r"(bar), "r"(lane & 1), "r"((int)(pred && lane < 2)) : "memory");
}
DEVI uint32_t bmul2(uint32_t a, uint32_t b) { uint32_t r; asm("mul.rn.bf16x2 %0, %1, %2;" : "=r"(r) : "r"(a), "r"(b)); return r; }
DEVI uint32_t badd2(uint32_t a, uint32_t b) { uint32_t r; asm("add.rn.bf16x2 %0, %1, %2;" : "=r"(r) : "r"(a), "r"(b)); return r; }
DEVI uint32_t bamax2(uint32_t a, uint32_t b) { uint32_t r; asm("max.NaN.xorsign.abs.bf16x2 %0, %1, %2;" : "=r"(r) : "r"(a), "r"(b)); return r; }
DEVI uint32_t hmul2(uint32_t a, uint32_t b) { uint32_t r; asm("mul.rn.f16x2 %0, %1, %2;" : "=r"(r) : "r"(a), "r"(b)); return r; }
DEVI uint32_t hadd2(uint32_t a, uint32_t b) { uint32_t r; asm("add.rn.f16x2 %0, %1, %2;" : "=r"(r) : "r"(a), "r"(b)); return r; }
DEVI uint32_t hsub2(uint32_t a, uint32_t b) { uint32_t r; asm("sub.rn.f16x2 %0, %1, %2;" : "=r"(r) : "r"(a), "r"(b)); return r; }
DEVI uint32_t hfma2(uint32_t a, uint32_t b, uint32_t c) { uint32_t r; asm("fma.rn.f16x2 %0, %1, %2, %3;" : "=r"(r) : "r"(a), "r"(b), "r"(c)); return r; }
DEVI uint32_t hfnma2(uint32_t a, uint32_t b, uint32_t c) {
  uint32_t r; asm("{\n.reg .b32 n;\nneg.f16x2 n, %1;\nfma.rn.f16x2 %0, n, %2, %3;\n}" : "=r"(r) : "r"(a), "r"(b), "r"(c)); return r;
}
DEVI float bf_lo(uint32_t w) { return __uint_as_float(w << 16); }
DEVI float bf_hi(uint32_t w) { return __uint_as_float(w & 0xffff0000u); }

DEVI uint32_t chan_exponent(const uint32_t* w) {
  uint32_t m[4];
#pragma unroll
  for (int i = 0; i < 4; i++) m[i] = bamax2(w[i], w[i + 4]);
#pragma unroll
  for (int i = 8; i < 32; i++) m[i & 3] = bamax2(m[i & 3], w[i]);
  uint32_t x = bamax2(bamax2(m[0], m[1]), bamax2(m[2], m[3])) & 0x7fff7fffu;
  x = max(x >> 16, x & 0xffffu);
  x = __reduce_max_sync(0xffffffffu, x);
  return min(x >> 7, 251u);
}
DEVI uint32_t to_f16(uint32_t w, uint32_t mul) { const uint32_t y = bmul2(w, mul); return pack_f16(bf_lo(y), bf_hi(y)); }

struct Tile { int j, r; };
DEVI Tile tile_of() {
  int cta; asm volatile("mov.u32 %0, %%ctaid.x;" : "=r"(cta));
  const int cl = cta >> 1, lo = (cl - 4) >> 31, hi = (35 - cl) >> 31;
  const int p = cl - 4 + (lo & (36 + 7 * cl)) + (hi & ((((cl - 36) * 37) >> 8) + 1)), g = p & 7, rr = p >> 3;
  return Tile{(g & 6) | (cta & 1), 2 * rr + (g & 1)};
}

static_assert(TAIL <= 4, "the releases up to stage 26 feed the ring");
__host__ __device__ constexpr bool prew(int it) { return it >= 28 && it < 31; }

DEVI void twiddle(uint32_t& ore, uint32_t& oim, uint32_t re, uint32_t im, uint32_t t, uint32_t s) {
  re = hfma2(t, im, re);
  oim = hfma2(s, re, im);
  ore = hfma2(t, oim, re);
}

__global__ void __cluster_dims__(2, 1, 1) __launch_bounds__(kThreads, 1)
fused_kernel(const __grid_constant__ Params P) {
  extern __shared__ __align__(1024) uint8_t smem[];
  const int tid = threadIdx.x, lane = tid & 31;
  const int warp = tid >> 5, warpu = __shfl_sync(0xffffffffu, tid >> 5, 0);
  const int cta = blockIdx.x, rho = cta & 1, cl = cta >> 1;
  const uint32_t sb = SM_BASE + (rho << 24);
  const uint32_t tstart = clock32();
  auto bar = [&](int i) INL { return sb + SM_BAR + 8u * i; };
  auto load1 = [&](int it, int s, int j, int r, bool mc) INL {
    const uint32_t fb = bar(B_F1 + s), xs = sb + x1_off(it);
    mbar_expect(fb, (it & 1) ? 16384 : 32768);
    tma4d(sb + w1_off(s), &P.w1, 32 * it, 2 * j, 1, fb);
    if (!(it & 1)) {
      if (mc) tma2d_mc(xs + rho * 8192, &P.x, 32 * it, 128 * r + 64 * rho, fb);
      else { tma2d(xs, &P.x, 32 * it, 128 * r, fb); tma2d(xs + 8192, &P.x, 32 * it, 128 * r + 64, fb); }
    }
  };
  TSTAMP(tid == 0, 0); GSTAMP(tid == 0, 62);

  if (warpu == 8 && elect()) {
    prefetch_map(&P.w1); prefetch_map(&P.x);
    for (int i = 0; i < EARLY; i++) mbar_init(bar(B_F1 + slot1(i)), 1);
    const Tile T = tile_of();
    for (int i = 0; i < EARLY; i++) load1(i, slot1(i), T.j, T.r, false);
    TSTAMP(true, 18);
    for (int i = EARLY; i < NS1; i++) mbar_init(bar(B_F1 + slot1(i)), 1);
    asm volatile("fence.mbarrier_init.release.cluster;" ::: "memory");
  }
  if (warpu == 9 && elect()) {
    if (sb != (uint32_t)__cvta_generic_to_shared(smem)) __trap();
#pragma unroll
    for (int i = B_F2; i < B_Q; i++) mbar_init(bar(i), 1);
    mbar_expect(bar(B_H), 32768);
    asm volatile("fence.mbarrier_init.release.cluster;" ::: "memory");
  }
  if (warpu == 10 && elect()) {
#pragma unroll
    for (int i = B_Q; i < B_KVE; i++) mbar_init(bar(i), i < B_E1 ? 1 : 16);
    mbar_expect(bar(B_Q), 32768); mbar_expect(bar(B_U), 16384); mbar_expect(bar(B_MAX), 1024);
    asm volatile("fence.mbarrier_init.release.cluster;" ::: "memory");
  }
  if (warpu == 11 && elect()) {
#pragma unroll
    for (int i = B_KVE; i < B_COUNT; i++) mbar_init(bar(i), i < B_OFREE ? 8 : i == B_F2M ? 3 : i < B_Y ? 4 : 9);
    mbar_expect(bar(B_Y), 8192); mbar_expect(bar(B_Y + 1), 8192);
    asm volatile("fence.mbarrier_init.release.cluster;" ::: "memory");
  }
  __syncwarp();
  cluster_sync();

  if (warpu < 8) {
    asm volatile("setmaxnreg.inc.sync.aligned.u32 %0;" :: "n"(232));
    const int wg = warp >> 2, wq = warp & 3, g = lane >> 2, q = lane & 3;
    constexpr uint32_t sbq = SM_BASE >> 4;
    const uint32_t wgu = warpu >> 2;
    const uint64_t z64 = P.zero;
    Desc dA(z64, sbq + wgu * 512, 1024, 1), dB(z64, sbq, 1024, 1);
    const int srow = wg * 64 + wq * 16 + (lane & 15);
    const uint32_t stm = srow * 128 + (((lane >> 4) ^ (srow & 7)) << 4);
    auto stage2 = [&](float* acc, int n, bool first) INL {
      const int s = slot2(n);
      mbar_wait(bar(B_F2 + s), par2(n));
      const uint32_t da = s * (ST2 >> 4) + dlo(0, 16), db = s * (ST2 >> 4) + dlo(16384, 8192);
      wg_fence();
      const uint64_t a0 = dA.at(da), b0 = dB.at(db);
      if (first) mma_n128_init(acc, a0, b0); else mma_n128(acc, a0, b0);
#pragma unroll
      for (int kk = 1; kk < 4; kk++) mma_n128(acc, a0 + 2 * kk, b0 + kk * (2048 >> 4));
      wg_commit();
    };
    auto release2 = [&](int n) INL { arrive_both(bar(B_E2 + slot2(n)), lane); };
    auto publish = [&](int b) INL { fence_async_smem(); __syncwarp(); mbar_arrive_if(bar(b), lane == 0); };

    float aq[64];
    uint32_t f1[8], tw[4];
    uint32_t su[2][32], sh[2][32];
    uint32_t x0[4][8], x1[4][8], p0[2][8], p1[2][8], z0[2][8], z1[2][8];
    auto s1 = [&](uint32_t* d, uint32_t base) INL {
      Desc db(z64, sbq + wgu * 1024 + dlo(base, 128), 512, 0);
      wg_fence();
      mma_s1_init(d, f1, db.v);
      mma_s1(d, f1 + 4, db.at(256 >> 4));
      wg_commit();
    };
    const uint64_t dre = Desc(z64, sbq + dlo(SM_F2 + 512, 128), 256, 0).v, dim = Desc(z64, sbq + dlo(SM_F2, 128), 256, 0).v;
    auto fwd2 = [&](uint32_t (*x)[8], int c) INL {
      uint32_t a[4][8];
#pragma unroll
      for (int t = 0; t < 4; t++) {
        uint32_t* s = (t < 2 ? sh[c >> 1] : su[c >> 1]) + 16 * (c & 1) + 8 * (t & 1);
        pin<8>(s);
#pragma unroll
        for (int i = 0; i < 4; i++) twiddle(a[t][i], a[t][4 + i], s[4 * (i & 1) + (i & 2)], s[4 * (i & 1) + (i & 2) + 1], tw[i & 2], tw[(i & 2) + 1]);
      }
      wg_fence();
#pragma unroll
      for (int t = 0; t < 4; t++) { mma_s2_init(x[t], a[t], dre); mma_s2(x[t], a[t] + 4, dim); }
      wg_commit();
    };
    auto half2 = [&](uint32_t (*x)[8], uint32_t* s) INL {
      uint32_t a[2][8];
      pin<16>(s);
#pragma unroll
      for (int t = 0; t < 2; t++)
#pragma unroll
        for (int i = 0; i < 4; i++) twiddle(a[t][i], a[t][4 + i], s[8 * t + 4 * (i & 1) + (i & 2)], s[8 * t + 4 * (i & 1) + (i & 2) + 1], tw[i & 2], tw[(i & 2) + 1]);
      wg_fence();
#pragma unroll
      for (int t = 0; t < 2; t++) { mma_s2_init(x[t], a[t], dre); mma_s2(x[t], a[t] + 4, dim); }
      wg_commit();
    };
    auto product = [&](uint32_t (*a)[8], uint32_t (*x)[8], int i) INL {
#pragma unroll
      for (int t = 0; t < 4; t++) { pin<2>(x[t] + i); pin<2>(x[t] + 4 + i); }
      auto hr = [&](int l) INL { return x[l >> 1][i + (l & 1)]; };
      auto hi = [&](int l) INL { return x[l >> 1][4 + i + (l & 1)]; };
      auto ur = [&](int l) INL { return x[2 + (l >> 1)][i + (l & 1)]; };
      auto ui = [&](int l) INL { return x[2 + (l >> 1)][4 + i + (l & 1)]; };
      uint32_t gr[4], gi[4];
      gr[0] = hr(0); gi[0] = hi(0);
#pragma unroll
      for (int l = 1; l < 4; l++) { gr[l] = hadd2(hr(l), hi(l - 1)); gi[l] = hsub2(hi(l), hr(l - 1)); }
#pragma unroll
      for (int p = 0; p < 4; p++) {
        uint32_t re = hfnma2(gi[0], ui(p), hmul2(gr[0], ur(p))), im = hfma2(gi[0], ur(p), hmul2(gr[0], ui(p)));
#pragma unroll
        for (int l = 1; l <= p; l++) {
          re = hfnma2(gi[l], ui(p - l), hfma2(gr[l], ur(p - l), re));
          im = hfma2(gi[l], ur(p - l), hfma2(gr[l], ui(p - l), im));
        }
        a[p >> 1][i + (p & 1)] = re; a[p >> 1][4 + i + (p & 1)] = im;
      }
#pragma unroll
      for (int t = 0; t < 2; t++) { pin<2>(a[t] + i); pin<2>(a[t] + 4 + i); }
    };
    auto inv1 = [&](uint32_t (*z)[8], uint32_t (*a)[8]) INL {
      wg_fence();
#pragma unroll
      for (int t = 0; t < 2; t++) { mma_s2_init(z[t], a[t], dre); mma_s2_neg(z[t], a[t] + 4, dim); }
      wg_commit();
    };
    auto zstore = [&](uint32_t (*z)[8], int c) INL {
      const uint32_t zoff = sb + RB + (q >> 1) * (RU + 16 - RB) + (8 * rho + 4 * wg) * 2048 + (4 * (8 * wq + g) + 2 * (q & 1)) * 16;
#pragma unroll
      for (int t = 0; t < 2; t++) {
        uint32_t a[8];
        pin<8>(z[t]);
#pragma unroll
        for (int i = 0; i < 4; i++) twiddle(a[i], a[4 + i], z[t][i], z[t][4 + i], tw[i & 2], tw[(i & 2) + 1]);
        const uint32_t dst = zoff + t * (16384 - rho * 32768) + c * 2048;
        sts128(dst, a[0], a[1], a[2], a[3]);
        sts128(dst + 16, a[4], a[5], a[6], a[7]);
      }
    };
    float kvr[18];
    auto kvstore = [&]() INL {
      const uint32_t dst = sb + kv_off(warp >> 1) + (warp & 1) * 256 + lane * 4;
      pin<18>(kvr);
#pragma unroll
      for (int b = 0; b < 4; b++) { sts32(dst + b * 512, pack_bf16(kvr[4 * b], kvr[4 * b + 1])); sts32(dst + b * 512 + 128, pack_bf16(kvr[4 * b + 2], kvr[4 * b + 3])); }
      sts32(dst + 2048, pack_bf16(kvr[16], kvr[16])); sts32(dst + 2176, pack_bf16(kvr[17], kvr[17]));
      publish(B_KVI);
    };
    {
      float ak[64], av[64];
      Desc dK(z64, sbq + wgu * 256, 1024, 1);
      auto kstep = [&](int c, int i) INL {
        const int s = slot1(c);
        if (!prew(c - 1)) mbar_wait(bar(B_F1 + s), (c / NS1 + i) & 1);
        TSTAMP(tid == 0 && c == 0, 1);
        const uint32_t dx = dlo(x1_off(c + 6 * i), 16), dk = dlo(w1_off(s), 16);
        const uint64_t xb = dB.at(dx) + (c & 1) * 4;
        wg_fence();
        if (c == 0) { mma_kt_init(ak, dK.at(dk), xb); mma_kt_init(av, dK.at(dk + 512), xb); }
        else { mma_kt(ak, dK.at(dk), xb); mma_kt(av, dK.at(dk + 512), xb); }
        mma_kt(ak, dK.at(dk + 128), xb + 2);
        mma_kt(av, dK.at(dk + 640), xb + 2);
        wg_commit();
        wg_wait<1>();
        if (c > 0) arrive_both(bar(B_E1 + (s + NS1 - 1) % NS1), lane);
        if (prew(c)) mbar_wait(bar(B_F1 + slot1(c + 1)), ((c + 1) / NS1) & 1);
        KSTAMP(c + 6 * i);
      };
      auto renew = [&]() INL { dK.renew(z64); dB.renew(z64); };
      uint32_t kk[7], u[36], sw[4], mx[2], um = 0, eu;
      unsigned short dskip;
      const int cp = 4 * (warp & 1) + (lane >> 3), run = 8 * (warp >> 1) + (lane & 7);
      const uint32_t ua = sb + RB + run * 32 + ((warp ^ (lane >> 2)) & 1) * 16 + (lane >> 3) * 4;
      sts32(sb + SM_MAX + (lane & 15) * 4, 0);
      ldg128(sw, P.shift_k + (cl * 16 + 2 * cp) * 4);
      asm volatile("ld.global.nc.b16 %0, [%1];" : "=h"(dskip) : "l"(P.ssm_d + 8 * cta + warp));
#pragma unroll
      for (int c = 0; c < L0; c++) kstep(c, 0);
      {
        pin<4>(sw);
        const uint32_t t0 = __byte_perm(sw[0], sw[2], 0x5410), t1 = __byte_perm(sw[0], sw[2], 0x7632), t2 = __byte_perm(sw[1], sw[3], 0x5410);
        sw[3] = __byte_perm(sw[1], sw[3], 0x7632); sw[0] = t0; sw[1] = t1; sw[2] = t2;
        pin<4>(sw);
      }
      float tap0 = lane == 0 ? bf_lo(dskip) : 0.f;
      pin<1>(&tap0);
#pragma unroll
      for (int e = 0; e < 36; e++) u[e] = 0;
#pragma unroll
      for (int e = 0; e < 7; e++) kk[e] = 0;
      renew();
#pragma unroll
      for (int c = L0; c < L0 + 6; c++) kstep(c, 0);
      renew();
#pragma unroll 1
      for (int i = 1; i < 4; i++) {
#pragma unroll
        for (int h = 0; h < 3; h++) {
          kstep(L0 + 2 * h, i);
          {
            const int slot = (3 * i + h + 4) & 7;
#pragma unroll
            for (int e = 4 * h; e < 4 * h + 4; e++) { u[e] = u[e + 12]; u[e + 12] = u[e + 24]; }
            pin<4>(u + 4 * h); pin<4>(u + 4 * h + 12);
            mbar_wait(bar(B_KVL + slot), h == 2 && i == 3);
#pragma unroll
            for (int e = 0; e < 4; e++) { kk[3 + e] = lds32(ua + slot * 8192 + e * 1024); u[24 + 4 * h + e] = lds32(ua + slot * 8192 + 4096 + e * 1024); }
          }
          kstep(L0 + 2 * h + 1, i);
          pin<7>(kk); pin<4>(u + 24 + 4 * h);
#pragma unroll
          for (int e = 0; e < 4; e++) {
            uint32_t& y = u[24 + 4 * h + e];
            y = bmul2(badd2(badd2(badd2(bmul2(kk[e], sw[3]), bmul2(kk[1 + e], sw[2])), bmul2(kk[2 + e], sw[1])), bmul2(kk[3 + e], sw[0])), y);
            um = bamax2(um, y);
          }
          if (h == 0) um = i == 1 ? 0 : um;
          kk[0] = kk[4]; kk[1] = kk[5]; kk[2] = kk[6];
          pin<4>(u + 24 + 4 * h); pin<1>(&um);
          if (h == 1) mbar_arrive_if(bar(B_KVE), lane == 0 && i == 2);
        }
      }
      um = bamax2(um, __shfl_xor_sync(0xffffffffu, um, 1));
      um = bamax2(um, __shfl_xor_sync(0xffffffffu, um, 2));
      red_async_max(mapa(sb + SM_MAX + cp * 8 + (q & 1) * 4, q >> 1), min((um >> (7 + 16 * (q & 1))) & 0xffu, 251u), mapa(bar(B_MAX), q >> 1));
      renew();
#pragma unroll
      for (int c = L0 + 24; c < 28; c++) {
        kstep(c, 0);
        if (c == L0 + 24) { ldg128(f1, P.tab + (tid & 127) * 4); ldg128(f1 + 4, P.tab + 512 + (tid & 127) * 4); ldg128(tw, P.tab + 1024 + (tid & 127) * 4); }
      }
      mbar_wait(bar(B_MAX), 0);
      TSTAMP(tid == 0, 5);
      asm volatile("ld.shared.v2.b32 {%0,%1}, [%2];" : "=r"(mx[0]), "=r"(mx[1]) : "r"(sb + SM_MAX + cp * 8));
      eu = lds32(sb + SM_MAX + (8 * rho + warp) * 4);
      const uint32_t ud = mapa(sb + RU + (lane >> 3) * 8192 + (2 * rho + wg) * 1024 + (run & 15) * 16, warp & 1), ub = mapa(bar(B_U), rho ^ 1);
#pragma unroll
      for (int i = 0; i < 4; i++) {
        kstep(28 + i, 0);
        if (i == 0) { pin<2>(mx); mx[0] = (0x00fd00fdu - (mx[0] | mx[1] << 16)) << 7; }
        uint32_t* y = u + 4 + 8 * i;
        pin<8>(y);
#pragma unroll
        for (int e = 0; e < 8; e++) y[e] = bmul2(y[e], mx[0]);
        st_either8((warpu & 1) == rho, ud + (i & 1) * 512 + (i >> 1) * 256, ub,
                   pack_f16(bf_lo(y[0]), bf_lo(y[1])), pack_f16(bf_lo(y[2]), bf_lo(y[3])), pack_f16(bf_lo(y[4]), bf_lo(y[5])), pack_f16(bf_lo(y[6]), bf_lo(y[7])),
                   pack_f16(bf_hi(y[0]), bf_hi(y[1])), pack_f16(bf_hi(y[2]), bf_hi(y[3])), pack_f16(bf_hi(y[4]), bf_hi(y[5])), pack_f16(bf_hi(y[6]), bf_hi(y[7])));
      }
      auto qstep = [&](int n) INL {
        if ((n & 3) == 0) { dA.renew(z64); dB.renew(z64); }
        stage2(aq, n, n == 0);
        wg_wait<1>();
        if (n == 0) arrive_both(bar(B_E1 + NS1 - 1), lane); else release2(n - 1);
        QSTAMP(n);
      };
      uint32_t pk[32];
      auto phik = [&](int i0, int i1) INL {
#pragma unroll
        for (int i = i0; i < i1; i++) { pin<2>(ak + 2 * i); pk[i] = phi2(ak[2 * i], ak[2 * i + 1]); pin<1>(pk + i); }
      };
      const uint32_t rot = tile_of().r & 3;
      const uint32_t stt = sb + RA + wg * 16384 + ((lane >> 4) * 8 + (lane & 7)) * 128 + (((2 * wq + ((lane >> 3) & 1)) ^ rot ^ (lane & 7)) << 4);
      auto vst = [&](int k0, int k1) INL {
#pragma unroll
        for (int kt = k0; kt < k1; kt++) {
          float* a = av + 8 * kt;
          pin<8>(a);
          stsm4_t(stt + kt * 2048, pack_bf16(a[0], a[1]), pack_bf16(a[2], a[3]), pack_bf16(a[4], a[5]), pack_bf16(a[6], a[7]));
        }
      };
      float dkv[36];
      Desc dV(z64, sbq + wgu * (1024u - (1024u << 16)) + dlo(RA, SM_ONES - RA), 1024, 1);
      auto kvmma = [&](int k0, int k1) INL {
        wg_fence();
#pragma unroll
        for (int ks = k0; ks < k1; ks++) {
          const uint64_t db = dV.at(ks * (128u - (128u << 16)));
          if (ks == 0) mma_kv_init(dkv, pk, db); else mma_kv(dkv, pk + 4 * ks, db);
        }
        wg_commit();
      };
      float* gacc;
      auto kvred = [&](int b) INL {
        const bool hh = wq >> 1;
        asm volatile("red.relaxed.gpu.global.add.v4.f32 [%0], {%1,%2,%3,%4};" :: "l"(gacc + (b ^ rot) * 128), "f"(hh ? dkv[16 + 4 * b] : dkv[4 * b]),
                     "f"(hh ? dkv[17 + 4 * b] : dkv[1 + 4 * b]), "f"(hh ? dkv[18 + 4 * b] : dkv[2 + 4 * b]), "f"(hh ? dkv[19 + 4 * b] : dkv[3 + 4 * b]) : "memory");
        if (b == 3) {
          asm volatile("{\n.reg .pred p;\nsetp.eq.s32 p, %3, 0;\n@p red.relaxed.gpu.global.add.v2.f32 [%0], {%1,%2};\n}"
                       :: "l"(gacc + 4096 - warp * 496 - g * 14), "f"(dkv[32]), "f"(dkv[34]), "r"(q) : "memory");
          __syncwarp();
          mbar_arrive_if(bar(B_KVP), lane == 0);
          TSTAMP(tid == 0, 4);
        }
      };
      uint32_t w[32], hmul;
      auto hload = [&](int i0, int i1) INL {
        const uint32_t a = sb + RB + warp * 4096 + (((lane >> 2) & 1) + (lane & 2) + 4 * (lane & 1) + (((lane << 2) ^ lane) & 24)) * 16;
#pragma unroll
        for (int i = i0; i < i1; i++) lds128(w + 4 * i, a + i * 512);
      };
      auto hmax = [&]() INL {
        pin<32>(w);
        tap0 += bf_lo(w[0]);
        w[0] = pack_bf16(tap0, bf_hi(w[0]));
        hmul = (252u - chan_exponent(w)) * 0x00800080u;
        const int e = min(max((int)(eu + 128 - (hmul >> 23)), 0), 254);
        asm volatile("st.shared.b16 [%0], %1;" :: "r"(sb + SM_SCALE + 2 * warp), "h"((unsigned short)(e << 7)) : "memory");
      };
      auto hstore = [&](int i0, int i1) INL {
        const uint32_t dst = sb + RB + warp * 4096 + (lane & 6) * 128 + ((lane ^ ((lane >> 2) & 6)) & 7) * 16;
#pragma unroll
        for (int i = i0; i < i1; i++) {
          pin<4>(w + 4 * i);
          const uint32_t w0 = i == 0 ? pack_f16(tap0 * bf_lo(hmul), bf_hi(w[0]) * bf_lo(hmul)) : to_f16(w[4 * i], hmul);
          sts128(dst + (i >> 1) * 1024 + (i & 1) * 128, w0, to_f16(w[4 * i + 1], hmul), to_f16(w[4 * i + 2], hmul), to_f16(w[4 * i + 3], hmul));
        }
      };
      auto kvload = [&]() INL {
        mbar_wait(bar(B_KV), 0);
        TSTAMP(tid == 0, 7);
#pragma unroll
        for (int b = 0; b < 4; b++)
          asm volatile("ld.global.cg.v4.f32 {%0,%1,%2,%3}, [%4];" : "=f"(kvr[4 * b]), "=f"(kvr[4 * b + 1]), "=f"(kvr[4 * b + 2]), "=f"(kvr[4 * b + 3]) : "l"(gacc + b * 128) : "memory");
        asm volatile("ld.global.cg.v2.f32 {%0,%1}, [%2];" : "=f"(kvr[16]), "=f"(kvr[17]) : "l"(gacc + 4096 - warp * 496 - g * 14 - q * 4) : "memory");
      };
      qstep(0);
      TSTAMP(tid == 0, 2);
      phik(0, 7);
      qstep(1);
      mbar_wait(bar(B_E1 + NS1 - 1), 1);
      vst(0, 4); phik(7, 10);
      qstep(2);
      vst(4, 8);
      publish(B_VST);
      phik(10, 13);
      qstep(3);
      mbar_wait(bar(B_ZERO), 0);
      mbar_wait(bar(B_VST), 0);
      kvmma(0, 3); phik(13, 20);
      qstep(4);
      kvmma(3, 5);
      mbar_wait(bar(B_H), 0);
      hload(0, 3); phik(20, 26);
      gacc = &P.g->kv[tile_of().j][warp * 512 + lane * 4];
      qstep(5);
      hload(3, 5); phik(26, 32); kvmma(5, 8); hload(5, 8);
      qstep(6);
      pin<36>(dkv);
      mbar_arrive_if(bar(B_KVM), lane == 0);
      kvred(0);
      mbar_wait(bar(B_U2), 1);
      s1(su[0], RU);
      hmax(); hstore(0, 1); kvred(1);
      qstep(7);
      hstore(1, 4); kvred(2);
      qstep(8);
      hstore(4, 6); kvred(3);
      qstep(9);
      hstore(6, 8);
      publish(B_VST);
      mbar_wait(bar(B_F2M), 0);
      half2(x0 + 2, su[0]);
      qstep(10);
      mbar_wait(bar(B_VST), 1);
      s1(sh[0], RB);
      half2(x1 + 2, su[0] + 16);
      qstep(11);
      half2(x0, sh[0]); half2(x1, sh[0] + 16);
      qstep(12);
      product(p0, x0, 0);
      qstep(13);
      product(p0, x0, 2);
      kvload();
      qstep(14);
      product(p1, x1, 0);
      qstep(15);
      product(p1, x1, 2);
    }

    float acc[64];
    {
      uint32_t pq[4][8];
      float dn[4][20];
      Desc dO(z64, sbq + dlo(0, 128), 512, 0);
      auto phiq = [&](int h) INL {
        pin<16>(aq + 16 * h);
#pragma unroll
        for (int i = 0; i < 8; i++) pq[h][i] = phi2(aq[16 * h + 2 * i], aq[16 * h + 2 * i + 1]);
        pin<8>(pq[h]);
      };
      auto omma = [&](int h) INL {
        wg_fence();
        mma_o_init(dn[h], pq[h], dO.at(kv_off(h) >> 4));
        mma_o(dn[h], pq[h] + 4, dO.at((kv_off(h) + 256) >> 4));
        wg_commit();
      };
      auto onorm = [&](int h) INL {
        pin<20>(dn[h]);
        const float i0 = rcp(dn[h][16] + 1e-6f), i1 = rcp(dn[h][18] + 1e-6f);
#pragma unroll
        for (int hf = 0; hf < 2; hf++) {
          const float* a = dn[h] + 8 * hf;
          stsm4(sb + (h >> 1) * ST2 + (stm ^ (((h & 1) * 2 + hf) << 5)), pack_bf16(a[0] * i0, a[1] * i0), pack_bf16(a[2] * i1, a[3] * i1),
                pack_bf16(a[4] * i0, a[5] * i0), pack_bf16(a[6] * i1, a[7] * i1));
        }
        if (h & 1) publish(B_OW + (h >> 1));
      };
      s1(su[1], RU + 8192);
      kvstore();
      wg_wait<1>();
      release2(15);
      TSTAMP(tid == 0, 6);
      uint32_t gf[4][4];
      auto gdup = [&]() INL {
#pragma unroll
        for (int i = 0; i < 4; i += 2) {
          pin<4>(gf[i + 1]);
          gf[i][0] = gf[i][1] = gf[i + 1][0]; gf[i][2] = gf[i][3] = gf[i + 1][1];
          gf[i + 1][0] = gf[i + 1][1] = gf[i + 1][2]; gf[i + 1][2] = gf[i + 1][3];
          pin<4>(gf[i]); pin<4>(gf[i + 1]);
        }
      };
      const uint32_t qa = sb + RA + warp * 4096 + lane * 32 + ((rho ^ g) & 1) * 16;
      uint32_t qv[4][4];
      auto qload = [&]() INL {
        mbar_wait(bar(B_Q), 0);
#pragma unroll
        for (int i = 0; i < 4; i++) lds128(qv[i], qa + i * 1024);
      };
      phiq(0); phiq(1);
      mbar_wait(bar(B_KVI), 0);
      omma(0); omma(1);
      wg_wait<1>(); onorm(0);
      wg_wait<0>(); onorm(1);
      TSTAMP(tid == 0, 8);
      s1(sh[1], RB + 8192);
      phiq(2); omma(2); phiq(3);
      wg_wait<0>(); onorm(2);
      omma(3); inv1(z0, p0);
      wg_wait<1>(); onorm(3);
      TSTAMP(tid == 0, 9);
      inv1(z1, p1); fwd2(x0, 2);
      wg_wait<1>();
      mbar_wait(bar(B_OW + 1), 0);
      zstore(z0, 0); zstore(z1, 1);
      wg_wait<0>();
      dA.renew(z64); dB.renew(z64);
      stage2(acc, 16, true);
      fwd2(x1, 3);
      product(p0, x0, 0); product(p0, x0, 2);
      inv1(z0, p0);
      stage2(acc, 17, false);
      wg_wait<2>();
      release2(16);
      ldg128(gf[1], P.tab + 1536 + (tid & 127) * 4); ldg128(gf[3], P.tab + 2048 + (tid & 127) * 4);
      product(p1, x1, 0); product(p1, x1, 2);
      inv1(z1, p1);
      wg_wait<2>();
      zstore(z0, 2);
      gdup();
      wg_wait<0>();
      release2(17);
      zstore(z1, 3);
      publish(B_ZST);
      TSTAMP(tid == 0, 10);
      qload();
      mbar_wait(bar(B_ZST), 0);
      float y[64];
      {
        Desc db(z64, sbq + wgu * ((RU + 16 - RB) >> 4) + dlo(RB, 128), 2048, 0);
        wg_fence();
        mma_i2_init(y, gf[0], db.v, 0xEEEE4444u);
#pragma unroll
        for (int i = 1; i < 4; i++) mma_i2(y, gf[i], db.at(i * (512 >> 4)), 0xEEEE4444u);
        wg_commit();
      }
      uint32_t sc[4];
      lds128(sc, sb + SM_SCALE);
      TSTAMP(tid == 0, 11);
      stage2(acc, 18, false);
      TSTAMP(tid == 0, 13);
      wg_wait<1>();
      QSTAMP(18);
      arrive_both(bar(B_I2), lane);
      pin<64>(y);
      uint32_t yv[8][4];
#pragma unroll
      for (int i = 0; i < 8; i++)
#pragma unroll
        for (int m = 0; m < 4; m++) yv[i][m] = bmul2(pack_bf16(y[32 * (i >> 2) + (i & 3) + 8 * m], y[32 * (i >> 2) + (i & 3) + 8 * m + 4]), sc[m]);
      pin<32>(&yv[0][0]);
      stage2(acc, 19, false);
      wg_wait<1>();
      QSTAMP(19);
      release2(18);
      mbar_wait(bar(B_I2), 0);
      const uint32_t yr = mapa(sb + Y_IN + tid * 16 + warp * 1536, rho ^ 1), yb = mapa(bar(B_Y), rho ^ 1);
      dA.renew(z64); dB.renew(z64);
#pragma unroll
      for (int i = 0; i < 4; i++) {
        if (i) { stage2(acc, 19 + i, false); wg_wait<1>(); QSTAMP(19 + i); release2(18 + i); }
        pin<4>(qv[i]);
        sts128(qa + i * 1024, bmul2(yv[i][0], qv[i][0]), bmul2(yv[i][1], qv[i][1]), bmul2(yv[i][2], qv[i][2]), bmul2(yv[i][3], qv[i][3]));
        st_async4(yr + i * 512, yv[4 + i][0], yv[4 + i][1], yv[4 + i][2], yv[4 + i][3], yb + 8 * (i >> 1));
        if (i & 1) { __syncwarp(); mbar_arrive_if(bar(B_Y + (i >> 1)), lane == 0); }
      }
      TSTAMP(tid == 0, 12);
    }
#pragma unroll 1
    for (int n = 23; n < 32 - TAIL; n++) {
      stage2(acc, n, false);
      TSTAMP(tid == 0 && n == 26, 14);
      wg_wait<1>();
      release2(n - 1);
      QSTAMP(n);
    }
    {
      const Tile T = tile_of();
      dA.renew(z64); dB.renew(z64);
      mbar_wait(bar(B_STG), wgu ^ 1);
#pragma unroll
      for (int n = 32 - TAIL; n < 32; n++) {
        stage2(acc, n, false);
        if (n == 28) { wg_wait<1>(); release2(27); }
      }
      mbar_wait(bar(wgu ? B_E2 + 5 : B_STG), 1);
      mbar_arrive_if(bar(B_STG), wgu == 0 && lane == 0);
      const uint32_t stg = sb + (wgu ? RB - 8192 : RU + 16384);
      wg_wait<0>();
      TSTAMP(tid == 0, 17); TSTAMP(tid == 128, 15);
      pin<64>(acc);
#pragma unroll
      for (int c = 0; c < 2; c++) {
#pragma unroll
        for (int t = 0; t < 4; t++) {
          const float* a = acc + 32 * c + 8 * t;
          stsm4(stg + c * 8192 + (stm ^ (t << 5)), pack_bf16(a[0], a[1]), pack_bf16(a[2], a[3]), pack_bf16(a[4], a[5]), pack_bf16(a[6], a[7]));
        }
        fence_async_smem();
        __syncwarp();
        tma2d_store_e(&P.outa, stg + c * 8192 + warpu * 2048, 128 * T.j + 64 * c, 128 * T.r + 16 * warpu);
      }
      bulk_wait_read();
      TSTAMP(tid == 128, 16);
    }
  } else {
    asm volatile("setmaxnreg.dec.sync.aligned.u32 %0;" :: "n"(40));
    const Tile T = tile_of();
    const int j = T.j, r = T.r;
    auto kcol = [&](int n) INL {
      return n < 20 ? 128 * (j ^ ((n >> 1) & 1)) + 64 * (n & 1) : 128 * (((j & 6) + n - (n < 26 ? 18 : 24)) & 7) + (n < 26 ? 0 : 64);
    };
    if (warpu == 8) {
      uint32_t ph = 0;
      int s = slot1(EARLY);
#pragma unroll 1
      for (int it = EARLY; it < 32; ++it, s = s + 1 == NS1 ? 0 : s + 1) {
        if (it >= NS1) { mbar_wait(bar(B_E1 + s), (ph >> s) & 1); ph ^= 1u << s; }
        if (elect()) load1(it, s, j, r, true);
      }
      int qn = 0;
      auto loadq = [&](int n) INL {
        if ((0x9c000 >> n) & 1) { if (elect()) tma5d(sb + RA + qn * 8192, &P.q, 16 * cl, 2 * rho, 2 * (qn & 2), 2 * (qn & 1), bar(B_Q)); qn++; }
      };
#pragma unroll 1
      for (int n = 0; n < 16; ++n) {
        const int s = n & 3, i = n + (n >> 1);
        mbar_wait(bar(n < 4 ? B_E1 + i : B_E2 + s), n < 4 ? (ph >> i) & 1 : ((n >> 2) - 1) & 1);
        const uint32_t st = sb + s * ST2, fb = bar(B_F2 + s);
        if (elect()) {
          mbar_expect(fb, ST2);
          tma4d(st + 16384, &P.w2, 64 * n, 2 * j, 0, fb);
          tma2d_mc(st + rho * 8192, &P.x, 64 * n, 128 * r + 64 * rho, fb);
        }
        loadq(n);
      }
      auto loadw = [&](int n) INL {
        const int s = n & 3;
        mbar_wait(bar(B_E2 + s), ((n >> 2) - 1) & 1);
        if (elect()) { mbar_expect(bar(B_F2 + s), n < 18 ? 16384 : ST2); tma4d(sb + s * ST2 + 16384, &P.wo, kcol(n), 2 * j, 0, bar(B_F2 + s)); }
      };
#pragma unroll 1
      for (int n = 16; n < 20; ++n) {
        loadw(n);
        loadq(n);
      }
#pragma unroll 1
      for (int n = 18; n < 20; ++n) {
        const uint32_t st = sb + (n & 3) * ST2, fb = bar(B_F2 + (n & 3));
        mbar_wait(bar(B_RDY + n - 18), 0);
        asm volatile("fence.proxy.async.global;" ::: "memory");
        if (elect()) { tma2d(st, &P.o, kcol(n), 128 * r, fb); tma2d(st + 8192, &P.o, kcol(n), 128 * r + 64, fb); }
      }
      mbar_wait(bar(B_OFREE), 0);
      uint64_t slots = 0x103251032510ull, frees = 0x103251032410ull;
      uint32_t pars = 0xc9f, kc = 128 * (j & 6) + 256;
#pragma unroll 1
      for (int n = 20; n < 32; ++n, slots >>= 4, frees >>= 4, pars >>= 1, kc += n == 26 ? 448 : 128) {
        const uint32_t s = slots & 7, st = sb + s * ST2, fb = bar(B_F2 + s);
        mbar_wait(bar(B_RDY + n - 18), 0);
        mbar_wait(bar(B_E2 + (frees & 7)), ~pars & 1);
        if (elect()) {
          mbar_expect(fb, ST2);
          tma4d(st + 16384, &P.wo, kc & 1023, 2 * j, 0, fb);
          tma2d_mc(st + rho * 8192, &P.o, kc & 1023, 128 * r + 64 * rho, fb);
        }
      }
    } else {
      const int at = tid - 288, aw = warpu - 9;
      const unsigned epoch = ld_relaxed(&P.g->epoch[cta]);
      if (aw < 2) {
        float4* zp = reinterpret_cast<float4*>(&P.g->kv[j][r * (KV_WORDS / 16)]) + at;
        zp[0] = zp[2] = make_float4(0.f, 0.f, 0.f, 0.f);
        sts128(sb + SM_ONES + (at & 15) * 128 + (at & 7) * 16, 0x3f803f80u, 0x3f803f80u, 0x3f803f80u, 0x3f803f80u);
        fence_async_smem();
        bar_sync(4, 64);
        if (at == 0) {
          asm volatile("fence.release.gpu;\nred.relaxed.gpu.global.add.u32 [%0], 1;" :: "l"(&P.g->zflag[j * 32]) : "memory");
          flag_wait(&P.g->zflag[j * 32], 16u * (epoch + 1));
          mbar_arrive(bar(B_ZERO));
        }
        __syncwarp();
      } else {
#pragma unroll 1
        for (int m = -1; m < 16; m++) {
          const int s = (m >> 1) & 7;
          pace(tstart, PREP0 + (m + 1) * PREPGAP);
          if (m == 14) mbar_wait(bar(B_KVE), 0);
          if (elect()) {
            if (m < 0 || !(m & 1)) mbar_expect(bar(B_KVL + s), m < 0 ? 4096 : 8192);
            tma3d(sb + RB + (m < 0 ? 14 : m) * 4096, m > 0 && (m & 1) ? &P.v : &P.k, 16 * cl, 32 * rho + (m >> 31), 2 * (m & 14), bar(B_KVL + s));
          }
        }
#pragma unroll 1
        for (int m = 0; m < 8; m++) {
          pace(tstart, HT0 + m * HGAP);
          if (elect()) bulk_load(sb + RB + m * 4096, P.ssm_k + (size_t)(8 * cta + m) * 2048, 4096, bar(B_H));
        }
      }
      if (aw == 1) {
        if (cta < 3) pf_line(P.tab + cta * 768 + lane * 32);
#pragma unroll 1
        for (int m = 0; m < 16; m++) {
          pace(tstart, m < 4 ? WQT + m * 500 : QT + (m - 4) * QGAP);
          pf_line(m < 4 ? P.w_ptr + (size_t)(cta + (2 * m + (lane >> 4)) * 128) * 3072 + (lane & 15) * 64
                        : (m < 12 ? P.q_ptr + cta * 16384 - 8192 : P.wo_ptr + cta * 8192 - 24576) + m * 2048 + lane * 64);
        }
      }
      uint32_t f2[4];
      ldg128(f2, P.tab + 2560 + at * 4);
      if (at == 0) { mbar_wait_long(bar(B_U), 0); fence_async_smem(); mbar_arrive(bar(B_U2)); }
      mbar_wait_long(bar(B_KVM), 0);
      sts128(sb + SM_F2 + at * 16, f2[0], f2[1], f2[2], f2[3]);
      fence_async_smem();
      __syncwarp();
      mbar_arrive_if(bar(B_F2M), lane == 0);
      if (aw == 2 && elect()) {
        mbar_wait(bar(B_KVP), 0);
        asm volatile("fence.release.gpu;\nred.relaxed.gpu.global.add.u32 [%0], 1;" :: "l"(&P.g->kvflag[j * 32]) : "memory");
        flag_wait(&P.g->kvflag[j * 32], 16u * (epoch + 1));
        mbar_arrive(bar(B_KV));
        TSTAMP(true, 19);
      }
      __syncwarp();
      if (aw < 2) {
        {
          const int c = aw;
          if (c == 1) {
            mbar_wait_long(bar(B_KVI), 0);
            if (elect()) { prefetch_map(&P.o); prefetch_map(&P.outb); prefetch_map(&P.outa); }
          }
          mbar_wait_long(bar(B_OW + c), 0);
          if (c == 1) mbar_wait(bar(B_ZERO), 1);
          if (elect()) {
            const uint32_t src = sb + c * ST2;
            tma2d_store(&P.o, src, 128 * j + 64 * c, 128 * r);
            tma2d_store(&P.o, src + 8192, 128 * j + 64 * c, 128 * r + 64);
            bulk_commit();
            bulk_wait_all();
            TSTAMP(c == 0, 21); TSTAMP(c == 1, 26);
            if (c == 0) mbar_arrive(bar(B_ZERO));
            asm volatile("mbarrier.arrive.shared::cluster.b64 _, [%0];\nmbarrier.arrive.shared::cluster.b64 _, [%1];"
                         :: "r"(mapa(bar(B_OFREE), 0)), "r"(mapa(bar(B_OFREE), 1)) : "memory");
            asm volatile("fence.release.gpu;\nst.relaxed.gpu.global.u32 [%0], %1;\nmbarrier.arrive.shared::cluster.b64 _, [%2];"
                         :: "l"(&P.g->oflag[r * 32 + 2 * j + c]), "r"(epoch + 1), "r"(mapa(bar(B_RDY + c), rho ^ 1)) : "memory");
            TSTAMP(c == 0, 22); TSTAMP(c == 1, 23);
          }
          __syncwarp();
        }
      } else {
        const unsigned* fp = &P.g->oflag[r * 32 + (kcol(18 + min(lane, 13)) >> 6)];
        bool done = lane > 13 || lane < 2;
        mbar_wait_long(bar(B_OW), 0);
        for (int i = 0; !__all_sync(0xffffffffu, done) && i < kSpinLimit; i++) {
          const bool now = !done && (int)(ld_relaxed(fp) - epoch) > 0;
          if (__any_sync(0xffffffffu, now)) {
            asm volatile("fence.acquire.gpu;\nfence.proxy.async.global;" ::: "memory");
            mbar_arrive_if(bar(B_RDY + lane), now);
            TSTAMP(lane == 2 && now, 24);
          }
          done |= now;
        }
        if (lane == 0) P.g->epoch[cta] = epoch + 1;
        TSTAMP(lane == 0, 25);
      }
#pragma unroll 1
      for (int m = aw; m < 16; m += 3) {
        const int u = 4 * (m & 7) + 2 * (m >> 3);
        mbar_wait_long(bar(B_Y + (m >> 3)), 0);
        TSTAMP(at == 0 && m == 0, 20);
        const uint32_t t0 = clock32();
        const uint32_t qa = sb + RA + u * 1024 + lane * 32 + ((rho ^ 1 ^ (lane >> 2)) & 1) * 16, ya = sb + Y_IN + u * 512 + lane * 16;
        uint32_t qv[2][4], yv[2][4];
#pragma unroll
        for (int h = 0; h < 2; h++) { lds128(qv[h], qa + h * 1024); lds128(yv[h], ya + h * 512); }
#pragma unroll
        for (int h = 0; h < 2; h++) sts128(qa + h * 1024, bmul2(qv[h][0], yv[h][0]), bmul2(qv[h][1], yv[h][1]), bmul2(qv[h][2], yv[h][2]), bmul2(qv[h][3], yv[h][3]));
        fence_async_smem();
        __syncwarp();
        if (elect()) tma5d_store(&P.outb, sb + RA + u * 1024, 1024 + 16 * cl, 2 * rho, (u >> 4) * 4 + (u & 3), (u >> 2) & 3);
        if (m < PSW) pace(t0, POSTGAP);
      }
      bulk_wait_read();
      TSTAMP(at == 0, 27);
    }
  }
  TSTAMP(tid == 128, 61); GSTAMP(tid == 128, 63);
}

typedef CUresult (*EncodeFn)(CUtensorMap*, CUtensorMapDataType, cuuint32_t, void*, const cuuint64_t*, const cuuint64_t*,
                             const cuuint32_t*, const cuuint32_t*, CUtensorMapInterleave, CUtensorMapSwizzle,
                             CUtensorMapL2promotion, CUtensorMapFloatOOBfill);

void encode(EncodeFn fn, CUtensorMap* m, const void* p, int rank, const cuuint64_t* dims, const cuuint64_t* strides,
            const cuuint32_t* box, CUtensorMapSwizzle sw) {
  const cuuint32_t es[5] = {1, 1, 1, 1, 1};
  fn(m, CU_TENSOR_MAP_DATA_TYPE_BFLOAT16, rank, const_cast<void*>(p), dims, strides, box, es, CU_TENSOR_MAP_INTERLEAVE_NONE, sw,
     CU_TENSOR_MAP_L2_PROMOTION_NONE, CU_TENSOR_MAP_FLOAT_OOB_FILL_NONE);
}
void encode2d(EncodeFn fn, CUtensorMap* m, const void* p, uint64_t cols, uint64_t rows, uint32_t bc, uint32_t br, CUtensorMapSwizzle sw) {
  const cuuint64_t dims[2] = {cols, rows}, strides[1] = {cols * 2};
  const cuuint32_t box[2] = {bc, br};
  encode(fn, m, p, 2, dims, strides, box, sw);
}
void encode3d(EncodeFn fn, CUtensorMap* m, const void* p) {
  const cuuint64_t dims[3] = {1024, 64, 32}, strides[2] = {2048 * 32, 2048};
  const cuuint32_t box[3] = {16, 32, 4};
  encode(fn, m, p, 3, dims, strides, box, CU_TENSOR_MAP_SWIZZLE_32B);
}
void encode4d(EncodeFn fn, CUtensorMap* m, const void* p, uint64_t cols, uint32_t rows, uint32_t nmat) {
  const cuuint64_t dims[4] = {64, 1024, 16, cols / 1024}, strides[3] = {cols * 2, 128, 2048};
  const cuuint32_t box[4] = {64, rows, 2, nmat};
  encode(fn, m, p, 4, dims, strides, box, CU_TENSOR_MAP_SWIZZLE_128B);
}
void encode5d(EncodeFn fn, CUtensorMap* m, const void* p, uint64_t cols, uint32_t n, uint32_t nw) {
  const cuuint64_t dims[5] = {cols, 4, 16, 8, 4}, strides[4] = {cols * 2 * 512, cols * 2 * 8, cols * 2, cols * 2 * 128};
  const cuuint32_t box[5] = {16, 2, 16, n, nw};
  encode(fn, m, p, 5, dims, strides, box, CU_TENSOR_MAP_SWIZZLE_32B);
}

}

extern "C" void kernel_launch(void* const* d_in, const int* in_sizes, int n_in, void* d_out, int out_size) {
  static EncodeFn fn = nullptr;
  static void *o_ptr = nullptr, *g_ptr = nullptr, *tab_ptr = nullptr;
  if (!fn) {
    cudaDriverEntryPointQueryResult qr;
    cudaGetDriverEntryPoint("cuTensorMapEncodeTiled", (void**)&fn, cudaEnableDefault, &qr);
    cudaGetSymbolAddress(&o_ptr, g_o);
    cudaGetSymbolAddress(&g_ptr, g_scratch);
    cudaGetSymbolAddress(&tab_ptr, d_tab);
    cudaFuncSetAttribute(fused_kernel, cudaFuncAttributeMaxDynamicSharedMemorySize, SM_TOTAL);
  }
  Params P;
  encode4d(fn, &P.w1, d_in[1], 3072, 32, 2);
  encode2d(fn, &P.x, d_in[0], 1024, 2048, 64, 64, CU_TENSOR_MAP_SWIZZLE_128B);
  encode4d(fn, &P.w2, d_in[1], 3072, 64, 1);
  encode4d(fn, &P.wo, d_in[2], 1024, 64, 1);
  encode2d(fn, &P.o, o_ptr, 1024, 2048, 64, 64, CU_TENSOR_MAP_SWIZZLE_128B);
  encode2d(fn, &P.outa, d_out, 2048, 2048, 64, 16, CU_TENSOR_MAP_SWIZZLE_128B);
  encode3d(fn, &P.k, d_in[4]);
  encode3d(fn, &P.v, d_in[5]);
  encode5d(fn, &P.q, d_in[3], 1024, 4, 2);
  encode5d(fn, &P.outb, d_out, 2048, 2, 1);
  P.shift_k = (const __nv_bfloat16*)d_in[6];
  P.ssm_k = (const __nv_bfloat16*)d_in[7];
  P.ssm_d = (const __nv_bfloat16*)d_in[8];
  P.q_ptr = (const __nv_bfloat16*)d_in[3];
  P.w_ptr = (const __nv_bfloat16*)d_in[1];
  P.wo_ptr = (const __nv_bfloat16*)d_in[2];
  P.zero = 0;
  P.g = (Scratch*)g_ptr;
  P.tab = (const uint32_t*)tab_ptr;
  fused_kernel<<<kCtas, kThreads, SM_TOTAL>>>(P);
}
```

```cpp
#include <cuda.h>
#include <cuda_runtime.h>
#include <cuda_bf16.h>
#include <stdint.h>

#define DEVI __device__ __forceinline__
#define INL __attribute__((always_inline))

namespace {

DEVI void mma_kt_init(float* d, uint64_t da, uint64_t db) {
  asm volatile("{\nwgmma.mma_async.sync.aligned.m64n128k16.f32.bf16.bf16 {%0, %1, %2, %3, %4, %5, %6, %7, %8, %9, %10, %11, %12, %13, %14, %15, %16, %17, %18, %19, %20, %21, %22, %23, %24, %25, %26, %27, %28, %29, %30, %31, %32, %33, %34, %35, %36, %37, %38, %39, %40, %41, %42, %43, %44, %45, %46, %47, %48, %49, %50, %51, %52, %53, %54, %55, %56, %57, %58, %59, %60, %61, %62, %63}, %64, %65, 0, 1, 1, 1, 0;\n}\n"
    : "=f"(d[0]), "=f"(d[1]), "=f"(d[2]), "=f"(d[3]), "=f"(d[4]), "=f"(d[5]), "=f"(d[6]), "=f"(d[7]), "=f"(d[8]), "=f"(d[9]), "=f"(d[10]), "=f"(d[11]), "=f"(d[12]), "=f"(d[13]), "=f"(d[14]), "=f"(d[15]), "=f"(d[16]), "=f"(d[17]), "=f"(d[18]), "=f"(d[19]), "=f"(d[20]), "=f"(d[21]), "=f"(d[22]), "=f"(d[23]), "=f"(d[24]), "=f"(d[25]), "=f"(d[26]), "=f"(d[27]), "=f"(d[28]), "=f"(d[29]), "=f"(d[30]), "=f"(d[31]), "=f"(d[32]), "=f"(d[33]), "=f"(d[34]), "=f"(d[35]), "=f"(d[36]), "=f"(d[37]), "=f"(d[38]), "=f"(d[39]), "=f"(d[40]), "=f"(d[41]), "=f"(d[42]), "=f"(d[43]), "=f"(d[44]), "=f"(d[45]), "=f"(d[46]), "=f"(d[47]), "=f"(d[48]), "=f"(d[49]), "=f"(d[50]), "=f"(d[51]), "=f"(d[52]), "=f"(d[53]), "=f"(d[54]), "=f"(d[55]), "=f"(d[56]), "=f"(d[57]), "=f"(d[58]), "=f"(d[59]), "=f"(d[60]), "=f"(d[61]), "=f"(d[62]), "=f"(d[63])
    : "l"(da), "l"(db));
}
DEVI void mma_kt(float* d, uint64_t da, uint64_t db) {
  asm volatile("{\nwgmma.mma_async.sync.aligned.m64n128k16.f32.bf16.bf16 {%0, %1, %2, %3, %4, %5, %6, %7, %8, %9, %10, %11, %12, %13, %14, %15, %16, %17, %18, %19, %20, %21, %22, %23, %24, %25, %26, %27, %28, %29, %30, %31, %32, %33, %34, %35, %36, %37, %38, %39, %40, %41, %42, %43, %44, %45, %46, %47, %48, %49, %50, %51, %52, %53, %54, %55, %56, %57, %58, %59, %60, %61, %62, %63}, %64, %65, 1, 1, 1, 1, 0;\n}\n"
    : "+f"(d[0]), "+f"(d[1]), "+f"(d[2]), "+f"(d[3]), "+f"(d[4]), "+f"(d[5]), "+f"(d[6]), "+f"(d[7]), "+f"(d[8]), "+f"(d[9]), "+f"(d[10]), "+f"(d[11]), "+f"(d[12]), "+f"(d[13]), "+f"(d[14]), "+f"(d[15]), "+f"(d[16]), "+f"(d[17]), "+f"(d[18]), "+f"(d[19]), "+f"(d[20]), "+f"(d[21]), "+f"(d[22]), "+f"(d[23]), "+f"(d[24]), "+f"(d[25]), "+f"(d[26]), "+f"(d[27]), "+f"(d[28]), "+f"(d[29]), "+f"(d[30]), "+f"(d[31]), "+f"(d[32]), "+f"(d[33]), "+f"(d[34]), "+f"(d[35]), "+f"(d[36]), "+f"(d[37]), "+f"(d[38]), "+f"(d[39]), "+f"(d[40]), "+f"(d[41]), "+f"(d[42]), "+f"(d[43]), "+f"(d[44]), "+f"(d[45]), "+f"(d[46]), "+f"(d[47]), "+f"(d[48]), "+f"(d[49]), "+f"(d[50]), "+f"(d[51]), "+f"(d[52]), "+f"(d[53]), "+f"(d[54]), "+f"(d[55]), "+f"(d[56]), "+f"(d[57]), "+f"(d[58]), "+f"(d[59]), "+f"(d[60]), "+f"(d[61]), "+f"(d[62]), "+f"(d[63])
    : "l"(da), "l"(db));
}
DEVI void mma_n128_init(float* d, uint64_t da, uint64_t db) {
  asm volatile("{\nwgmma.mma_async.sync.aligned.m64n128k16.f32.bf16.bf16 {%0, %1, %2, %3, %4, %5, %6, %7, %8, %9, %10, %11, %12, %13, %14, %15, %16, %17, %18, %19, %20, %21, %22, %23, %24, %25, %26, %27, %28, %29, %30, %31, %32, %33, %34, %35, %36, %37, %38, %39, %40, %41, %42, %43, %44, %45, %46, %47, %48, %49, %50, %51, %52, %53, %54, %55, %56, %57, %58, %59, %60, %61, %62, %63}, %64, %65, 0, 1, 1, 0, 1;\n}\n"
    : "=f"(d[0]), "=f"(d[1]), "=f"(d[2]), "=f"(d[3]), "=f"(d[4]), "=f"(d[5]), "=f"(d[6]), "=f"(d[7]), "=f"(d[8]), "=f"(d[9]), "=f"(d[10]), "=f"(d[11]), "=f"(d[12]), "=f"(d[13]), "=f"(d[14]), "=f"(d[15]), "=f"(d[16]), "=f"(d[17]), "=f"(d[18]), "=f"(d[19]), "=f"(d[20]), "=f"(d[21]), "=f"(d[22]), "=f"(d[23]), "=f"(d[24]), "=f"(d[25]), "=f"(d[26]), "=f"(d[27]), "=f"(d[28]), "=f"(d[29]), "=f"(d[30]), "=f"(d[31]), "=f"(d[32]), "=f"(d[33]), "=f"(d[34]), "=f"(d[35]), "=f"(d[36]), "=f"(d[37]), "=f"(d[38]), "=f"(d[39]), "=f"(d[40]), "=f"(d[41]), "=f"(d[42]), "=f"(d[43]), "=f"(d[44]), "=f"(d[45]), "=f"(d[46]), "=f"(d[47]), "=f"(d[48]), "=f"(d[49]), "=f"(d[50]), "=f"(d[51]), "=f"(d[52]), "=f"(d[53]), "=f"(d[54]), "=f"(d[55]), "=f"(d[56]), "=f"(d[57]), "=f"(d[58]), "=f"(d[59]), "=f"(d[60]), "=f"(d[61]), "=f"(d[62]), "=f"(d[63])
    : "l"(da), "l"(db));
}
DEVI void mma_n128(float* d, uint64_t da, uint64_t db) {
  asm volatile("{\nwgmma.mma_async.sync.aligned.m64n128k16.f32.bf16.bf16 {%0, %1, %2, %3, %4, %5, %6, %7, %8, %9, %10, %11, %12, %13, %14, %15, %16, %17, %18, %19, %20, %21, %22, %23, %24, %25, %26, %27, %28, %29, %30, %31, %32, %33, %34, %35, %36, %37, %38, %39, %40, %41, %42, %43, %44, %45, %46, %47, %48, %49, %50, %51, %52, %53, %54, %55, %56, %57, %58, %59, %60, %61, %62, %63}, %64, %65, 1, 1, 1, 0, 1;\n}\n"
    : "+f"(d[0]), "+f"(d[1]), "+f"(d[2]), "+f"(d[3]), "+f"(d[4]), "+f"(d[5]), "+f"(d[6]), "+f"(d[7]), "+f"(d[8]), "+f"(d[9]), "+f"(d[10]), "+f"(d[11]), "+f"(d[12]), "+f"(d[13]), "+f"(d[14]), "+f"(d[15]), "+f"(d[16]), "+f"(d[17]), "+f"(d[18]), "+f"(d[19]), "+f"(d[20]), "+f"(d[21]), "+f"(d[22]), "+f"(d[23]), "+f"(d[24]), "+f"(d[25]), "+f"(d[26]), "+f"(d[27]), "+f"(d[28]), "+f"(d[29]), "+f"(d[30]), "+f"(d[31]), "+f"(d[32]), "+f"(d[33]), "+f"(d[34]), "+f"(d[35]), "+f"(d[36]), "+f"(d[37]), "+f"(d[38]), "+f"(d[39]), "+f"(d[40]), "+f"(d[41]), "+f"(d[42]), "+f"(d[43]), "+f"(d[44]), "+f"(d[45]), "+f"(d[46]), "+f"(d[47]), "+f"(d[48]), "+f"(d[49]), "+f"(d[50]), "+f"(d[51]), "+f"(d[52]), "+f"(d[53]), "+f"(d[54]), "+f"(d[55]), "+f"(d[56]), "+f"(d[57]), "+f"(d[58]), "+f"(d[59]), "+f"(d[60]), "+f"(d[61]), "+f"(d[62]), "+f"(d[63])
    : "l"(da), "l"(db));
}
DEVI void mma_kv_init(float* d, const uint32_t* a, uint64_t db) {
  asm volatile("{\nwgmma.mma_async.sync.aligned.m64n72k16.f32.bf16.bf16 {%0, %1, %2, %3, %4, %5, %6, %7, %8, %9, %10, %11, %12, %13, %14, %15, %16, %17, %18, %19, %20, %21, %22, %23, %24, %25, %26, %27, %28, %29, %30, %31, %32, %33, %34, %35}, {%36,%37,%38,%39}, %40, 0, 1, 1, 1;\n}\n"
    : "=f"(d[0]), "=f"(d[1]), "=f"(d[2]), "=f"(d[3]), "=f"(d[4]), "=f"(d[5]), "=f"(d[6]), "=f"(d[7]), "=f"(d[8]), "=f"(d[9]), "=f"(d[10]), "=f"(d[11]), "=f"(d[12]), "=f"(d[13]), "=f"(d[14]), "=f"(d[15]), "=f"(d[16]), "=f"(d[17]), "=f"(d[18]), "=f"(d[19]), "=f"(d[20]), "=f"(d[21]), "=f"(d[22]), "=f"(d[23]), "=f"(d[24]), "=f"(d[25]), "=f"(d[26]), "=f"(d[27]), "=f"(d[28]), "=f"(d[29]), "=f"(d[30]), "=f"(d[31]), "=f"(d[32]), "=f"(d[33]), "=f"(d[34]), "=f"(d[35])
    : "r"(a[0]), "r"(a[1]), "r"(a[2]), "r"(a[3]), "l"(db));
}
DEVI void mma_kv(float* d, const uint32_t* a, uint64_t db) {
  asm volatile("{\nwgmma.mma_async.sync.aligned.m64n72k16.f32.bf16.bf16 {%0, %1, %2, %3, %4, %5, %6, %7, %8, %9, %10, %11, %12, %13, %14, %15, %16, %17, %18, %19, %20, %21, %22, %23, %24, %25, %26, %27, %28, %29, %30, %31, %32, %33, %34, %35}, {%36,%37,%38,%39}, %40, 1, 1, 1, 1;\n}\n"
    : "+f"(d[0]), "+f"(d[1]), "+f"(d[2]), "+f"(d[3]), "+f"(d[4]), "+f"(d[5]), "+f"(d[6]), "+f"(d[7]), "+f"(d[8]), "+f"(d[9]), "+f"(d[10]), "+f"(d[11]), "+f"(d[12]), "+f"(d[13]), "+f"(d[14]), "+f"(d[15]), "+f"(d[16]), "+f"(d[17]), "+f"(d[18]), "+f"(d[19]), "+f"(d[20]), "+f"(d[21]), "+f"(d[22]), "+f"(d[23]), "+f"(d[24]), "+f"(d[25]), "+f"(d[26]), "+f"(d[27]), "+f"(d[28]), "+f"(d[29]), "+f"(d[30]), "+f"(d[31]), "+f"(d[32]), "+f"(d[33]), "+f"(d[34]), "+f"(d[35])
    : "r"(a[0]), "r"(a[1]), "r"(a[2]), "r"(a[3]), "l"(db));
}
DEVI void mma_o_init(float* d, const uint32_t* a, uint64_t db) {
  asm volatile("{\nwgmma.mma_async.sync.aligned.m64n40k16.f32.bf16.bf16 {%0, %1, %2, %3, %4, %5, %6, %7, %8, %9, %10, %11, %12, %13, %14, %15, %16, %17, %18, %19}, {%20,%21,%22,%23}, %24, 0, 1, 1, 1;\n}\n"
    : "=f"(d[0]), "=f"(d[1]), "=f"(d[2]), "=f"(d[3]), "=f"(d[4]), "=f"(d[5]), "=f"(d[6]), "=f"(d[7]), "=f"(d[8]), "=f"(d[9]), "=f"(d[10]), "=f"(d[11]), "=f"(d[12]), "=f"(d[13]), "=f"(d[14]), "=f"(d[15]), "=f"(d[16]), "=f"(d[17]), "=f"(d[18]), "=f"(d[19])
    : "r"(a[0]), "r"(a[1]), "r"(a[2]), "r"(a[3]), "l"(db));
}
DEVI void mma_o(float* d, const uint32_t* a, uint64_t db) {
  asm volatile("{\nwgmma.mma_async.sync.aligned.m64n40k16.f32.bf16.bf16 {%0, %1, %2, %3, %4, %5, %6, %7, %8, %9, %10, %11, %12, %13, %14, %15, %16, %17, %18, %19}, {%20,%21,%22,%23}, %24, 1, 1, 1, 1;\n}\n"
    : "+f"(d[0]), "+f"(d[1]), "+f"(d[2]), "+f"(d[3]), "+f"(d[4]), "+f"(d[5]), "+f"(d[6]), "+f"(d[7]), "+f"(d[8]), "+f"(d[9]), "+f"(d[10]), "+f"(d[11]), "+f"(d[12]), "+f"(d[13]), "+f"(d[14]), "+f"(d[15]), "+f"(d[16]), "+f"(d[17]), "+f"(d[18]), "+f"(d[19])
    : "r"(a[0]), "r"(a[1]), "r"(a[2]), "r"(a[3]), "l"(db));
}
DEVI void mma_s1_init(uint32_t* d, const uint32_t* a, uint64_t db) {
  asm volatile("{\nwgmma.mma_async.sync.aligned.m64n128k16.f16.f16.f16 {%0, %1, %2, %3, %4, %5, %6, %7, %8, %9, %10, %11, %12, %13, %14, %15, %16, %17, %18, %19, %20, %21, %22, %23, %24, %25, %26, %27, %28, %29, %30, %31}, {%32,%33,%34,%35}, %36, 0, 1, 1, 1;\n}\n"
    : "=r"(d[0]), "=r"(d[1]), "=r"(d[2]), "=r"(d[3]), "=r"(d[4]), "=r"(d[5]), "=r"(d[6]), "=r"(d[7]), "=r"(d[8]), "=r"(d[9]), "=r"(d[10]), "=r"(d[11]), "=r"(d[12]), "=r"(d[13]), "=r"(d[14]), "=r"(d[15]), "=r"(d[16]), "=r"(d[17]), "=r"(d[18]), "=r"(d[19]), "=r"(d[20]), "=r"(d[21]), "=r"(d[22]), "=r"(d[23]), "=r"(d[24]), "=r"(d[25]), "=r"(d[26]), "=r"(d[27]), "=r"(d[28]), "=r"(d[29]), "=r"(d[30]), "=r"(d[31])
    : "r"(a[0]), "r"(a[1]), "r"(a[2]), "r"(a[3]), "l"(db));
}
DEVI void mma_s1(uint32_t* d, const uint32_t* a, uint64_t db) {
  asm volatile("{\nwgmma.mma_async.sync.aligned.m64n128k16.f16.f16.f16 {%0, %1, %2, %3, %4, %5, %6, %7, %8, %9, %10, %11, %12, %13, %14, %15, %16, %17, %18, %19, %20, %21, %22, %23, %24, %25, %26, %27, %28, %29, %30, %31}, {%32,%33,%34,%35}, %36, 1, 1, 1, 1;\n}\n"
    : "+r"(d[0]), "+r"(d[1]), "+r"(d[2]), "+r"(d[3]), "+r"(d[4]), "+r"(d[5]), "+r"(d[6]), "+r"(d[7]), "+r"(d[8]), "+r"(d[9]), "+r"(d[10]), "+r"(d[11]), "+r"(d[12]), "+r"(d[13]), "+r"(d[14]), "+r"(d[15]), "+r"(d[16]), "+r"(d[17]), "+r"(d[18]), "+r"(d[19]), "+r"(d[20]), "+r"(d[21]), "+r"(d[22]), "+r"(d[23]), "+r"(d[24]), "+r"(d[25]), "+r"(d[26]), "+r"(d[27]), "+r"(d[28]), "+r"(d[29]), "+r"(d[30]), "+r"(d[31])
    : "r"(a[0]), "r"(a[1]), "r"(a[2]), "r"(a[3]), "l"(db));
}
DEVI void mma_s2_init(uint32_t* d, const uint32_t* a, uint64_t db) {
  asm volatile("{\nwgmma.mma_async.sync.aligned.m64n32k16.f16.f16.f16 {%0, %1, %2, %3, %4, %5, %6, %7}, {%8,%9,%10,%11}, %12, 0, 1, 1, 0;\n}\n"
    : "=r"(d[0]), "=r"(d[1]), "=r"(d[2]), "=r"(d[3]), "=r"(d[4]), "=r"(d[5]), "=r"(d[6]), "=r"(d[7])
    : "r"(a[0]), "r"(a[1]), "r"(a[2]), "r"(a[3]), "l"(db));
}
DEVI void mma_s2(uint32_t* d, const uint32_t* a, uint64_t db) {
  asm volatile("{\nwgmma.mma_async.sync.aligned.m64n32k16.f16.f16.f16 {%0, %1, %2, %3, %4, %5, %6, %7}, {%8,%9,%10,%11}, %12, 1, 1, 1, 0;\n}\n"
    : "+r"(d[0]), "+r"(d[1]), "+r"(d[2]), "+r"(d[3]), "+r"(d[4]), "+r"(d[5]), "+r"(d[6]), "+r"(d[7])
    : "r"(a[0]), "r"(a[1]), "r"(a[2]), "r"(a[3]), "l"(db));
}
DEVI void mma_s2_neg(uint32_t* d, const uint32_t* a, uint64_t db) {
  asm volatile("{\nwgmma.mma_async.sync.aligned.m64n32k16.f16.f16.f16 {%0, %1, %2, %3, %4, %5, %6, %7}, {%8,%9,%10,%11}, %12, 1, -1, 1, 0;\n}\n"
    : "+r"(d[0]), "+r"(d[1]), "+r"(d[2]), "+r"(d[3]), "+r"(d[4]), "+r"(d[5]), "+r"(d[6]), "+r"(d[7])
    : "r"(a[0]), "r"(a[1]), "r"(a[2]), "r"(a[3]), "l"(db));
}
DEVI void mma_i2_init(float* d, const uint32_t* a, uint64_t db, uint32_t meta) {
  asm volatile("{\nwgmma.mma_async.sp.sync.aligned.m64n128k32.f32.f16.f16 {%0, %1, %2, %3, %4, %5, %6, %7, %8, %9, %10, %11, %12, %13, %14, %15, %16, %17, %18, %19, %20, %21, %22, %23, %24, %25, %26, %27, %28, %29, %30, %31, %32, %33, %34, %35, %36, %37, %38, %39, %40, %41, %42, %43, %44, %45, %46, %47, %48, %49, %50, %51, %52, %53, %54, %55, %56, %57, %58, %59, %60, %61, %62, %63}, {%64,%65,%66,%67}, %68, %69, 0, 0, 1, 1, 1;\n}\n"
    : "=f"(d[0]), "=f"(d[1]), "=f"(d[2]), "=f"(d[3]), "=f"(d[4]), "=f"(d[5]), "=f"(d[6]), "=f"(d[7]), "=f"(d[8]), "=f"(d[9]), "=f"(d[10]), "=f"(d[11]), "=f"(d[12]), "=f"(d[13]), "=f"(d[14]), "=f"(d[15]), "=f"(d[16]), "=f"(d[17]), "=f"(d[18]), "=f"(d[19]), "=f"(d[20]), "=f"(d[21]), "=f"(d[22]), "=f"(d[23]), "=f"(d[24]), "=f"(d[25]), "=f"(d[26]), "=f"(d[27]), "=f"(d[28]), "=f"(d[29]), "=f"(d[30]), "=f"(d[31]), "=f"(d[32]), "=f"(d[33]), "=f"(d[34]), "=f"(d[35]), "=f"(d[36]), "=f"(d[37]), "=f"(d[38]), "=f"(d[39]), "=f"(d[40]), "=f"(d[41]), "=f"(d[42]), "=f"(d[43]), "=f"(d[44]), "=f"(d[45]), "=f"(d[46]), "=f"(d[47]), "=f"(d[48]), "=f"(d[49]), "=f"(d[50]), "=f"(d[51]), "=f"(d[52]), "=f"(d[53]), "=f"(d[54]), "=f"(d[55]), "=f"(d[56]), "=f"(d[57]), "=f"(d[58]), "=f"(d[59]), "=f"(d[60]), "=f"(d[61]), "=f"(d[62]), "=f"(d[63])
    : "r"(a[0]), "r"(a[1]), "r"(a[2]), "r"(a[3]), "l"(db), "r"(meta));
}
DEVI void mma_i2(float* d, const uint32_t* a, uint64_t db, uint32_t meta) {
  asm volatile("{\nwgmma.mma_async.sp.sync.aligned.m64n128k32.f32.f16.f16 {%0, %1, %2, %3, %4, %5, %6, %7, %8, %9, %10, %11, %12, %13, %14, %15, %16, %17, %18, %19, %20, %21, %22, %23, %24, %25, %26, %27, %28, %29, %30, %31, %32, %33, %34, %35, %36, %37, %38, %39, %40, %41, %42, %43, %44, %45, %46, %47, %48, %49, %50, %51, %52, %53, %54, %55, %56, %57, %58, %59, %60, %61, %62, %63}, {%64,%65,%66,%67}, %68, %69, 0, 1, 1, 1, 1;\n}\n"
    : "+f"(d[0]), "+f"(d[1]), "+f"(d[2]), "+f"(d[3]), "+f"(d[4]), "+f"(d[5]), "+f"(d[6]), "+f"(d[7]), "+f"(d[8]), "+f"(d[9]), "+f"(d[10]), "+f"(d[11]), "+f"(d[12]), "+f"(d[13]), "+f"(d[14]), "+f"(d[15]), "+f"(d[16]), "+f"(d[17]), "+f"(d[18]), "+f"(d[19]), "+f"(d[20]), "+f"(d[21]), "+f"(d[22]), "+f"(d[23]), "+f"(d[24]), "+f"(d[25]), "+f"(d[26]), "+f"(d[27]), "+f"(d[28]), "+f"(d[29]), "+f"(d[30]), "+f"(d[31]), "+f"(d[32]), "+f"(d[33]), "+f"(d[34]), "+f"(d[35]), "+f"(d[36]), "+f"(d[37]), "+f"(d[38]), "+f"(d[39]), "+f"(d[40]), "+f"(d[41]), "+f"(d[42]), "+f"(d[43]), "+f"(d[44]), "+f"(d[45]), "+f"(d[46]), "+f"(d[47]), "+f"(d[48]), "+f"(d[49]), "+f"(d[50]), "+f"(d[51]), "+f"(d[52]), "+f"(d[53]), "+f"(d[54]), "+f"(d[55]), "+f"(d[56]), "+f"(d[57]), "+f"(d[58]), "+f"(d[59]), "+f"(d[60]), "+f"(d[61]), "+f"(d[62]), "+f"(d[63])
    : "r"(a[0]), "r"(a[1]), "r"(a[2]), "r"(a[3]), "l"(db), "r"(meta));
}
__device__ const __align__(128) uint32_t d_tab[2944] = {
  0x3bf13bff,0x2fbd25e4,0x38ee3986,0x3a4d39c9,0x3b9a3bcf,0x34ff32f7,0x3737384a,0x3b243ac1,0x3af73b52,0x37dd3676,0x344b35c8,0x3bb53b76,
  0x3a113a8c,0x39373899,0x2cce3185,0x3bfa3be1,0x3a933bf2,0x388e2f59,0xb1b6b8f8,0xbbdfba45,0xa452374e,0x3c003b1e,0x39c034e7,0xb990bb9e,
  0xbabab7c8,0x38553afe,0x3bd23bb2,0x32c6b463,0xbb57bbf9,0xb65f2d33,0x35df3a19,0x3b71392e,0x37643bd4,0x3b183294,0xb4cf385f,0x3ba13ab3,
  0xbbaeb648,0x347b3b5c,0xbb04bb6c,0xb7b235f7,0xad97ba9b,0xbbf8b884,0x3924b1e8,0xba21bbdd,0x3bf439b8,0x2ef5b999,0x39023c00,0x3a3d217f,
  0x9cb63ba5,0x3c0034b7,0x39afb77a,0xb9a1bb13,0xb86abbab,0xbaac3493,0xb2633b0a,0x3bd7379b,0x3b60391b,0x3631ba29,0xb60ebbf7,0xbb682dfb,
  0xbbdaae91,0x32193bf5,0x3aa23a35,0x387ab90c,0xb7853b65,0x3b10361a,0xbba73625,0x34ab3b63,0x3911baa9,0xba31b86f,0x3bf6b24b,0xae5fbbd8,
  0xba2d39aa,0x391639a6,0xbbf61648,0xae2d3c00,0x3b0db874,0xb790baa5,0x3ba93232,0x349fbbd9,0xba9e3b16,0x387f376f,0x3bdcb4c3,0x3201bba3,
  0x3b6aaec3,0x3602bbf5,0xb63cb907,0xbb5e3a39,0xb27cba25,0xbbd6391f,0xb8653bf8,0x3ab02dc9,0xb99d3bac,0x39b33487,0x3c00b7a6,0x9fdbbb07,
  0xbbf33ab6,0x2f27385a,0xba4132ad,0xb8fd3bd3,0xad653994,0x3bf9b9bc,0xba1d3c00,0x3929a311,0x3bb0b889,0x346fba97,0x37bd31cf,0x3b01bbde,
  0x3759bb59,0xbb1b3654,0x3b9fbb6f,0xb4dbb5eb,0xbb733a49,0xb5d438f3,0x366baf8b,0x3b54bbf2,0xbbd03bfa,0x32de2d00,0x3abdb933,0x3850ba15,
  0xb98b3afb,0x39c5b7d2,0x3c00bbb3,0xa51bb457,0xb19e3742,0x3be0bb21,0x3a90bb9c,0xb89434f3,0xb93c39cd,0xba0d3982,0x2c9c26ad,0xbbfb3bff,
  0xb7e8389e,0xbaf43a89,0x343eb16c,0xbbb73be2,0xb50b3682,0xbb983b4f,0x372cb5bc,0xbb273b78,0xafef330f,0xbbf03bce,0x38eab845,0xba503ac4,
  0xb3403946,0xbbcb3a04,0xb83a2c38,0x3acbbbfc,0x3979b426,0xb9d63bba,0xbbff3aee,0x281fb7fe,0x3be4bb94,0x313b3523,0xb8a83b2c,0xba813715,
  0x3699ba58,0x3b4ab8e0,0x35a53029,0xbb7c3bef,0x340e38b2,0xbbbd3a7a,0x3ae8b109,0xb80a3be6,0x3b32bb45,0x36ff36af,0x353abb81,0x3b90b58d,
  0xb8d6b371,0x3a60bbc8,0xbbed3830,0x305bbad1,0xb94f3bfe,0xb9fca8e8,0x2ba739df,0xbbfc3970,0x39663815,0xb9e73ae1,0xbbfe33eb,0x29b1bbc0,
  0xb0d7bb37,0x3be8b6e8,0x3a733552,0xb8bc3b8b,0xb6c63beb,0xbb3fb08d,0xb576ba67,0x3b85b8cc,0x3ad8b9f4,0x38253958,0xb3a23bfd,0xbbc52ade,
  0x3b8736dd,0xb56a3b3a,0x3b3db55e,0x36d23b89,0xbbe9b3d3,0x30bebbc2,0xba6f381a,0xb8c1bade,0x3bfe2a7a,0x2a163bfd,0x3962b95d,0x39eb39f0,
  0xbbc330a6,0xb3babbea,0xb8203a6b,0xbadbb8c7,0x3bec3581,0x30743b83,0xb8d136bb,0xba64bb42,0xb6f438b7,0xbb35ba76,0xb546bbe7,0x3b8e30f0,
  0xb80fbbfe,0x3ae5a94d,0x3bbf396b,0xb40239e3,0x3bfd382a,0xab433ad5,0xb9f83389,0xb954bbc6,0x3a7e341a,0x38ad3bbc,0x3122b805,0x3be53aeb,
  0x39da3bfc,0xb974ac06,0x3bff3a00,0x2884394a,0xb8353042,0xbacebbee,0x33593a5c,0xbbc9b8db,0xbb7fbb92,0x3599b52f,0xbb47b70a,0xb6a4bb2f,
  0x37213153,0x3b2a3be3,0x351738a3,0xbb96ba85,0x3af1397d,0x37f339d2,0xb4322776,0xbbb8bbff,0x3bfb3bcc,0xac6a3328,0xba09b840,0xb941bac7,
  0x3a543b7a,0xb8e5b5b1,0xbbefbb4c,0xb010b68d,0x32f72fbd,0xbbcfbbf1,0x3ac13a4d,0xb84ab8ee,0x367634ff,0xbb52bb9a,0x3b763b24,0xb5c8b737,
  0x389937dd,0xba8cbaf7,0x3be13bb5,0xb185b44b,0x39c93937,0xb986ba11,0x3bff3bfa,0x25e4acce,0x392e32c6,0xba19bbd2,0xbbf9baba,0x2d333855,
  0x3bf23b71,0x2f59b5df,0xb8f8bb57,0xba45b65f,0x374e3a93,0x3b1e388e,0x34e7b1b6,0xbb9ebbdf,0xb7c8a452,0x3afe3c00,0x3bb239c0,0xb463b990,
  0x3b6c34cf,0xb5f7bba1,0x3b5c3b18,0x3648b764,0x31e83b04,0x3bdd37b2,0xb884347b,0x3a9b3bae,0xbc00b924,0xa17f3a21,0xb999bbf8,0xb9b82d97,
  0x3294b902,0xbbd4ba3d,0x3ab32ef5,0xb85fbbf4,0x3bf53631,0x2e91bb60,0xb90cbb68,0xba35360e,0xbb133219,0x377a3bda,0x3ba5387a,0x34b7baa2,
  0x379bb9a1,0xbb0ab9af,0xbbab9cb6,0x34933c00,0x2dfb3bd7,0x3bf73263,0x391bb86a,0xba29baac,0x3aa93785,0x386fbb10,0x324b3ba7,0x3bd8b4ab,
  0xb9aab911,0xb9a63a31,0x9648bbf6,0xbc002e5f,0x38743a2d,0x3aa5b916,0xb2323bf6,0x3bd92e2d,0xb625bb0d,0xbb633790,0x361abba9,0xbb65b49f,
  0x37a63865,0x3b07bab0,0x3487bbd6,0xbbac327c,0x376fbc00,0xbb161fdb,0xbba339b3,0x34c3399d,0xbbf5387f,0x2ec33a9e,0x3a393201,0x3907bbdc,
  0x391f3602,0x3a25bb6a,0x2dc9bb5e,0xbbf8363c,0x231138fd,0x3c00ba41,0xb9943bf3,0x39bcaf27,0x3bdeb929,0x31cfba1d,0x38892d65,0x3a97bbf9,
  0x35ebbb01,0xbb6f37bd,0x3b59bbb0,0xb654b46f,0xbab634db,0xb85a3b9f,0xb2adb759,0xbbd33b1b,0xb742398b,0x3b21b9c5,0x3b9cbc00,0xb4f3251b,
  0x2f8b319e,0x3bf2bbe0,0x38f3ba90,0xba493894,0x3933b66b,0x3a15bb54,0x2d00b5d4,0xbbfa3b73,0x3bb3babd,0x3457b850,0xb7d232de,0xbafb3bd0,
  0xba893a0d,0x389eb93c,0xbbe23bfb,0xb16c2c9c,0xbb4f3af4,0x3682b7e8,0xbb783bb7,0xb5bc343e,0xbbce3b98,0x330fb50b,0xbac43b27,0xb845372c,
  0xbbff3bf0,0x26adafef,0xb9cd3a50,0xb98238ea,0xbbef3a81,0x3029b8a8,0x3a58bbe4,0x38e0b13b,0xb9463b7c,0xba0435a5,0xac38b699,0x3bfcbb4a,
  0x34263340,0xbbba3bcb,0xbaee383a,0x37febacb,0x3b94b979,0xb52339d6,0xbb2c3bff,0xb715a81f,0xbb813ae8,0xb58db80a,0xb6af3bbd,0xbb45340e,
  0x3830353a,0xbad13b90,0x3bc8b6ff,0xb3713b32,0x39dfbbed,0x3970305b,0x28e8ba60,0x3bfeb8d6,0xba7a2ba7,0x38b2bbfc,0xbbe639fc,0xb109b94f,
  0xb9583b3f,0xb9f4b6c6,0xaadebb85,0x3bfdb576,0x3bc0b825,0x33eb3ad8,0xb8153bc5,0xbae1b3a2,0xbb8ba9b1,0x3552bbfe,0x3b37b966,0x36e839e7,
  0x38cc38bc,0xba673a73,0xbbeb30d7,0x308dbbe8,0xb3d33b87,0xbbc2b56a,0x381a3b3d,0xbade36d2,0x2a7abbe9,0x3bfd30be,0xb95dba6f,0x39f0b8c1,
  0x30a63bfe,0xbbea2a16,0x3a6b3962,0xb8c739eb,0xb55ebbc3,0x3b89b3ba,0xbb3ab820,0x36ddbadb,0x33893bbf,0xbbc6b402,0xbad5bae5,0x382ab80f,
  0xbb83b9f8,0x3581b954,0x3b422b43,0x36bb3bfd,0x3a76b074,0x38b73bec,0xb0f03a64,0xbbe7b8d1,0x294d3b35,0xbbfeb6f4,0xb9e3bb8e,0x396bb546,
  0x394a3be5,0xba00b122,0x3bfc3a7e,0xac0638ad,0xb8db2884,0xba5cbbff,0x304239da,0xbbeeb974,0xbb2fbbc9,0x370ab359,0xbb92b835,0xb52fbace,
  0x341ab6a4,0x3bbc3b47,0xb805bb7f,0x3aeb3599,0x3b7a3bfb,0xb5b1ac6a,0xbb4cba09,0xb68db941,0x38a33a54,0xba85b8e5,0xbbe3bbef,0x3153b010,
  0x27763517,0xbbffbb96,0xb9d2bb2a,0x397d3721,0xb840b432,0xbac7bbb8,0xb328b7f3,0x3bcc3af1,0x3be23bfb,0x316c2c9c,0x389e393c,0x3a893a0d,
  0x3b783bb7,0x35bc343e,0x368237e8,0x3b4f3af4,0x3ac43b27,0x3845372c,0x330f350b,0x3bce3b98,0x39cd3a50,0x398238ea,0x26ad2fef,0x3bff3bf0,
  0x39463b7c,0x3a0435a5,0x2c38b699,0xbbfcbb4a,0xb4263340,0x3bba3bcb,0x3aee383a,0xb7febacb,0xbb94b979,0x352339d6,0x3b2c3bff,0x3715a81f,
  0xba58bbe4,0xb8e0b13b,0x302938a8,0x3bef3a81,0x28e83a60,0x3bfe38d6,0xb970305b,0x39df3bed,0xbbe6b9fc,0xb109394f,0xb8b2bbfc,0xba7aaba7,
  0x358db80a,0xbb81bae8,0x3b45340e,0xb6afbbbd,0x3ad13b90,0x3830b53a,0x33713b32,0x3bc836ff,0xb8cc38bc,0x3a673a73,0x3beb30d7,0xb08dbbe8,
  0x2adebb85,0xbbfdb576,0xb9f436c6,0x39583b3f,0x38153bc5,0x3ae1b3a2,0x33ebbad8,0xbbc0b825,0xbb37b966,0xb6e839e7,0x35523bfe,0x3b8ba9b1,
  0xbbc2356a,0x33d33b87,0xbadeb6d2,0xb81a3b3d,0x3bfdb0be,0xaa7abbe9,0x39f038c1,0x395dba6f,0xbbeaaa16,0xb0a63bfe,0xb8c7b9eb,0xba6b3962,
  0x3b8933ba,0x355ebbc3,0x36dd3adb,0x3b3ab820,0xbb422b43,0xb6bb3bfd,0x35813954,0x3b83b9f8,0x30f03a64,0x3be7b8d1,0x38b7bbec,0xba76b074,
  0x39e3bb8e,0xb96bb546,0xbbfe36f4,0xa94d3b35,0xbbc63402,0xb3893bbf,0x382a380f,0x3ad5bae5,0xb70ab359,0xbb2f3bc9,0x352fbace,0xbb923835,
  0xbbbc3b47,0x341a36a4,0xbaeb3599,0xb8053b7f,0x2c0638ad,0x3bfcba7e,0xb94a3be5,0x3a00b122,0x3beeb974,0x3042b9da,0x38db2884,0x3a5cbbff,
  0x3328b7f3,0xbbcc3af1,0xbac73bb8,0x3840b432,0xb5b12c6a,0xbb7a3bfb,0xb68d3941,0x3b4cba09,0xba8538e5,0xb8a33a54,0x31533010,0x3be3bbef,
  0xbbff3b96,0xa7763517,0x397db721,0x39d2bb2a,0x3a4db9c9,0xb8ee3986,0x3bf1bbff,0x2fbda5e4,0x3b24bac1,0xb737384a,0x3b9abbcf,0x34ffb2f7,
  0x3bb5bb76,0xb44b35c8,0x3af7bb52,0x37ddb676,0x3bfabbe1,0xacce3185,0x3a11ba8c,0x3937b899,0x3c00bb1e,0x2452374e,0xb9903b9e,0xb9c034e7,
  0x3855bafe,0x3abab7c8,0x32c63463,0xbbd23bb2,0xb65fad33,0x3b57bbf9,0x3b71b92e,0xb5df3a19,0xbbdf3a45,0x31b6b8f8,0x3a93bbf2,0x388eaf59,
  0x3a21bbdd,0x392431e8,0x2d97ba9b,0x3bf8b884,0xba3d217f,0x3902bc00,0xbbf439b8,0xaef5b999,0xb7643bd4,0xbb183294,0x34cf385f,0xbba13ab3,
  0x3baeb648,0xb47b3b5c,0x3b04bb6c,0x37b235f7,0x3219bbf5,0x3bdaae91,0x387a390c,0xbaa23a35,0xb9a13b13,0xb9afb77a,0x9cb6bba5,0x3c00b4b7,
  0x3bd7b79b,0x32633b0a,0xb86a3bab,0xbaacb493,0xbb68adfb,0x360ebbf7,0x3b60b91b,0x36313a29,0xb785bb65,0x3b10b61a,0xbba7b625,0x34abbb63,
  0x39113aa9,0xba31386f,0x3bf6324b,0xae5f3bd8,0xba2db9aa,0x3916b9a6,0xbbf69648,0xae2dbc00,0x3b0d3874,0xb7903aa5,0x3ba9b232,0x349f3bd9,
  0xbb5eba39,0x363cb907,0x3b6a2ec3,0x36023bf5,0x3ab0adc9,0x38653bf8,0xb27c3a25,0xbbd6b91f,0x9fdb3b07,0xbc00b7a6,0xb99dbbac,0x39b3b487,
  0xba9ebb16,0x387fb76f,0x3bdc34c3,0x32013ba3,0xbbb0b889,0xb46fba97,0xb7bd31cf,0xbb01bbde,0xb759bb59,0x3b1b3654,0xbb9fbb6f,0x34dbb5eb,
  0x3a4132ad,0x38fd3bd3,0x2f27b85a,0x3bf33ab6,0x3a1d3c00,0xb929a311,0x3bf939bc,0x2d653994,0xb894b4f3,0xba90bb9c,0xb19eb742,0x3be03b21,
  0xbb73ba49,0xb5d4b8f3,0x366b2f8b,0x3b543bf2,0xbbd0bbfa,0x32dead00,0x3abd3933,0x38503a15,0xb98bbafb,0x39c537d2,0x3c003bb3,0xa51b3457,
  0xb43eb16c,0x3bb73be2,0xbaf4ba89,0x37e8389e,0xb72cb5bc,0x3b273b78,0xbb98bb4f,0x350b3682,0xb8eab845,0x3a503ac4,0xbbf0bbce,0x2fef330f,
  0xba0db982,0x393c39cd,0xbbfbbbff,0xac9c26ad,0xba81b715,0x38a83b2c,0x3be43b94,0x313bb523,0xbb7cbbef,0xb5a53029,0x36993a58,0x3b4a38e0,
  0xb340b946,0xbbcbba04,0xb83aac38,0x3acb3bfc,0x39793426,0xb9d6bbba,0xbbffbaee,0x281f37fe,0xbbfcb970,0xaba739df,0xb94fbbfe,0xb9fc28e8,
  0x340eb8b2,0xbbbdba7a,0x3ae83109,0xb80abbe6,0x3b323b45,0x36ffb6af,0x353a3b81,0x3b90358d,0xb8d63371,0x3a603bc8,0xbbedb830,0x305b3ad1,
  0xb9e7bae1,0xb9663815,0x29b13bc0,0x3bfe33eb,0x3be836e8,0x30d7bb37,0xb8bcbb8b,0xba733552,0xbb3f308d,0x36c63beb,0x3b8538cc,0x3576ba67,
  0x3825b958,0xbad8b9f4,0xbbc5aade,0x33a23bfd,0xb0bebbc2,0xbbe933d3,0x38c1bade,0xba6fb81a,0xaa163bfd,0x3bfeaa7a,0xb9eb39f0,0x3962395d,
  0x33babbea,0xbbc3b0a6,0x3adbb8c7,0xb820ba6b,0xb6d23b89,0x3b3d355e,0xbb8736dd,0x356a3b3a,0x380fbbfe,0xbae5a94d,0xbbbf396b,0x340239e3,
  0xbbfd382a,0x2b433ad5,0x39f83389,0x3954bbc6,0x38d136bb,0x3a64bb42,0x3074bb83,0xbbec3581,0x3546bbe7,0xbb8e30f0,0xbb353a76,0x36f438b7,
  0x3b7fbb92,0xb599b52f,0x3b47b70a,0x36a4bb2f,0xb122b805,0xbbe53aeb,0x38adbbbc,0xba7e341a,0xbbff3a00,0xa884394a,0xb9742c06,0xb9da3bfc,
  0xb3593a5c,0x3bc9b8db,0xbace3bee,0x38353042,0x3b96ba85,0x3517b8a3,0xb7213153,0xbb2a3be3,0x3bb8bbff,0xb432a776,0xbaf1397d,0xb7f339d2,
  0x3941bac7,0xba093840,0xbbfb3bcc,0x2c6a3328,0x3010b68d,0xbbef3b4c,0xba543b7a,0x38e5b5b1,0x384ab8ee,0x3ac1ba4d,0xb2f72fbd,0x3bcfbbf1,
  0x35c8b737,0x3b76bb24,0xb67634ff,0x3b52bb9a,0x3185b44b,0x3be1bbb5,0xb89937dd,0x3a8cbaf7,0xa5e4acce,0x3bffbbfa,0xb9c93937,0x3986ba11,
  0xaf59b5df,0x3bf2bb71,0x3a45b65f,0xb8f83b57,0xbb1e388e,0x374eba93,0x3b9ebbdf,0x34e731b6,0xbafe3c00,0xb7c82452,0x3463b990,0x3bb2b9c0,
  0xad333855,0xbbf93aba,0xb92e32c6,0x3a19bbd2,0xb9b8ad97,0x3999bbf8,0xbc003924,0xa17fba21,0xb85f3bf4,0xbab32ef5,0x32943902,0xbbd43a3d,
  0x3b6cb4cf,0xb5f73ba1,0x3b5cbb18,0x36483764,0x31e8bb04,0x3bddb7b2,0xb884b47b,0x3a9bbbae,0xbbf73263,0x2dfbbbd7,0x3a29baac,0x391b386a,
  0x3a35360e,0xb90c3b68,0xbbf53631,0xae91bb60,0xb4b7baa2,0x3ba5b87a,0x3b133219,0xb77a3bda,0xb4933c00,0xbbab1cb6,0xb79bb9a1,0x3b0ab9af,
  0xbaa93785,0xb86fbb10,0xb24b3ba7,0xbbd8b4ab,0x39aab911,0x39a63a31,0x1648bbf6,0x3c002e5f,0xb8743a2d,0xbaa5b916,0x32323bf6,0xbbd92e2d,
  0x3625bb0d,0x3b633790,0xb61abba9,0x3b65b49f,0xb4c3399d,0xbba3b9b3,0xb76fbc00,0x3b161fdb,0xb907bbdc,0x3a39b201,0x3bf5387f,0xaec33a9e,
  0x3bf8363c,0x2dc93b5e,0xb91f3602,0xba25bb6a,0xb7a63865,0xbb07bab0,0xb487bbd6,0x3bac327c,0x35eb3b01,0xbb6fb7bd,0x3b593bb0,0xb654346f,
  0xbab6b4db,0xb85abb9f,0xb2ad3759,0xbbd3bb1b,0xb994bbf3,0x39bc2f27,0xbc00ba41,0x2311b8fd,0x3889ad65,0x3a973bf9,0xb1cfba1d,0x3bde3929,
  0x3afb3bd0,0xb7d2b2de,0xbbb3babd,0xb457b850,0x3742398b,0xbb21b9c5,0xbb9cbc00,0x34f3251b,0xaf8b319e,0xbbf2bbe0,0xb8f3ba90,0x3a493894,
  0xb933b66b,0xba15bb54,0xad00b5d4,0x3bfa3b73,0x211b21e4,0xa51ba5e4,0x98b69248,0x1cb61648,0x1f122052,0xa311a452,0x9d7f9bdb,0x217f1fdb,
  0x1bdb1d7f,0x9fdba17f,0xa0529f12,0x24522311,0x124818b6,0x96489cb6,0xa1e4a11b,0x25e4251b,0x2a632b5f,0xae5faf59,0xa1e49bdb,0x25e41fdb,
  0x286b2967,0xac6aad65,0xa6e0a4e9,0x2ade28e8,0x24e926e0,0xa8e8aade,0xa967a86b,0x2d652c6a,0x1bdb21e4,0x9fdba5e4,0xab5faa63,0x2f592e5f,
  0x2dc22ea7,0xb1b6b294,0xa54d9f12,0x294d2311,0x2bf62cde,0xafefb0d7,0xaa31a86b,0x2e2d2c6a,0x286b2a31,0xac6aae2d,0xacdeabf6,0x30d72fef,
  0x1f12254d,0xa311a94d,0xaea7adc2,0x329431b6,0x302c30d2,0xb41ab4b7,0xa7a9a11b,0x2ba7251b,0x2dc22f0c,0xb1b6b2f7,0xac79aa63,0x30742e5f,
  0x2a632c79,0xae5fb074,0xaf0cadc2,0x32f731b6,0x211b27a9,0xa51baba7,0xb0d2b02c,0x34b7341a,0x317a3257,0xb552b61a,0xa902a2ad,0x2d0026ad,
  0x2f8c309f,0xb371b487,0xaddcac2e,0x31cf3029,0x2c2e2ddc,0xb029b1cf,0xb09faf8c,0x34873371,0x22ad2902,0xa6adad00,0xb257b17a,0x361a3552,
  0x32cd33e3,0xb682b76f,0xaa31a420,0x2e2d281f,0x30ac31bb,0xb493b58d,0xaf3fad2a,0x33283122,0x2d2a2f3f,0xb122b328,0xb1bbb0ac,0x358d3493,
  0x24202a31,0xa81fae2d,0xb3e3b2cd,0x376f3682,0x341334bc,0xb7a6b85a,0xab5fa4e9,0x2f5928e8,0x319432da,0xb56ab68d,0xb052ae28,0x343e3219,
  0x2e283052,0xb219b43e,0xb2dab194,0x368d356a,0x24e92b5f,0xa8e8af59,0xb4bcb413,0x385a37a6,0x34c3358c,0xb85fb8f3,0xac47a5b2,0x304229b1,
  0x327e33fd,0xb63cb785,0xb106af26,0x34e7330f,0x2f263106,0xb30fb4e7,0xb3fdb27e,0x3785363c,0x25b22c47,0xa9b1b042,0xb58cb4c3,0x38f3385f,
  0x35773662,0xb8e5b982,0xacdea67b,0x30d72a7a,0x336b3493,0xb70ab83a,0xb1bbb012,0x358d3402,0x301231bb,0xb402b58d,0xb493b36b,0x383a370a,
  0x267b2cde,0xaa7ab0d7,0xb662b577,0x398238e5,0x36303741,0xb962ba04,0xad76a744,0x316c2b43,0x342e352a,0xb7d2b8ad,0xb271b092,0x3631347b,
  0x30923271,0xb47bb631,0xb52ab42e,0x38ad37d2,0x27442d76,0xab43b16c,0xb741b630,0x3a043962,0x36ee3815,0xb9d6ba7a,0xae0ea807,0x32012c06,
  0x34a735c4,0xb84ab91b,0xb329b113,0x36d234f3,0x31133329,0xb4f3b6d2,0xb5c4b4a7,0x391b384a,0x28072e0e,0xac06b201,0xb815b6ee,0x3a7a39d6,
  0x37b4388e,0xba41bae1,0xaea7a86b,0x32942c6a,0x35233662,0xb8a8b982,0xb3e3b194,0x376f356a,0x319433e3,0xb56ab76f,0xb662b523,0x398238a8,
  0x286b2ea7,0xac6ab294,0xb88eb7b4,0x3ae13a41,0x3841390f,0xbaa2bb3a,0xaf3fa8d0,0x33282cce,0x35a13705,0xb902b9e3,0xb44fb216,0x380535df,
  0x3216344f,0xb5dfb805,0xb705b5a1,0x39e33902,0x28d02f3f,0xacceb328,0xb90fb841,0x3b3a3aa2,0x38ac3997,0xbaf7bb83,0xafd8a935,0x33ba2d33,
  0x362137ac,0xb958ba3d,0xb4aeb298,0x38503654,0x329834ae,0xb654b850,0xb7acb621,0x3a3d3958,0x29352fd8,0xad33b3ba,0xb997b8ac,0x3b833af7,
  0x391c3a28,0xbb42bbbc,0xb039a999,0x34262d97,0x36a4382d,0xb9aaba90,0xb50eb31c,0x389936c6,0x331c350e,0xb6c6b899,0xb82db6a4,0x3a9039aa,
  0x29993039,0xad97b426,0xba28b91c,0x3bbc3b42,0x39923ac3,0xbb81bbe3,0xb085a9fe,0x346f2dfb,0x372a3886,0xb9f8badb,0xb570b3a0,0x38e03737,
  0x33a03570,0xb737b8e0,0xb886b72a,0x3adb39f8,0x29fe3085,0xadfbb46f,0xbac3b992,0x3be33b81,0xb9cfbb16,0x3b9c3bf1,0x30ac2a31,0xb493ae2d,
  0xb76fb8b4,0x3a1d3afe,0x35a133e3,0xb902b76f,0xb3e3b5a1,0x376f3902,0x38b4376f,0xbafeba1d,0xaa31b0ac,0x2e2d3493,0x3b1639cf,0xbbf1bb9c,
  0xb956ba74,0x3b633bd2,0x305f29cc,0xb44badc9,0xb6e7b859,0x39d23ab6,0x353f335e,0xb8bcb6ff,0xb35eb53f,0x36ff38bc,0x385936e7,0xbab6b9d2,
  0xa9ccb05f,0x2dc9344b,0x3a743956,0xbbd2bb63,0xb8e3b9de,0x3b1e3ba1,0x30122967,0xb402ad65,0xb662b801,0x39823a67,0x34de32da,0xb874b68d,
  0xb2dab4de,0x368d3874,0x38013662,0xba67b982,0xa967b012,0x2d653402,0x39de38e3,0xbba1bb1e,0xb876b952,0x3ace3b60,0x2f8c2902,0xb371ad00,
  0xb5e1b758,0x392e3a11,0x347e3257,0xb82ab61a,0xb257b47e,0x361a382a,0x375835e1,0xba11b92e,0xa902af8c,0x2d003371,0x39523876,0xbb60bace,
  0xb80db8ce,0x3a733b10,0x2ef3289e,0xb2deac9c,0xb562b6b3,0x38d639b3,0x342031d5,0xb7bdb5a5,0xb1d5b420,0x35a537bd,0x36b33562,0xb9b3b8d6,
  0xa89eaef3,0x2c9c32de,0x38ce380d,0xbb10ba73,0xb750b851,0x3a0d3ab0,0x2e5a2839,0xb24bac38,0xb4e5b613,0x387a394f,0x33863153,0xb721b52f,
  0xb153b386,0x352f3721,0x361334e5,0xb94fb87a,0xa839ae5a,0x2c38324b,0x38513750,0xbab0ba0d,0xb68eb7b4,0x399d3a41,0x2dc227a9,0xb1b6aba7,
  0xb46ab577,0x381a38e5,0x32cd30d2,0xb682b4b7,0xb0d2b2cd,0x34b73682,0x3577346a,0xb8e5b81a,0xa7a9adc2,0x2ba731b6,0x37b4368e,0xba41b99d,
  0xb5d2b6d1,0x392439c5,0x2d2a26e0,0xb122aade,0xb3e3b4de,0x376f3874,0x32163052,0xb5dfb43e,0xb052b216,0x343e35df,0x34de33e3,0xb874b76f,
  0xa6e0ad2a,0x2ade3122,0x36d135d2,0xb9c5b924,0xb51cb5f6,0x38a3393c,0x2c932617,0xb08daa16,0xb2f4b448,0x36a437fe,0x31602fa5,0xb53ab389,
  0xafa5b160,0x3389353a,0x344832f4,0xb7feb6a4,0xa617ac93,0x2a16308d,0x35f6351c,0xb93cb8a3,0xb46ab523,0x381a38a8,0x2bf6254d,0xafefa94d,
  0xb209b36b,0x35d4370a,0x30ac2ea7,0xb493b294,0xaea7b0ac,0x32943493,0x336b3209,0xb70ab5d4,0xa54dabf6,0x294d2fef,0x3523346a,0xb8a8b81a,
  0xb378b456,0x3715380a,0x2ac82484,0xaec3a884,0xb120b24a,0x34ff360e,0x2ff22da9,0xb3d3b19e,0xada9aff2,0x319e33d3,0x324a3120,0xb60eb4ff,
  0xa484aac8,0x28842ec3,0x34563378,0xb80ab715,0xb223b31c,0x35eb36c6,0x29992376,0xad97a776,0xb039b12d,0x3426350b,0x2e8d2cac,0xb27cb0a6,
  0xacacae8d,0x30a6327c,0x312d3039,0xb50bb426,0xa376a999,0x27762d97,0x331c3223,0xb6c6b5eb,0xb0d2b194,0x34b7356a,0x286b21e4,0xac6aa5e4,
  0xaea7b012,0x32943402,0x2d2a2b5f,0xb122af59,0xab5fad2a,0x2f593122,0x30122ea7,0xb402b294,0xa1e4a86b,0x25e42c6a,0x319430d2,0xb56ab4b7,
  0xaf0cb012,0x32f73402,0x267b2052,0xaa7aa452,0xacdeadf5,0x30d731e8,0x2b912967,0xaf8bad65,0xa967ab91,0x2d652f8b,0x2df52cde,0xb1e8b0d7,
  0xa052a67b,0x24522a7a,0x30122f0c,0xb402b2f7,0xac79ad2a,0x30743122,0x24201d7f,0xa81fa17f,0xaa31ab91,0x2e2d2f8b,0x28d026e0,0xacceaade,
  0xa6e0a8d0,0x2ade2cce,0x2b912a31,0xaf8bae2d,0x9d7fa420,0x217f281f,0x2d2a2c79,0xb122b074,0xa7a9a86b,0x2ba72c6a,0x1f1218b6,0xa3119cb6,
  0xa54da67b,0x294d2a7a,0x242021e4,0xa81fa5e4,0xa1e4a420,0x25e4281f,0x267b254d,0xaa7aa94d,0x98b69f12,0x1cb62311,0x286b27a9,0xac6aaba7,
  0xa5e43bff,0xb61a3b65,0xb98239cd,0xbb3a36dd,0xaf593bf2,0xb76f3b16,0xba043946,0xbb833581,0xb2943bd4,0xb85a3ab6,0xba7a38b2,0xbbbc341a,
  0xb4b73ba5,0xb8f33a49,0xbae13815,0xbbe33153,0xac9c3bfb,0xbb87356a,0xb986b9c9,0x361abb65,0xb5a53b7c,0xbbfd2b43,0xb74ebb1e,0x3907ba39,
  0xb8d63a60,0xbbc9b359,0xb1e8bbdd,0x3a97b889,0xba7338bc,0xbaf1b7f3,0x2e91bbf5,0x3b9cb4f3,0xafbd3bf1,0xbb10b785,0x3a0db93c,0x356a3b87,
  0xb88e3a93,0xb87fba9e,0x3bcbb340,0xb0743bec,0xbb183764,0xaf27bbf3,0x3bbd340e,0xb8ad3a7e,0xbc009cb6,0x35d4bb73,0x39e73966,0xbb2a3721,
  0xb16c3be2,0xb3d3bbc2,0x38ee3a4d,0xbb10b785,0xba043946,0x36bbbb42,0xa4523c00,0xb63cbb5e,0xbbfe28e8,0x3b2fb70a,0xb9243a21,0x346fbbb0,
  0xba67b8cc,0x3bcc3328,0xbbda3219,0x3a90b894,0xb2f73bcf,0x386fbaa9,0xba89389e,0x3bc2b3d3,0xbb1e374e,0x3bf5aec3,0xbbbab426,0x3a7638b7,
  0xbb5cb648,0x39bc3994,0xb6afbb45,0x2c063bfc,0xb493bbab,0xad003bfa,0x36e8bb37,0xb9d2397d,0xb43e3bb7,0x3be9b0be,0xb84abac1,0xb86f3aa9,
  0xbbcb3340,0x38d13a64,0x37c8bafe,0xbbf8adc9,0xb94fb9fc,0xb6a43b47,0x3c00217f,0xb654bb59,0x3576bb85,0xbbfb2c6a,0x377a3b13,0x38f3ba49,
  0xb4ff3b9a,0x3a313911,0x3af4b7e8,0xb0bebbe9,0xbc00a452,0xb6023b6a,0x39d63979,0x3b35b6f4,0xb47bbbae,0xbbf9ad65,0xb6ff3b32,0x397439da,
  0x3aacb86a,0xb2debbd0,0xbbe8b0d7,0xb7f33af1,0xb5bc3b78,0x2a7a3bfd,0x37373b24,0x3a313911,0xbbbab426,0xbbe730f0,0xbaba3855,0xb8653ab0,
  0x3109bbe6,0xb41abbbc,0xb902ba3d,0xbb1bb759,0x3bfd2ade,0x3b7ab5b1,0x39afb9a1,0x35d4bb73,0xb6763b52,0xb9a639aa,0xbb4f3682,0xbbfd2a7a,
  0xbafeb7c8,0xb91fba25,0xb523bb94,0x294dbbfe,0x3884ba9b,0x3a97b889,0x3bc8b371,0x3bee3042,0x3a29391b,0x37d23afb,0x308d3beb,0xb3283bcc,
  0xb72c3b27,0xbbfeaa16,0xb5c8bb76,0x39a6b9aa,0xb9d6b979,0x3546bb8e,0x3bf9ad33,0x37a63b07,0x3ae8b80a,0x3a7e38ad,0xb2943bd4,0xbbd332ad,
  0x33a23bc5,0xba5438e5,0xbb0ab79b,0x2d00bbfa,0xb7dd3af7,0xb916ba2d,0x3b98b50b,0xaa163bfe,0xb855baba,0x3bd6b27c,0xb13b3be4,0xbae5b80f,
  0x3bf8ad97,0xb46f3bb0,0xba60b8d6,0x3aceb835,0xb6313b60,0xb9c5b98b,0x3b3fb6c6,0x2c6a3bfb,0xb8453ac4,0x30a6bbea,0x344b3bb5,0xb916ba2d,
  0xb523bb94,0x396b39e3,0xbb57b65f,0x3c009fdb,0x3b81358d,0xbbfc2c06,0x3b18b764,0xb8fd3a41,0xbae13815,0x38a3ba85,0xb2633bd7,0xb2debbd0,
  0xb8993a8c,0x3aa5b874,0xbbce330f,0x3bea30a6,0xad33bbf9,0xb4873bac,0x38e0ba58,0xbad5382a,0x399939b8,0xb654bb59,0x28e83bfe,0x352fbb92,
  0xbbf5ae91,0x3b213742,0xb958b9f4,0x35b13b7a,0xb8ea3a50,0x3bc333ba,0xb185bbe1,0xbaa53874,0x313bbbe4,0xbbbf3402,0x38f83a45,0x376fbb16,
  0x353a3b90,0x39dab974,0xbb5cb648,0x23113c00,0xb9e7b966,0xb5173b96,0x3bf7adfb,0xb7d2bafb,0xb9373a11,0x37903b0d,0x3bf0afef,0x33babbc3,
  0x365fbb57,0xb9b3b99d,0xbb4a3699,0x2b433bfd,0xaef53bf4,0x3b1b3759,0x39fcb94f,0xb599bb7f,0xb219bbda,0xbbe0b19e,0xb8253ad8,0x38e53a54,
  0xb98239cd,0xb55e3b89,0x2cce3bfa,0x37903b0d,0x38e0ba58,0x3389bbc6,0xb1b6bbdf,0xb87fba9e,0xb8303ad1,0xb0423bee,0x347b3bae,0x39293a1d,
  0x36e8bb37,0x2776bbff,0xb60ebb68,0xb9c5b98b,0xb9c93986,0xbb633625,0xbbff26ad,0xbb89b55e,0x3a45b8f8,0x3ba3b4c3,0x3bfc2c38,0x3b4236bb,
  0xbab3385f,0xbbd332ad,0xbbe6b109,0xbaebb805,0x3b13b77a,0x3bf2af8b,0x3bc033eb,0x3a8538a3,0xba0d393c,0xbb3db6d2,0x25e4bbff,0x3b63b625,
  0x3b4ab699,0x39f83954,0xb4e73b9e,0xbbf52ec3,0xbbed305b,0xb835bace,0x3884ba9b,0x3bde31cf,0x3be830d7,0x34323bb8,0xba35390c,0xbb21b742,
  0xba4d38ee,0xb4abbba7,0x3bfb2c9c,0xb6d23b3d,0x3bdfb1b6,0xb2013bdc,0xbacbb83a,0x3a64b8d1,0xbba1b4cf,0x38fdba41,0x380a3ae8,0xbbe53122,
  0x39a139af,0xbb54366b,0xa9b1bbfe,0x3b963517,0xba89389e,0x381abade,0xafbd3bf1,0xb4abbba7,0x3bfc2c38,0xbb833581,0x39c0b990,0xb6023b6a,
  0xb9dfb970,0x3b92352f,0xbbf82d97,0x3b01b7bd,0x308d3beb,0xb840bac7,0x3aa2387a,0xbbe0b19e,0xbac1384a,0x3bd8b24b,0xbbe2b16c,0x3ade381a,
  0x3b9e34e7,0xba39b907,0x37fe3aee,0xb0f0bbe7,0xb5f7bb6c,0x23113c00,0x358dbb81,0xb94a3a00,0xb79b3b0a,0x3a15b933,0xbb8b3552,0x3bff2776,
  0xbaf437e8,0x3a6f38c1,0x32f7bbcf,0xbbd8324b,0x3acb383a,0x3074bbec,0xbbb23463,0x391f3a25,0x2ba7bbfc,0xbb7f3599,0x399939b8,0x35ebbb6f,
  0xbb3f36c6,0x3a093941,0x34b7bba5,0xbbf22f8b,0xbb243737,0x2e5f3bf6,0x3bb7343e,0x38c1ba6f,0x399039c0,0x3b5eb63c,0xa81fbbff,0xbb8eb546,
  0x37b2bb04,0xb929ba1d,0xbb90353a,0xa8843bff,0xbbd7b263,0xb8503abd,0x38bc3a73,0x3bb8b432,0xbb4f3682,0xb95d39f0,0xb4ff3b9a,0x2e5f3bf6,
  0x37fe3aee,0x3a7638b7,0x3bd232c6,0x3bd6b27c,0x3a7ab8b2,0x3805baeb,0x2ef5bbf4,0xb4dbbb9f,0xb958b9f4,0xbb4cb68d,0xbc009cb6,0xbb54366b,
  0xbb7635c8,0xbc001648,0xbb78b5bc,0xb9f0b95d,0x34633bb2,0xadc93bf8,0xb7153b2c,0xb9e3396b,0x3bddb1e8,0x3bde31cf,0x3ad13830,0x38db3a5c,
  0xadfbbbf7,0x3457bbb3,0x38ccba67,0x3ac7b840,0xbb98350b,0xb962b9eb,0x3676bb52,0x3c009648,0x281f3bff,0xbb3536f4,0xba19b92e,0x3487bbac,
  0x3bbd340e,0x31223be5,0xbab3385f,0xbab6b85a,0x3825bad8,0x3bef3010,0x34933bab,0xba153933,0xbbb5344b,0x2e2dbbf6,0x3b27372c,0xb9eb3962,
  0xb2c63bd2,0xbab0b865,0x3a81b8a8,0x34023bbf,0x3a213924,0xbb0137bd,0xb05bbbed,0x3bc93359,0x3b68b60e,0x251b3c00,0xbb85b576,0x3941ba09,
  0xbbce330f,0x3a6bb8c7,0xb7dd3af7,0x2e2dbbf6,0xb7153b2c,0x294dbbfe,0x35df3b71,0xb9b3b99d,0x36af3b45,0xba00b94a,0x3ba134cf,0xbbf32f27,
  0x3bc033eb,0xbbe33153,0x3aacb86a,0xb8503abd,0xbbe13185,0x3bd93232,0xbac4b845,0x38c73a6b,0xb92e3a19,0x3b07b7a6,0xbbef3029,0x3bc63389,
  0xa17f3c00,0x35ebbb6f,0xb97039df,0x3b2fb70a,0x390c3a35,0xb4f3bb9c,0xaade3bfd,0x368dbb4c,0xbbf02fef,0x38203adb,0x3899ba8c,0xbbd9b232,
  0xba8138a8,0x3ae5380f,0x2f59bbf2,0xbba334c3,0xb6ff3b32,0x3bff2884,0xb5f7bb6c,0xb99439bc,0x29b13bfe,0x3b2ab721,0xba29b91b,0xb4573bb3,
  0xbbfa2cce,0xb49f3ba9,0x3a5038ea,0x3adbb820,0xbb7135df,0x1fdb3c00,0x3b7c35a5,0x3954b9f8,0xba3d3902,0x34db3b9f,0x3bfc2ba7,0x36a4bb47,
  0xb87a3aa2,0x38943a90,0x3bc5b3a2,0x3010bbef,0xbbff26ad,0xbb3a36dd,0xb9373a11,0xb49f3ba9,0xbbef3029,0xbad5382a,0xb88e3a93,0xb2013bdc,
  0xbbc83371,0xba5c38db,0xb7b23b04,0xad653bf9,0xbb8b3552,0xb9d2397d,0xb6313b60,0x251b3c00,0x3bf12fbd,0x3b103785,0x393c3a0d,0x356a3b87,
  0x3bd232c6,0x3ab03865,0x38a83a81,0x34023bbf,0x3ba134cf,0x3a4138fd,0x380a3ae8,0x31223be5,0x3b603631,0x39c5398b,0x36c63b3f,0x2c6a3bfb,
  0xbbe2b16c,0xb3d3bbc2,0x3a4db8ee,0x3b103785,0xbb2cb715,0x294dbbfe,0x3b71b5df,0x39b3399d,0xb9dfb970,0x352fbb92,0x3bf8ad97,0x37bd3b01,
  0xb815bae1,0x38a3ba85,0x3bd73263,0x32de3bd0,0x3bcf32f7,0xb86f3aa9,0xb89eba89,0x3bc2b3d3,0x3a19392e,0xbb0737a6,0xb029bbef,0x3bc63389,
  0x35f73b6c,0xbc002311,0x358dbb81,0x3a00394a,0xae913bf5,0xbb21b742,0x39f4b958,0x35b13b7a,0xbbb7b43e,0x3be9b0be,0xbac1384a,0x386fbaa9,
  0xb8a8ba81,0x3ae5380f,0xbbf2af59,0x3ba3b4c3,0x2ba7bbfc,0x35993b7f,0xb999b9b8,0x3b6f35eb,0x3966b9e7,0xb5173b96,0xadfbbbf7,0x37d23afb,
  0x3b9a34ff,0xba31b911,0x37e83af4,0xb0bebbe9,0x35df3b71,0x9fdbbc00,0xb5a53b7c,0x3954b9f8,0xb7b23b04,0x3a1db929,0xbb90353a,0x3bff2884,
  0xbbda3219,0x3be0319e,0xbad8b825,0x38e53a54,0xbb78b5bc,0x2a7a3bfd,0x3b24b737,0xba31b911,0xb029bbef,0xbad5382a,0x3a93388e,0x3201bbdc,
  0x3a7ab8b2,0xbaebb805,0xaef53bf4,0x3b9fb4db,0x3b3736e8,0x2776bbff,0xbb68360e,0x39c5398b,0x3b523676,0x39a6b9aa,0xb682bb4f,0xbbfd2a7a,
  0xaf593bf2,0x3b16376f,0x3a04b946,0xb581bb83,0xbbdd31e8,0xb1cf3bde,0x3ad13830,0x3a5cb8db,0xb77abb13,0xbbf22f8b,0xb3eb3bc0,0x3a8538a3,
  0xbb27b72c,0xbbfeaa16,0xbb7635c8,0xb9a639aa,0x35a5bb7c,0xab43bbfd,0xb74ebb1e,0xba39b907,0x3bbd340e,0x3be5b122,0x3ab3b85f,0x385abab6,
  0xb0d73be8,0x34323bb8,0x390c3a35,0x3b213742,0x3af737dd,0x39163a2d,0x350b3b98,0xaa163bfe,0xb88e3a93,0xba9e387f,0xbbcb3340,0xbbecb074,
  0xba21b924,0xb7bdbb01,0xb05bbbed,0x3359bbc9,0x39afb9a1,0x3b54b66b,0x3bfea9b1,0x3b963517,0xbac4b845,0x30a6bbea,0x3bb5b44b,0x39163a2d,
  0x3a04b946,0x3b4236bb,0xa4523c00,0xbb5e363c,0x36af3b45,0xb94a3a00,0xbba1b4cf,0xaf27bbf3,0xbbeb308d,0xb840bac7,0x387abaa2,0x3be0319e,
  0x3a8c3899,0xbaa53874,0xb30fbbce,0x3bea30a6,0xbb1e374e,0xaec3bbf5,0x3bba3426,0xb8b73a76,0x217fbc00,0x3b6f35eb,0xb97039df,0xb70abb2f,
  0x3b0a379b,0xba153933,0xb552bb8b,0x3bff2776,0xba50b8ea,0x3bc333ba,0xbbe13185,0x3aa5b874,0x3bcbb340,0xba6438d1,0x37c8bafe,0xadc93bf8,
  0xb6ff3b32,0x2884bbff,0x35f73b6c,0xb9bcb994,0xb6c6bb3f,0x3a093941,0xbba5b4b7,0x3bf2af8b,0x3a113937,0xb790bb0d,0x2fef3bf0,0x33babbc3,
  0xbc00a452,0x3b6a3602,0xb9d6b979,0x36f43b35,0x3a3db902,0xbb9f34db,0x3bfc2ba7,0xbb47b6a4,0xb2633bd7,0x3850babd,0xba7338bc,0x3bb8b432,
  0xb9cdb982,0xb55e3b89,0x3bfaacce,0xb790bb0d,0x3bba3426,0xb0f0bbe7,0xbaba3855,0x3ab03865,0xbbc83371,0x38db3a5c,0x37b2bb04,0xbbf9ad65,
  0x39f4b958,0xbb4cb68d,0x9cb63c00,0x3b54b66b,0x398639c9,0x3b63b625,0xa6adbbff,0xbb89b55e,0xbafeb7c8,0xba25391f,0x35233b94,0x3bfe294d,
  0x3bd43294,0x385abab6,0xb8b2ba7a,0xbbbc341a,0xbbf72dfb,0xb4573bb3,0x3a6738cc,0x3ac7b840,0xb93cba0d,0xbb3db6d2,0xbbffa5e4,0xbb633625,
  0x39d63979,0x3b8e3546,0x3bf9ad33,0x3b07b7a6,0xba60b8d6,0xbbc9b359,0xbbdd31e8,0xba973889,0x3ad83825,0x3bef3010,0x3babb493,0x3a15b933,
  0x38ee3a4d,0x34ab3ba7,0xac9c3bfb,0xb6d23b3d,0xb855baba,0xb27cbbd6,0x313bbbe4,0x380fbae5,0x37643b18,0x2f273bf3,0xb40e3bbd,0xb8ad3a7e,
  0xb60ebb68,0xa51bbc00,0x3576bb85,0x3941ba09,0xb89eba89,0x381abade,0x3bf12fbd,0x34ab3ba7,0x35233b94,0xb9e3396b,0xbb57b65f,0x9fdbbc00,
  0xa8e8bbfe,0x3b2fb70a,0x3a213924,0xb46f3bb0,0xb3eb3bc0,0xbbe33153,0xb86abaac,0x3850babd,0x384a3ac1,0xbbd8324b,0x316cbbe2,0x3ade381a,
  0xad33bbf9,0x3bac3487,0xb8e03a58,0xb82abad5,0xb6483b5c,0xb9bcb994,0x3b45b6af,0x2c063bfc,0x3a35b90c,0x34f33b9c,0xbbfdaade,0x368dbb4c,
  0xb7e8baf4,0x3a6f38c1,0xbbcfb2f7,0x3bd8b24b,0xb13b3be4,0xb402bbbf,0x38f83a45,0xbb16b76f,0x39fcb94f,0xb6a43b47,0x217fbc00,0x36543b59,
  0xbbfe29b1,0x3b2ab721,0xb91b3a29,0x3457bbb3,0x37373b24,0xae5fbbf6,0xb43e3bb7,0x38c1ba6f,0x365fbb57,0xb99d39b3,0x3b4ab699,0xbbfd2b43,
  0xbbae347b,0x3bf92d65,0xbb32b6ff,0x397439da,0x3aa2387a,0xb894ba90,0x33a23bc5,0x3010bbef,0xb682bb4f,0xb95d39f0,0x3b9a34ff,0xae5fbbf6,
  0xb8e03a58,0x3bc63389,0xb1b6bbdf,0xba9e387f,0x3be63109,0xb41abbbc,0xba3d3902,0x3b1b3759,0xb552bb8b,0xb9d2397d,0x3b603631,0xa51bbc00,
  0x35c83b76,0x3c009648,0x35bcbb78,0xb9f0b95d,0x3a45b8f8,0xb4c3bba3,0xbbfcac38,0xb6bb3b42,0xba9bb884,0xba973889,0x33713bc8,0x3bee3042,
  0xb4b73ba5,0x3a4938f3,0x3ae1b815,0xb153bbe3,0xb50bbb98,0xb962b9eb,0xbb52b676,0xbc001648,0xbb4a3699,0xb95439f8,0xb4e73b9e,0x2ec33bf5,
  0x380a3ae8,0x3a7e38ad,0x3bd43294,0x3bd3b2ad,0x3a73b8bc,0x37f3baf1,0x2e91bbf5,0xb4f3bb9c,0x344b3bb5,0xae2d3bf6,0xb72c3b27,0xb9eb3962,
  0x3bdfb1b6,0x3bdc3201,0x3acb383a,0x38d13a64,0xad97bbf8,0x346fbbb0,0x38d6ba60,0x3aceb835,0xbc009cb6,0xbb73b5d4,0xb9e7b966,0xb721bb2a,
  0xb30fbbce,0x3a6bb8c7,0x3af737dd,0xae2d3bf6,0xbbfcac38,0xb581bb83,0x39c0b990,0x3b6a3602,0xb58d3b81,0xbbfc2c06,0xb764bb18,0x38fdba41,
  0x3a6738cc,0xb3283bcc,0xbbda3219,0xb894ba90,0x31853be1,0xbbd9b232,0x3845bac4,0x38c73a6b,0x3b9e34e7,0xb9073a39,0xb7febaee,0x3be7b0f0,
  0x39b8b999,0x36543b59,0xbbfe28e8,0x352fbb92,0xb493bbab,0x3bfa2d00,0xb6e83b37,0xb97db9d2,0xafefbbf0,0x38203adb,0xba8cb899,0x3bd93232,
  0xbacbb83a,0x3bec3074,0xbbb23463,0x3a25b91f,0xbb90353a,0x39dab974,0xb6483b5c,0xa311bc00,0xb5763b85,0xac6abbfb,0x377a3b13,0xba49b8f3,
  0x2cce3bfa,0x349fbba9,0xb8ea3a50,0x3adbb820,0x399039c0,0xb63cbb5e,0x281f3bff,0x3546bb8e,0x3bf42ef5,0xbb1bb759,0x394f39fc,0xb599bb7f,
  0x3aacb86a,0xbbd032de,0x3be830d7,0xbaf1b7f3,0xa6adbbff,0xbb3a36dd,0x3a113937,0x349fbba9,0xb7febaee,0xb8b73a76,0x3bd232c6,0xb27cbbd6,
  0xbad1b830,0xb0423bee,0x3baeb47b,0xb929ba1d,0xbbfdaade,0x35b13b7a,0x39afb9a1,0xbb73b5d4,0xa5e43bff,0x3b65361a,0x3982b9cd,0xb6ddbb3a,
  0x34633bb2,0x3bf82dc9,0x3715bb2c,0xb96bb9e3,0x385f3ab3,0x3bd3b2ad,0x3109bbe6,0xbaebb805,0x3a29391b,0x3afbb7d2,0xb08dbbeb,0xbbccb328,
  0x2c9cbbfb,0xb56abb87,0xb986b9c9,0xbb65b61a,0xa81fbbff,0xb6f4bb35,0xba19b92e,0xbbacb487,0xb05bbbed,0xb835bace,0xba9bb884,0xbbdeb1cf,
  0xb3a2bbc5,0xb8e5ba54,0xbb0ab79b,0xbbfaad00,0x00000000,0x00000000,0x00000000,0x00000000,0xaa1f0000,0xaf64ada8,0xaf64b000,0xaa1fada8,
  0xada80000,0xada8b000,0x2da88000,0x2da83000,0xaf640000,0x2a1fada8,0x2a1f3000,0xaf64ada8,0xb0000000,0x30008000,0xb0000000,0x30008000,
  0xaf640000,0x2a1f2da8,0x2a1fb000,0xaf642da8,0xada80000,0xada83000,0x2da88000,0x2da8b000,0xaa1f0000,0xaf642da8,0xaf643000,0xaa1f2da8,
  0x00000000,0x00000000,0x00000000,0x00000000,0x2a1f8000,0x2f642da8,0x2f643000,0x2a1f2da8,0xada80000,0xada8b000,0x2da88000,0x2da83000,
  0x2f648000,0xaa1f2da8,0xaa1fb000,0x2f642da8,0xb0000000,0x30008000,0xb0000000,0x30008000,0x2f648000,0xaa1fada8,0xaa1f3000,0x2f64ada8,
  0xada80000,0xada83000,0x2da88000,0x2da8b000,0x2a1f8000,0x2f64ada8,0x2f64b000,0x2a1fada8,0x80000000,0x80000000,0x80000000,0x80000000,
  0x2a1f0000,0x2f64ada8,0x2f64b000,0x2a1fada8,0x2da80000,0x2da8b000,0xada88000,0xada83000,0x2f640000,0xaa1fada8,0xaa1f3000,0x2f64ada8,
  0x30000000,0xb0008000,0x30000000,0xb0008000,0x2f640000,0xaa1f2da8,0xaa1fb000,0x2f642da8,0x2da80000,0x2da83000,0xada88000,0xada8b000,
  0x2a1f0000,0x2f642da8,0x2f643000,0x2a1f2da8,0x80000000,0x80000000,0x80000000,0x80000000,0xaa1f8000,0xaf642da8,0xaf643000,0xaa1f2da8,
  0x2da80000,0x2da8b000,0xada88000,0xada83000,0xaf648000,0x2a1f2da8,0x2a1fb000,0xaf642da8,0x30000000,0xb0008000,0x30000000,0xb0008000,
  0xaf648000,0x2a1fada8,0x2a1f3000,0xaf64ada8,0x2da80000,0x2da83000,0xada88000,0xada8b000,0xaa1f8000,0xaf64ada8,0xaf64b000,0xaa1fada8,
  0x30003000,0x30003000,0x30003000,0x30003000,0x2f643000,0x2a1f2da8,0xaa1f0000,0xaf64ada8,0x2da83000,0xada80000,0xada8b000,0x2da88000,
  0x2a1f3000,0xaf64ada8,0x2f648000,0xaa1f2da8,0x00003000,0x8000b000,0x00003000,0x8000b000,0xaa1f3000,0x2f64ada8,0xaf640000,0x2a1f2da8,
  0xada83000,0x2da88000,0x2da8b000,0xada80000,0xaf643000,0xaa1f2da8,0x2a1f8000,0x2f64ada8,0x30003000,0x30003000,0x30003000,0x30003000,
  0xaf64b000,0xaa1fada8,0x2a1f8000,0x2f642da8,0x2da83000,0xada80000,0xada8b000,0x2da88000,0xaa1fb000,0x2f642da8,0xaf640000,0x2a1fada8,
  0x00003000,0x8000b000,0x00003000,0x8000b000,0x2a1fb000,0xaf642da8,0x2f648000,0xaa1fada8,0xada83000,0x2da88000,0x2da8b000,0xada80000,
  0x2f64b000,0x2a1fada8,0xaa1f0000,0xaf642da8,0xb0003000,0xb0003000,0xb0003000,0xb0003000,0xaf643000,0xaa1f2da8,0x2a1f0000,0x2f64ada8,
  0xada83000,0x2da80000,0x2da8b000,0xada88000,0xaa1f3000,0x2f64ada8,0xaf648000,0x2a1f2da8,0x80003000,0x0000b000,0x80003000,0x0000b000,
  0x2a1f3000,0xaf64ada8,0x2f640000,0xaa1f2da8,0x2da83000,0xada88000,0xada8b000,0x2da80000,0x2f643000,0x2a1f2da8,0xaa1f8000,0xaf64ada8,
  0xb0003000,0xb0003000,0xb0003000,0xb0003000,0x2f64b000,0x2a1fada8,0xaa1f8000,0xaf642da8,0xada83000,0x2da80000,0x2da8b000,0xada88000,
  0x2a1fb000,0xaf642da8,0x2f640000,0xaa1fada8,0x80003000,0x0000b000,0x80003000,0x0000b000,0xaa1fb000,0x2f642da8,0xaf648000,0x2a1fada8,
  0x2da83000,0xada88000,0xada8b000,0x2da80000,0xaf64b000,0xaa1fada8,0x2a1f0000,0x2f642da8,0x80008000,0x80008000,0x80008000,0x80008000,
  0x2a1f8000,0x2f642da8,0x2f643000,0x2a1f2da8,0x2da88000,0x2da83000,0xada80000,0xada8b000,0x2f648000,0xaa1f2da8,0xaa1fb000,0x2f642da8,
  0x30008000,0xb0000000,0x30008000,0xb0000000,0x2f648000,0xaa1fada8,0xaa1f3000,0x2f64ada8,0x2da88000,0x2da8b000,0xada80000,0xada83000,
  0x2a1f8000,0x2f64ada8,0x2f64b000,0x2a1fada8,0x80008000,0x80008000,0x80008000,0x80008000,0xaa1f0000,0xaf64ada8,0xaf64b000,0xaa1fada8,
  0x2da88000,0x2da83000,0xada80000,0xada8b000,0xaf640000,0x2a1fada8,0x2a1f3000,0xaf64ada8,0x30008000,0xb0000000,0x30008000,0xb0000000,
  0xaf640000,0x2a1f2da8,0x2a1fb000,0xaf642da8,0x2da88000,0x2da8b000,0xada80000,0xada83000,0xaa1f0000,0xaf642da8,0xaf643000,0xaa1f2da8,
  0x00008000,0x00008000,0x00008000,0x00008000,0xaa1f8000,0xaf642da8,0xaf643000,0xaa1f2da8,0xada88000,0xada83000,0x2da80000,0x2da8b000,
  0xaf648000,0x2a1f2da8,0x2a1fb000,0xaf642da8,0xb0008000,0x30000000,0xb0008000,0x30000000,0xaf648000,0x2a1fada8,0x2a1f3000,0xaf64ada8,
  0xada88000,0xada8b000,0x2da80000,0x2da83000,0xaa1f8000,0xaf64ada8,0xaf64b000,0xaa1fada8,0x00008000,0x00008000,0x00008000,0x00008000,
  0x2a1f0000,0x2f64ada8,0x2f64b000,0x2a1fada8,0xada88000,0xada83000,0x2da80000,0x2da8b000,0x2f640000,0xaa1fada8,0xaa1f3000,0x2f64ada8,
  0xb0008000,0x30000000,0xb0008000,0x30000000,0x2f640000,0xaa1f2da8,0xaa1fb000,0x2f642da8,0xada88000,0xada8b000,0x2da80000,0x2da83000,
  0x2a1f0000,0x2f642da8,0x2f643000,0x2a1f2da8,
};

constexpr int kThreads = 384;
constexpr int kCtas = 128;

#define PREP0 1600
#define PREPGAP 650
#define HT0 13800
#define HGAP 500
#define WQT 11800
#define QT 17800
#define QGAP 400
#define POSTGAP 1000
#define TAIL 3
#define PSW 6
constexpr int EARLY = 2, L0 = 2;

constexpr int NS1 = 6;
__host__ __device__ constexpr int slot1(int it) { return (it + 4) % NS1; }
__host__ __device__ constexpr uint32_t w1_off(int s) { return (1 + s + (s >> 1)) * 16384; }
__host__ __device__ constexpr uint32_t x1_off(int it) { return ((it >> 1) & 3) * 49152; }
constexpr uint32_t ST2 = 32768;
constexpr uint32_t RA = 131072;
constexpr uint32_t RB = 163840;
constexpr uint32_t RU = 196608;
constexpr uint32_t Y_IN = RU;
constexpr uint32_t SM_ONES = 229376;
constexpr uint32_t SM_F2 = SM_ONES + 128;
constexpr uint32_t SM_BAR = 231424;
constexpr uint32_t SM_SCALE = SM_ONES + 1792;
constexpr uint32_t SM_MAX = SM_BAR + 512;
constexpr uint32_t SM_TOTAL = 232448;
constexpr uint32_t SM_BASE = 1024;
__host__ __device__ constexpr uint32_t kv_off(int h) { return RB + (h >> 1) * 16384 + (h & 1) * 2560; }

enum Bar { B_F1 = 0, B_F2 = 6, B_H = B_F2 + 4, B_KVL = 12, B_RDY = 20, B_Q = 34, B_MAX, B_ZERO, B_U, B_KV,
           B_E1 = 39, B_E2 = 45, B_I2 = B_E2 + 4,
           B_KVE = 51, B_VST, B_KVM, B_KVP, B_KVI, B_OW, B_ZST = 58,
           B_OFREE = 59, B_F2M, B_STG, B_Y, B_COUNT = 64, B_U2 = B_KVL };
__host__ __device__ constexpr int slot2(int n) { return n < 22 ? n & 3 : (0x1032510325ull >> (4 * (n - 22))) & 7; }
__host__ __device__ constexpr int par2(int n) { return n < 22 ? (n >> 2) & 1 : (0x326 >> (n - 22)) & 1; }

constexpr int KV_WORDS = 4096 + 128;
struct Scratch {
  float kv[8][KV_WORDS];
  unsigned kvflag[8 * 32], zflag[8 * 32], oflag[16 * 32], epoch[kCtas];
};
struct Params {
  CUtensorMap w1, x, k, v, w2, wo, o, outa, q, outb;
  const __nv_bfloat16* shift_k;
  const __nv_bfloat16* ssm_k;
  const __nv_bfloat16* ssm_d;
  const __nv_bfloat16* q_ptr;
  const __nv_bfloat16* w_ptr;
  const __nv_bfloat16* wo_ptr;
  uint64_t zero;
  Scratch* g;
  const uint32_t* tab;
};

__device__ __align__(128) Scratch g_scratch;
__device__ __align__(128) __nv_bfloat16 g_o[2048 * 1024];

#define TSTAMP(cond, i) do { } while (0)
#define GSTAMP(cond, i) do { } while (0)
#define KSTAMP(n) do { } while (0)
#define QSTAMP(n) do { } while (0)

#define JIT() do { } while (0)
constexpr int kSpinLimit = 1 << 16;

DEVI void mbar_init(uint32_t a, uint32_t c) { asm volatile("mbarrier.init.shared::cta.b64 [%0], %1;" :: "r"(a), "r"(c) : "memory"); }
DEVI void mbar_expect(uint32_t a, uint32_t b) { asm volatile("mbarrier.arrive.expect_tx.shared::cta.b64 _, [%0], %1;" :: "r"(a), "r"(b) : "memory"); }
DEVI void mbar_arrive(uint32_t a) { asm volatile("mbarrier.arrive.shared::cta.b64 _, [%0];" :: "r"(a) : "memory"); }
DEVI void mbar_arrive_if(uint32_t a, bool pred) {
  asm volatile("{\n.reg .pred p;\nsetp.ne.b32 p, %1, 0;\n@p mbarrier.arrive.shared::cta.b64 _, [%0];\n}" :: "r"(a), "r"((int)pred) : "memory");
}
DEVI void mbar_wait(uint32_t a, uint32_t parity) {
  asm volatile("{\n.reg .pred p;\n.reg .u32 n;\nmov.u32 n, 0;\nW_LOOP:\n"
               "mbarrier.try_wait.parity.shared::cta.b64 p, [%0], %1;\n@p bra W_DONE;\n"
               "add.u32 n, n, 1;\nsetp.lt.u32 p, n, %2;\n@p bra W_LOOP;\nW_DONE:\n}"
               :: "r"(a), "r"(parity), "n"(kSpinLimit) : "memory");
  JIT();
}
DEVI void mbar_wait4(uint32_t a, uint32_t b, uint32_t c, uint32_t d) {
  asm volatile("{\n.reg .pred p, q, r, s;\n.reg .u32 n;\nmov.u32 n, 0;\nW_LOOP:\n"
               "mbarrier.try_wait.parity.shared::cta.b64 p, [%0], 0;\nmbarrier.try_wait.parity.shared::cta.b64 q, [%1], 0;\n"
               "mbarrier.try_wait.parity.shared::cta.b64 r, [%2], 0;\nmbarrier.try_wait.parity.shared::cta.b64 s, [%3], 0;\n"
               "and.pred p, p, q;\nand.pred r, r, s;\nand.pred p, p, r;\n@p bra W_DONE;\n"
               "add.u32 n, n, 1;\nsetp.lt.u32 p, n, %4;\n@p bra W_LOOP;\nW_DONE:\n}"
               :: "r"(a), "r"(b), "r"(c), "r"(d), "n"(kSpinLimit) : "memory");
  JIT();
}
DEVI uint32_t mbar_test(uint32_t a, uint32_t parity) {
  uint32_t ok; asm volatile("{\n.reg .pred p;\nmbarrier.test_wait.parity.shared::cta.b64 p, [%1], %2;\nselp.u32 %0, 1, 0, p;\n}" : "=r"(ok) : "r"(a), "r"(parity) : "memory"); return ok;
}
DEVI void mbar_wait_unless(uint32_t ok, uint32_t a, uint32_t parity) {
  asm volatile("{\n.reg .pred p;\n.reg .u32 n;\nsetp.ne.u32 p, %3, 0;\n@p bra W_DONE;\nmov.u32 n, 0;\nW_LOOP:\n"
               "mbarrier.try_wait.parity.shared::cta.b64 p, [%0], %1;\n@p bra W_DONE;\n"
               "add.u32 n, n, 1;\nsetp.lt.u32 p, n, %2;\n@p bra W_LOOP;\nW_DONE:\n}"
               :: "r"(a), "r"(parity), "n"(kSpinLimit), "r"(ok) : "memory");
  JIT();
}
DEVI void mbar_wait_long(uint32_t a, uint32_t parity) {
  asm volatile("{\n.reg .pred p;\n.reg .u32 n;\nmov.u32 n, 0;\nW_LOOP:\n"
               "mbarrier.try_wait.parity.shared::cta.b64 p, [%0], %1, %3;\n@p bra W_DONE;\n"
               "add.u32 n, n, 1;\nsetp.lt.u32 p, n, %2;\n@p bra W_LOOP;\nW_DONE:\n}"
               :: "r"(a), "r"(parity), "n"(kSpinLimit), "r"(4000) : "memory");
  JIT();
}
DEVI void flag_wait(const unsigned* p, unsigned target) {
  int n = 0; unsigned v;
  do {
    asm volatile("ld.relaxed.gpu.global.u32 %0, [%1];" : "=r"(v) : "l"(p) : "memory");
  } while ((int)(v - target) < 0 && ++n < kSpinLimit);
  asm volatile("fence.acquire.gpu;" ::: "memory");
}
DEVI unsigned ld_relaxed(const unsigned* p) { unsigned v; asm volatile("ld.relaxed.gpu.global.u32 %0, [%1];" : "=r"(v) : "l"(p) : "memory"); return v; }
DEVI uint32_t clock32() { uint32_t t; asm volatile("mov.u32 %0, %%clock;" : "=r"(t)); return t; }
DEVI void pace(uint32_t t0, uint32_t n) { while (clock32() - t0 < n) __nanosleep(20); }
DEVI bool elect() { uint32_t p; asm volatile("{\n.reg .pred p;\nelect.sync _|p, 0xffffffff;\nselp.u32 %0, 1, 0, p;\n}" : "=r"(p)); return p; }
DEVI void fence_async_smem() { asm volatile("fence.proxy.async.shared::cta;" ::: "memory"); }
DEVI void bar_sync(int id, int n) { asm volatile("bar.sync %0, %1;" :: "r"(id), "r"(n) : "memory"); }
DEVI void cluster_sync() { asm volatile("barrier.cluster.arrive.relaxed.aligned;\nbarrier.cluster.wait.aligned;" ::: "memory"); }
DEVI void wg_fence() { asm volatile("wgmma.fence.sync.aligned;" ::: "memory"); }
DEVI void wg_commit() { asm volatile("wgmma.commit_group.sync.aligned;" ::: "memory"); }
template <int N> DEVI void wg_wait() { asm volatile("wgmma.wait_group.sync.aligned %0;" :: "n"(N) : "memory"); }
template <int N> DEVI void pin(uint32_t* r) {
#pragma unroll
  for (int i = 0; i < N; i++) asm volatile("" : "+r"(r[i]));
}
template <int N> DEVI void pin(float* r) {
#pragma unroll
  for (int i = 0; i < N; i++) asm volatile("" : "+f"(r[i]));
}

DEVI void tma2d(uint32_t dst, const CUtensorMap* m, int c0, int c1, uint32_t bar) {
  asm volatile("cp.async.bulk.tensor.2d.shared::cluster.global.mbarrier::complete_tx::bytes [%0], [%1, {%3, %4}], [%2];"
               :: "r"(dst), "l"(m), "r"(bar), "r"(c0), "r"(c1) : "memory");
}
DEVI void tma2d_mc(uint32_t dst, const CUtensorMap* m, int c0, int c1, uint32_t bar) {
  asm volatile("cp.async.bulk.tensor.2d.shared::cluster.global.mbarrier::complete_tx::bytes.multicast::cluster [%0], [%1, {%3, %4}], [%2], %5;"
               :: "r"(dst), "l"(m), "r"(bar), "r"(c0), "r"(c1), "h"((uint16_t)3) : "memory");
}
DEVI void tma3d(uint32_t dst, const CUtensorMap* m, int c0, int c1, int c2, uint32_t bar) {
  asm volatile("cp.async.bulk.tensor.3d.shared::cluster.global.mbarrier::complete_tx::bytes [%0], [%1, {%3, %4, %5}], [%2];"
               :: "r"(dst), "l"(m), "r"(bar), "r"(c0), "r"(c1), "r"(c2) : "memory");
}
DEVI void tma4d(uint32_t dst, const CUtensorMap* m, int c1, int c2, int c3, uint32_t bar) {
  asm volatile("cp.async.bulk.tensor.4d.shared::cluster.global.mbarrier::complete_tx::bytes [%0], [%1, {%3, %4, %5, %6}], [%2];"
               :: "r"(dst), "l"(m), "r"(bar), "r"(0), "r"(c1), "r"(c2), "r"(c3) : "memory");
}
DEVI void tma5d(uint32_t dst, const CUtensorMap* m, int c0, int c1, int c3, int c4, uint32_t bar) {
  asm volatile("cp.async.bulk.tensor.5d.shared::cluster.global.mbarrier::complete_tx::bytes [%0], [%1, {%3, %4, %5, %6, %7}], [%2];"
               :: "r"(dst), "l"(m), "r"(bar), "r"(c0), "r"(c1), "r"(0), "r"(c3), "r"(c4) : "memory");
}
DEVI void tma2d_store(const CUtensorMap* m, uint32_t src, int c0, int c1) {
  asm volatile("cp.async.bulk.tensor.2d.global.shared::cta.bulk_group [%0, {%2, %3}], [%1];" :: "l"(m), "r"(src), "r"(c0), "r"(c1) : "memory");
}
DEVI void tma2d_store_e(const CUtensorMap* m, uint32_t src, int c0, int c1) {
  asm volatile("{\n.reg .pred e;\nelect.sync _|e, 0xffffffff;\n@e cp.async.bulk.tensor.2d.global.shared::cta.bulk_group [%0, {%2, %3}], [%1];\n"
               "@e cp.async.bulk.commit_group;\n}" :: "l"(m), "r"(src), "r"(c0), "r"(c1) : "memory");
}
DEVI void tma5d_store(const CUtensorMap* m, uint32_t src, int c0, int c1, int c3, int c4) {
  asm volatile("cp.async.bulk.tensor.5d.global.shared::cta.bulk_group [%0, {%2, %3, %4, %5, %6}], [%1];\ncp.async.bulk.commit_group;"
               :: "l"(m), "r"(src), "r"(c0), "r"(c1), "r"(0), "r"(c3), "r"(c4) : "memory");
}
DEVI void bulk_load(uint32_t dst, const void* src, uint32_t bytes, uint32_t bar) {
  asm volatile("cp.async.bulk.shared::cluster.global.mbarrier::complete_tx::bytes [%0], [%1], %2, [%3];" :: "r"(dst), "l"(src), "r"(bytes), "r"(bar) : "memory");
}
DEVI uint32_t mapa(uint32_t a, int rank) { uint32_t r; asm("mapa.shared::cluster.u32 %0, %1, %2;" : "=r"(r) : "r"(a), "r"(rank)); return r; }
DEVI void st_async4(uint32_t dst, uint32_t a, uint32_t b, uint32_t c, uint32_t d, uint32_t bar) {
  asm volatile("st.async.weak.shared::cluster.mbarrier::complete_tx::bytes.v4.b32 [%0], {%1,%2,%3,%4}, [%5];"
               :: "r"(dst), "r"(a), "r"(b), "r"(c), "r"(d), "r"(bar) : "memory");
}
DEVI void st_either8(bool local, uint32_t dst, uint32_t bar, uint32_t a, uint32_t b, uint32_t c, uint32_t d, uint32_t e, uint32_t f, uint32_t g, uint32_t h) {
  asm volatile("{\n.reg .pred p;\nsetp.ne.b32 p, %10, 0;\n@p st.shared.v4.b32 [%0], {%2,%3,%4,%5};\n@p st.shared.v4.b32 [%0 + 4096], {%6,%7,%8,%9};\n@p bra.uni E_DONE;\n"
               "st.async.weak.shared::cluster.mbarrier::complete_tx::bytes.v4.b32 [%0], {%2,%3,%4,%5}, [%1];\n"
               "st.async.weak.shared::cluster.mbarrier::complete_tx::bytes.v4.b32 [%0 + 4096], {%6,%7,%8,%9}, [%1];\nE_DONE:\n}"
               :: "r"(dst), "r"(bar), "r"(a), "r"(b), "r"(c), "r"(d), "r"(e), "r"(f), "r"(g), "r"(h), "r"((int)local) : "memory");
}
DEVI void red_async_max(uint32_t dst, uint32_t a, uint32_t bar) {
  asm volatile("red.async.relaxed.cluster.shared::cluster.mbarrier::complete_tx::bytes.max.u32 [%0], %1, [%2];" :: "r"(dst), "r"(a), "r"(bar) : "memory");
}
DEVI void pf_line(const void* p) { asm volatile("prefetch.global.L2 [%0];" :: "l"(p) : "memory"); }
DEVI void bulk_commit() { asm volatile("cp.async.bulk.commit_group;" ::: "memory"); }
DEVI void bulk_wait_all() { asm volatile("cp.async.bulk.wait_group 0;" ::: "memory"); }
DEVI void bulk_wait_read() { asm volatile("cp.async.bulk.wait_group.read 0;" ::: "memory"); }
DEVI void prefetch_map(const CUtensorMap* m) { asm volatile("prefetch.tensormap [%0];" :: "l"(m) : "memory"); }

__host__ __device__ constexpr uint32_t dlo(uint32_t off, uint32_t lbo) { return (off >> 4) + ((lbo >> 4) << 16); }
struct Desc {
  uint64_t v;
  DEVI Desc(uint64_t z, uint32_t base, uint32_t sbo, uint32_t mode) : v(z + (base | (uint64_t)((sbo >> 4) | (mode << 30)) << 32)) { asm volatile("" : "+l"(v)); }
  DEVI void renew(uint64_t z) { asm volatile("add.s64 %0, %0, %1;" : "+l"(v) : "l"(z)); }
  DEVI uint64_t at(uint32_t lo) const { uint64_t r; asm volatile("add.s64 %0, %1, %2;" : "=l"(r) : "l"(v), "l"((int64_t)(int32_t)lo)); return r; }
};
DEVI uint32_t pack_bf16(float lo, float hi) { uint32_t r; asm("cvt.rn.bf16x2.f32 %0, %1, %2;" : "=r"(r) : "f"(hi), "f"(lo)); return r; }
DEVI uint32_t pack_f16(float lo, float hi) { uint32_t r; asm("cvt.rn.f16x2.f32 %0, %1, %2;" : "=r"(r) : "f"(hi), "f"(lo)); return r; }
DEVI void stsm4(uint32_t addr, uint32_t r0, uint32_t r1, uint32_t r2, uint32_t r3) {
  asm volatile("stmatrix.sync.aligned.m8n8.x4.shared.b16 [%0], {%1,%2,%3,%4};" :: "r"(addr), "r"(r0), "r"(r1), "r"(r2), "r"(r3) : "memory");
}
DEVI void stsm4_t(uint32_t addr, uint32_t r0, uint32_t r1, uint32_t r2, uint32_t r3) {
  asm volatile("stmatrix.sync.aligned.m8n8.x4.trans.shared.b16 [%0], {%1,%2,%3,%4};" :: "r"(addr), "r"(r0), "r"(r1), "r"(r2), "r"(r3) : "memory");
}
DEVI void sts128(uint32_t addr, uint32_t a, uint32_t b, uint32_t c, uint32_t d) {
  asm volatile("st.shared.v4.b32 [%0], {%1,%2,%3,%4};" :: "r"(addr), "r"(a), "r"(b), "r"(c), "r"(d) : "memory");
}
DEVI void sts32(uint32_t addr, uint32_t v) { asm volatile("st.shared.b32 [%0], %1;" :: "r"(addr), "r"(v) : "memory"); }
DEVI uint32_t lds32(uint32_t a) { uint32_t v; asm volatile("ld.shared.b32 %0, [%1];" : "=r"(v) : "r"(a)); return v; }
DEVI void lds128(uint32_t* v, uint32_t a) {
  asm volatile("ld.shared.v4.b32 {%0,%1,%2,%3}, [%4];" : "=r"(v[0]), "=r"(v[1]), "=r"(v[2]), "=r"(v[3]) : "r"(a));
}
DEVI void ldg128(uint32_t* v, const void* p) {
  asm volatile("ld.global.nc.L1::no_allocate.v4.b32 {%0,%1,%2,%3}, [%4];" : "=r"(v[0]), "=r"(v[1]), "=r"(v[2]), "=r"(v[3]) : "l"(p));
}
DEVI float rcp(float x) { float r; asm("rcp.approx.ftz.f32 %0, %1;" : "=f"(r) : "f"(x)); return r; }
DEVI float exp_sat(float t) {
  float e, s;
  asm("ex2.approx.ftz.f32 %0, %1;" : "=f"(e) : "f"(t * 1.4426950408889634f));
  asm("add.sat.f32 %0, %1, 0f358637BD;" : "=f"(s) : "f"(e));
  return s;
}
DEVI uint32_t phi2(float a, float b) {
  uint32_t r, o;
  asm("cvt.rn.relu.bf16x2.f32 %0, %1, %2;" : "=r"(r) : "f"(b), "f"(a));
  asm("add.rn.bf16x2 %0, %1, %2;" : "=r"(o) : "r"(r), "r"(pack_bf16(exp_sat(a), exp_sat(b))));
  return o;
}
DEVI void arrive_both(uint32_t bar, int lane, bool pred = true) {
  asm volatile("{\n.reg .pred p;\n.reg .b32 r;\nsetp.ne.b32 p, %2, 0;\nmapa.shared::cluster.u32 r, %0, %1;\n@p mbarrier.arrive.shared::cluster.b64 _, [r];\n}"
               :: "r"(bar), "r"(lane & 1), "r"((int)(pred && lane < 2)) : "memory");
}
DEVI uint32_t bmul2(uint32_t a, uint32_t b) { uint32_t r; asm("mul.rn.bf16x2 %0, %1, %2;" : "=r"(r) : "r"(a), "r"(b)); return r; }
DEVI uint32_t badd2(uint32_t a, uint32_t b) { uint32_t r; asm("add.rn.bf16x2 %0, %1, %2;" : "=r"(r) : "r"(a), "r"(b)); return r; }
DEVI uint32_t bamax2(uint32_t a, uint32_t b) { uint32_t r; asm("max.NaN.xorsign.abs.bf16x2 %0, %1, %2;" : "=r"(r) : "r"(a), "r"(b)); return r; }
DEVI uint32_t hmul2(uint32_t a, uint32_t b) { uint32_t r; asm("mul.rn.f16x2 %0, %1, %2;" : "=r"(r) : "r"(a), "r"(b)); return r; }
DEVI uint32_t hadd2(uint32_t a, uint32_t b) { uint32_t r; asm("add.rn.f16x2 %0, %1, %2;" : "=r"(r) : "r"(a), "r"(b)); return r; }
DEVI uint32_t hsub2(uint32_t a, uint32_t b) { uint32_t r; asm("sub.rn.f16x2 %0, %1, %2;" : "=r"(r) : "r"(a), "r"(b)); return r; }
DEVI uint32_t hfma2(uint32_t a, uint32_t b, uint32_t c) { uint32_t r; asm("fma.rn.f16x2 %0, %1, %2, %3;" : "=r"(r) : "r"(a), "r"(b), "r"(c)); return r; }
DEVI uint32_t hfnma2(uint32_t a, uint32_t b, uint32_t c) {
  uint32_t r; asm("{\n.reg .b32 n;\nneg.f16x2 n, %1;\nfma.rn.f16x2 %0, n, %2, %3;\n}" : "=r"(r) : "r"(a), "r"(b), "r"(c)); return r;
}
DEVI float bf_lo(uint32_t w) { return __uint_as_float(w << 16); }
DEVI float bf_hi(uint32_t w) { return __uint_as_float(w & 0xffff0000u); }

DEVI uint32_t chan_exponent(const uint32_t* w) {
  uint32_t m[4];
#pragma unroll
  for (int i = 0; i < 4; i++) m[i] = bamax2(w[i], w[i + 4]);
#pragma unroll
  for (int i = 8; i < 32; i++) m[i & 3] = bamax2(m[i & 3], w[i]);
  uint32_t x = bamax2(bamax2(m[0], m[1]), bamax2(m[2], m[3])) & 0x7fff7fffu;
  x = max(x >> 16, x & 0xffffu);
  x = __reduce_max_sync(0xffffffffu, x);
  return min(x >> 7, 251u);
}
DEVI uint32_t to_f16(uint32_t w, uint32_t mul) { const uint32_t y = bmul2(w, mul); return pack_f16(bf_lo(y), bf_hi(y)); }

struct Tile { int j, r; };
DEVI Tile tile_of() {
  int cta; asm volatile("mov.u32 %0, %%ctaid.x;" : "=r"(cta));
  const int cl = cta >> 1, lo = (cl - 4) >> 31, hi = (35 - cl) >> 31;
  const int p = cl - 4 + (lo & (36 + 7 * cl)) + (hi & ((((cl - 36) * 37) >> 8) + 1)), g = p & 7, rr = p >> 3;
  return Tile{(g & 6) | (cta & 1), 2 * rr + (g & 1)};
}

static_assert(TAIL <= 4, "the releases up to stage 26 feed the ring");
__host__ __device__ constexpr bool prew(int it) { return it >= 28 && it < 31; }

DEVI void twiddle(uint32_t& ore, uint32_t& oim, uint32_t re, uint32_t im, uint32_t t, uint32_t s) {
  re = hfma2(t, im, re);
  oim = hfma2(s, re, im);
  ore = hfma2(t, oim, re);
}

__global__ void __cluster_dims__(2, 1, 1) __launch_bounds__(kThreads, 1)
fused_kernel(const __grid_constant__ Params P) {
  extern __shared__ __align__(1024) uint8_t smem[];
  const int tid = threadIdx.x, lane = tid & 31;
  const int warp = tid >> 5, warpu = __shfl_sync(0xffffffffu, tid >> 5, 0);
  const int cta = blockIdx.x, rho = cta & 1, cl = cta >> 1;
  const uint32_t sb = SM_BASE + (rho << 24);
  const uint32_t tstart = clock32();
  auto bar = [&](int i) INL { return sb + SM_BAR + 8u * i; };
  auto load1 = [&](int it, int s, int j, int r, bool mc) INL {
    const uint32_t fb = bar(B_F1 + s), xs = sb + x1_off(it);
    mbar_expect(fb, (it & 1) ? 16384 : 32768);
    tma4d(sb + w1_off(s), &P.w1, 32 * it, 2 * j, 1, fb);
    if (!(it & 1)) {
      if (mc) tma2d_mc(xs + rho * 8192, &P.x, 32 * it, 128 * r + 64 * rho, fb);
      else { tma2d(xs, &P.x, 32 * it, 128 * r, fb); tma2d(xs + 8192, &P.x, 32 * it, 128 * r + 64, fb); }
    }
  };
  TSTAMP(tid == 0, 0); GSTAMP(tid == 0, 62);

  if (warpu == 8 && elect()) {
    prefetch_map(&P.w1); prefetch_map(&P.x);
    for (int i = 0; i < EARLY; i++) mbar_init(bar(B_F1 + slot1(i)), 1);
    const Tile T = tile_of();
    for (int i = 0; i < EARLY; i++) load1(i, slot1(i), T.j, T.r, false);
    TSTAMP(true, 18);
    for (int i = EARLY; i < NS1; i++) mbar_init(bar(B_F1 + slot1(i)), 1);
    asm volatile("fence.mbarrier_init.release.cluster;" ::: "memory");
  }
  if (warpu == 9 && elect()) {
    if (sb != (uint32_t)__cvta_generic_to_shared(smem)) __trap();
#pragma unroll
    for (int i = B_F2; i < B_Q; i++) mbar_init(bar(i), 1);
    mbar_expect(bar(B_H), 32768);
    asm volatile("fence.mbarrier_init.release.cluster;" ::: "memory");
  }
  if (warpu == 10 && elect()) {
#pragma unroll
    for (int i = B_Q; i < B_KVE; i++) mbar_init(bar(i), i < B_E1 ? 1 : 16);
    mbar_expect(bar(B_Q), 32768); mbar_expect(bar(B_U), 16384); mbar_expect(bar(B_MAX), 1024);
    asm volatile("fence.mbarrier_init.release.cluster;" ::: "memory");
  }
  if (warpu == 11 && elect()) {
#pragma unroll
    for (int i = B_KVE; i < B_COUNT; i++) mbar_init(bar(i), i < B_OFREE ? 8 : i == B_F2M ? 3 : i < B_Y ? 4 : 9);
    mbar_expect(bar(B_Y), 8192); mbar_expect(bar(B_Y + 1), 8192);
    asm volatile("fence.mbarrier_init.release.cluster;" ::: "memory");
  }
  __syncwarp();
  cluster_sync();

  if (warpu < 8) {
    asm volatile("setmaxnreg.inc.sync.aligned.u32 %0;" :: "n"(232));
    const int wg = warp >> 2, wq = warp & 3, g = lane >> 2, q = lane & 3;
    constexpr uint32_t sbq = SM_BASE >> 4;
    const uint32_t wgu = warpu >> 2;
    const uint64_t z64 = P.zero;
    Desc dA(z64, sbq + wgu * 512, 1024, 1), dB(z64, sbq, 1024, 1);
    const int srow = wg * 64 + wq * 16 + (lane & 15);
    const uint32_t stm = srow * 128 + (((lane >> 4) ^ (srow & 7)) << 4);
    auto stage2 = [&](float* acc, int n, bool first, bool wait = true) INL {
      const int s = slot2(n);
      if (wait) mbar_wait(bar(B_F2 + s), par2(n));
      const uint32_t da = s * (ST2 >> 4) + dlo(0, 16), db = s * (ST2 >> 4) + dlo(16384, 8192);
      wg_fence();
      const uint64_t a0 = dA.at(da), b0 = dB.at(db);
      if (first) mma_n128_init(acc, a0, b0); else mma_n128(acc, a0, b0);
#pragma unroll
      for (int kk = 1; kk < 4; kk++) mma_n128(acc, a0 + 2 * kk, b0 + kk * (2048 >> 4));
      wg_commit();
    };
    auto release2 = [&](int n) INL { arrive_both(bar(B_E2 + slot2(n)), lane); };
    auto publish = [&](int b) INL { fence_async_smem(); __syncwarp(); mbar_arrive_if(bar(b), lane == 0); };

    float aq[64];
    uint32_t f1[8], tw[4];
    uint32_t su[2][32], sh[2][32];
    uint32_t x0[4][8], x1[4][8], p0[2][8], p1[2][8], z0[2][8], z1[2][8];
    auto s1 = [&](uint32_t* d, uint32_t base) INL {
      Desc db(z64, sbq + wgu * 1024 + dlo(base, 128), 512, 0);
      wg_fence();
      mma_s1_init(d, f1, db.v);
      mma_s1(d, f1 + 4, db.at(256 >> 4));
      wg_commit();
    };
    const uint64_t dre = Desc(z64, sbq + dlo(SM_F2 + 512, 128), 256, 0).v, dim = Desc(z64, sbq + dlo(SM_F2, 128), 256, 0).v;
    auto fwd2 = [&](uint32_t (*x)[8], int c) INL {
      uint32_t a[4][8];
#pragma unroll
      for (int t = 0; t < 4; t++) {
        uint32_t* s = (t < 2 ? sh[c >> 1] : su[c >> 1]) + 16 * (c & 1) + 8 * (t & 1);
        pin<8>(s);
#pragma unroll
        for (int i = 0; i < 4; i++) twiddle(a[t][i], a[t][4 + i], s[4 * (i & 1) + (i & 2)], s[4 * (i & 1) + (i & 2) + 1], tw[i & 2], tw[(i & 2) + 1]);
      }
      wg_fence();
#pragma unroll
      for (int t = 0; t < 4; t++) { mma_s2_init(x[t], a[t], dre); mma_s2(x[t], a[t] + 4, dim); }
      wg_commit();
    };
    auto half2 = [&](uint32_t (*x)[8], uint32_t* s) INL {
      uint32_t a[2][8];
      pin<16>(s);
#pragma unroll
      for (int t = 0; t < 2; t++)
#pragma unroll
        for (int i = 0; i < 4; i++) twiddle(a[t][i], a[t][4 + i], s[8 * t + 4 * (i & 1) + (i & 2)], s[8 * t + 4 * (i & 1) + (i & 2) + 1], tw[i & 2], tw[(i & 2) + 1]);
      wg_fence();
#pragma unroll
      for (int t = 0; t < 2; t++) { mma_s2_init(x[t], a[t], dre); mma_s2(x[t], a[t] + 4, dim); }
      wg_commit();
    };
    auto product = [&](uint32_t (*a)[8], uint32_t (*x)[8], int i) INL {
#pragma unroll
      for (int t = 0; t < 4; t++) { pin<2>(x[t] + i); pin<2>(x[t] + 4 + i); }
      auto hr = [&](int l) INL { return x[l >> 1][i + (l & 1)]; };
      auto hi = [&](int l) INL { return x[l >> 1][4 + i + (l & 1)]; };
      auto ur = [&](int l) INL { return x[2 + (l >> 1)][i + (l & 1)]; };
      auto ui = [&](int l) INL { return x[2 + (l >> 1)][4 + i + (l & 1)]; };
      uint32_t gr[4], gi[4];
      gr[0] = hr(0); gi[0] = hi(0);
#pragma unroll
      for (int l = 1; l < 4; l++) { gr[l] = hadd2(hr(l), hi(l - 1)); gi[l] = hsub2(hi(l), hr(l - 1)); }
#pragma unroll
      for (int p = 0; p < 4; p++) {
        uint32_t re = hfnma2(gi[0], ui(p), hmul2(gr[0], ur(p))), im = hfma2(gi[0], ur(p), hmul2(gr[0], ui(p)));
#pragma unroll
        for (int l = 1; l <= p; l++) {
          re = hfnma2(gi[l], ui(p - l), hfma2(gr[l], ur(p - l), re));
          im = hfma2(gi[l], ur(p - l), hfma2(gr[l], ui(p - l), im));
        }
        a[p >> 1][i + (p & 1)] = re; a[p >> 1][4 + i + (p & 1)] = im;
      }
#pragma unroll
      for (int t = 0; t < 2; t++) { pin<2>(a[t] + i); pin<2>(a[t] + 4 + i); }
    };
    auto inv1 = [&](uint32_t (*z)[8], uint32_t (*a)[8]) INL {
      wg_fence();
#pragma unroll
      for (int t = 0; t < 2; t++) { mma_s2_init(z[t], a[t], dre); mma_s2_neg(z[t], a[t] + 4, dim); }
      wg_commit();
    };
    auto zstore = [&](uint32_t (*z)[8], int c) INL {
      const uint32_t zoff = sb + RB + (q >> 1) * (RU + 16 - RB) + (8 * rho + 4 * wg) * 2048 + (4 * (8 * wq + g) + 2 * (q & 1)) * 16;
#pragma unroll
      for (int t = 0; t < 2; t++) {
        uint32_t a[8];
        pin<8>(z[t]);
#pragma unroll
        for (int i = 0; i < 4; i++) twiddle(a[i], a[4 + i], z[t][i], z[t][4 + i], tw[i & 2], tw[(i & 2) + 1]);
        const uint32_t dst = zoff + t * (16384 - rho * 32768) + c * 2048;
        sts128(dst, a[0], a[1], a[2], a[3]);
        sts128(dst + 16, a[4], a[5], a[6], a[7]);
      }
    };
    float kvr[18];
    auto kvstore = [&]() INL {
      const uint32_t dst = sb + kv_off(warp >> 1) + (warp & 1) * 256 + lane * 4;
      pin<18>(kvr);
#pragma unroll
      for (int b = 0; b < 4; b++) { sts32(dst + b * 512, pack_bf16(kvr[4 * b], kvr[4 * b + 1])); sts32(dst + b * 512 + 128, pack_bf16(kvr[4 * b + 2], kvr[4 * b + 3])); }
      sts32(dst + 2048, pack_bf16(kvr[16], kvr[16])); sts32(dst + 2176, pack_bf16(kvr[17], kvr[17]));
      publish(B_KVI);
    };
    {
      float ak[64], av[64];
      Desc dK(z64, sbq + wgu * 256, 1024, 1);
      auto kstep = [&](int c, int i) INL {
        const int s = slot1(c);
        if (!prew(c - 1)) mbar_wait(bar(B_F1 + s), (c / NS1 + i) & 1);
        TSTAMP(tid == 0 && c == 0, 1);
        const uint32_t dx = dlo(x1_off(c + 6 * i), 16), dk = dlo(w1_off(s), 16);
        const uint64_t xb = dB.at(dx) + (c & 1) * 4;
        wg_fence();
        if (c == 0) { mma_kt_init(ak, dK.at(dk), xb); mma_kt_init(av, dK.at(dk + 512), xb); }
        else { mma_kt(ak, dK.at(dk), xb); mma_kt(av, dK.at(dk + 512), xb); }
        mma_kt(ak, dK.at(dk + 128), xb + 2);
        mma_kt(av, dK.at(dk + 640), xb + 2);
        wg_commit();
        wg_wait<1>();
        if (c > 0) arrive_both(bar(B_E1 + (s + NS1 - 1) % NS1), lane);
        if (prew(c)) mbar_wait(bar(B_F1 + slot1(c + 1)), ((c + 1) / NS1) & 1);
        KSTAMP(c + 6 * i);
      };
      auto renew = [&]() INL { dK.renew(z64); dB.renew(z64); };
      uint32_t kk[7], u[36], sw[4], mx[2], um = 0, eu;
      unsigned short dskip;
      const int cp = 4 * (warp & 1) + (lane >> 3), run = 8 * (warp >> 1) + (lane & 7);
      const uint32_t ua = sb + RB + run * 32 + ((warp ^ (lane >> 2)) & 1) * 16 + (lane >> 3) * 4;
      sts32(sb + SM_MAX + (lane & 15) * 4, 0);
      ldg128(sw, P.shift_k + (cl * 16 + 2 * cp) * 4);
      asm volatile("ld.global.nc.b16 %0, [%1];" : "=h"(dskip) : "l"(P.ssm_d + 8 * cta + warp));
#pragma unroll
      for (int c = 0; c < L0; c++) kstep(c, 0);
      {
        pin<4>(sw);
        const uint32_t t0 = __byte_perm(sw[0], sw[2], 0x5410), t1 = __byte_perm(sw[0], sw[2], 0x7632), t2 = __byte_perm(sw[1], sw[3], 0x5410);
        sw[3] = __byte_perm(sw[1], sw[3], 0x7632); sw[0] = t0; sw[1] = t1; sw[2] = t2;
        pin<4>(sw);
      }
      float tap0 = lane == 0 ? bf_lo(dskip) : 0.f;
      pin<1>(&tap0);
#pragma unroll
      for (int e = 0; e < 36; e++) u[e] = 0;
#pragma unroll
      for (int e = 0; e < 7; e++) kk[e] = 0;
      renew();
#pragma unroll
      for (int c = L0; c < L0 + 6; c++) kstep(c, 0);
      renew();
#pragma unroll 1
      for (int i = 1; i < 4; i++) {
#pragma unroll
        for (int h = 0; h < 3; h++) {
          kstep(L0 + 2 * h, i);
          {
            const int slot = (3 * i + h + 4) & 7;
#pragma unroll
            for (int e = 4 * h; e < 4 * h + 4; e++) { u[e] = u[e + 12]; u[e + 12] = u[e + 24]; }
            pin<4>(u + 4 * h); pin<4>(u + 4 * h + 12);
            mbar_wait(bar(B_KVL + slot), h == 2 && i == 3);
#pragma unroll
            for (int e = 0; e < 4; e++) { kk[3 + e] = lds32(ua + slot * 8192 + e * 1024); u[24 + 4 * h + e] = lds32(ua + slot * 8192 + 4096 + e * 1024); }
          }
          kstep(L0 + 2 * h + 1, i);
          pin<7>(kk); pin<4>(u + 24 + 4 * h);
#pragma unroll
          for (int e = 0; e < 4; e++) {
            uint32_t& y = u[24 + 4 * h + e];
            y = bmul2(badd2(badd2(badd2(bmul2(kk[e], sw[3]), bmul2(kk[1 + e], sw[2])), bmul2(kk[2 + e], sw[1])), bmul2(kk[3 + e], sw[0])), y);
            um = bamax2(um, y);
          }
          if (h == 0) um = i == 1 ? 0 : um;
          kk[0] = kk[4]; kk[1] = kk[5]; kk[2] = kk[6];
          pin<4>(u + 24 + 4 * h); pin<1>(&um);
          if (h == 1) mbar_arrive_if(bar(B_KVE), lane == 0 && i == 2);
        }
      }
      um = bamax2(um, __shfl_xor_sync(0xffffffffu, um, 1));
      um = bamax2(um, __shfl_xor_sync(0xffffffffu, um, 2));
      red_async_max(mapa(sb + SM_MAX + cp * 8 + (q & 1) * 4, q >> 1), min((um >> (7 + 16 * (q & 1))) & 0xffu, 251u), mapa(bar(B_MAX), q >> 1));
      renew();
#pragma unroll
      for (int c = L0 + 24; c < 28; c++) {
        kstep(c, 0);
        if (c == L0 + 24) { ldg128(f1, P.tab + (tid & 127) * 4); ldg128(f1 + 4, P.tab + 512 + (tid & 127) * 4); ldg128(tw, P.tab + 1024 + (tid & 127) * 4); }
      }
      mbar_wait(bar(B_MAX), 0);
      TSTAMP(tid == 0, 5);
      asm volatile("ld.shared.v2.b32 {%0,%1}, [%2];" : "=r"(mx[0]), "=r"(mx[1]) : "r"(sb + SM_MAX + cp * 8));
      eu = lds32(sb + SM_MAX + (8 * rho + warp) * 4);
      const uint32_t ud = mapa(sb + RU + (lane >> 3) * 8192 + (2 * rho + wg) * 1024 + (run & 15) * 16, warp & 1), ub = mapa(bar(B_U), rho ^ 1);
#pragma unroll
      for (int i = 0; i < 4; i++) {
        kstep(28 + i, 0);
        if (i == 0) { pin<2>(mx); mx[0] = (0x00fd00fdu - (mx[0] | mx[1] << 16)) << 7; }
        uint32_t* y = u + 4 + 8 * i;
        pin<8>(y);
#pragma unroll
        for (int e = 0; e < 8; e++) y[e] = bmul2(y[e], mx[0]);
        st_either8((warpu & 1) == rho, ud + (i & 1) * 512 + (i >> 1) * 256, ub,
                   pack_f16(bf_lo(y[0]), bf_lo(y[1])), pack_f16(bf_lo(y[2]), bf_lo(y[3])), pack_f16(bf_lo(y[4]), bf_lo(y[5])), pack_f16(bf_lo(y[6]), bf_lo(y[7])),
                   pack_f16(bf_hi(y[0]), bf_hi(y[1])), pack_f16(bf_hi(y[2]), bf_hi(y[3])), pack_f16(bf_hi(y[4]), bf_hi(y[5])), pack_f16(bf_hi(y[6]), bf_hi(y[7])));
      }
      auto qstep = [&](int n) INL {
        if ((n & 3) == 0) { dA.renew(z64); dB.renew(z64); }
        stage2(aq, n, n == 0);
        wg_wait<1>();
        if (n == 0) arrive_both(bar(B_E1 + NS1 - 1), lane); else release2(n - 1);
        QSTAMP(n);
      };
      uint32_t pk[32];
      auto phik = [&](int i0, int i1) INL {
#pragma unroll
        for (int i = i0; i < i1; i++) { pin<2>(ak + 2 * i); pk[i] = phi2(ak[2 * i], ak[2 * i + 1]); pin<1>(pk + i); }
      };
      const uint32_t rot = tile_of().r & 3;
      const uint32_t stt = sb + RA + wg * 16384 + ((lane >> 4) * 8 + (lane & 7)) * 128 + (((2 * wq + ((lane >> 3) & 1)) ^ rot ^ (lane & 7)) << 4);
      auto vst = [&](int k0, int k1) INL {
#pragma unroll
        for (int kt = k0; kt < k1; kt++) {
          float* a = av + 8 * kt;
          pin<8>(a);
          stsm4_t(stt + kt * 2048, pack_bf16(a[0], a[1]), pack_bf16(a[2], a[3]), pack_bf16(a[4], a[5]), pack_bf16(a[6], a[7]));
        }
      };
      float dkv[36];
      Desc dV(z64, sbq + wgu * (1024u - (1024u << 16)) + dlo(RA, SM_ONES - RA), 1024, 1);
      auto kvmma = [&](int k0, int k1) INL {
        wg_fence();
#pragma unroll
        for (int ks = k0; ks < k1; ks++) {
          const uint64_t db = dV.at(ks * (128u - (128u << 16)));
          if (ks == 0) mma_kv_init(dkv, pk, db); else mma_kv(dkv, pk + 4 * ks, db);
        }
        wg_commit();
      };
      float* gacc;
      auto kvred = [&](int b) INL {
        const bool hh = wq >> 1;
        asm volatile("red.relaxed.gpu.global.add.v4.f32 [%0], {%1,%2,%3,%4};" :: "l"(gacc + (b ^ rot) * 128), "f"(hh ? dkv[16 + 4 * b] : dkv[4 * b]),
                     "f"(hh ? dkv[17 + 4 * b] : dkv[1 + 4 * b]), "f"(hh ? dkv[18 + 4 * b] : dkv[2 + 4 * b]), "f"(hh ? dkv[19 + 4 * b] : dkv[3 + 4 * b]) : "memory");
        if (b == 3) {
          asm volatile("{\n.reg .pred p;\nsetp.eq.s32 p, %3, 0;\n@p red.relaxed.gpu.global.add.v2.f32 [%0], {%1,%2};\n}"
                       :: "l"(gacc + 4096 - warp * 496 - g * 14), "f"(dkv[32]), "f"(dkv[34]), "r"(q) : "memory");
          __syncwarp();
          mbar_arrive_if(bar(B_KVP), lane == 0);
          TSTAMP(tid == 0, 4);
        }
      };
      uint32_t w[32], hmul;
      auto hload = [&](int i0, int i1) INL {
        const uint32_t a = sb + RB + warp * 4096 + (((lane >> 2) & 1) + (lane & 2) + 4 * (lane & 1) + (((lane << 2) ^ lane) & 24)) * 16;
#pragma unroll
        for (int i = i0; i < i1; i++) lds128(w + 4 * i, a + i * 512);
      };
      auto hmax = [&]() INL {
        pin<32>(w);
        tap0 += bf_lo(w[0]);
        w[0] = pack_bf16(tap0, bf_hi(w[0]));
        hmul = (252u - chan_exponent(w)) * 0x00800080u;
        const int e = min(max((int)(eu + 128 - (hmul >> 23)), 0), 254);
        asm volatile("st.shared.b16 [%0], %1;" :: "r"(sb + SM_SCALE + 2 * warp), "h"((unsigned short)(e << 7)) : "memory");
      };
      auto hstore = [&](int i0, int i1) INL {
        const uint32_t dst = sb + RB + warp * 4096 + (lane & 6) * 128 + ((lane ^ ((lane >> 2) & 6)) & 7) * 16;
#pragma unroll
        for (int i = i0; i < i1; i++) {
          pin<4>(w + 4 * i);
          const uint32_t w0 = i == 0 ? pack_f16(tap0 * bf_lo(hmul), bf_hi(w[0]) * bf_lo(hmul)) : to_f16(w[4 * i], hmul);
          sts128(dst + (i >> 1) * 1024 + (i & 1) * 128, w0, to_f16(w[4 * i + 1], hmul), to_f16(w[4 * i + 2], hmul), to_f16(w[4 * i + 3], hmul));
        }
      };
      auto kvload = [&]() INL {
        mbar_wait(bar(B_KV), 0);
        TSTAMP(tid == 0, 7);
#pragma unroll
        for (int b = 0; b < 4; b++)
          asm volatile("ld.global.cg.v4.f32 {%0,%1,%2,%3}, [%4];" : "=f"(kvr[4 * b]), "=f"(kvr[4 * b + 1]), "=f"(kvr[4 * b + 2]), "=f"(kvr[4 * b + 3]) : "l"(gacc + b * 128) : "memory");
        asm volatile("ld.global.cg.v2.f32 {%0,%1}, [%2];" : "=f"(kvr[16]), "=f"(kvr[17]) : "l"(gacc + 4096 - warp * 496 - g * 14 - q * 4) : "memory");
      };
      qstep(0);
      TSTAMP(tid == 0, 2);
      phik(0, 7);
      qstep(1);
      mbar_wait(bar(B_E1 + NS1 - 1), 1);
      vst(0, 4); phik(7, 10);
      qstep(2);
      vst(4, 8);
      publish(B_VST);
      phik(10, 13);
      qstep(3);
      mbar_wait(bar(B_ZERO), 0);
      mbar_wait(bar(B_VST), 0);
      kvmma(0, 3); phik(13, 20);
      qstep(4);
      kvmma(3, 5);
      mbar_wait(bar(B_H), 0);
      hload(0, 3); phik(20, 26);
      gacc = &P.g->kv[tile_of().j][warp * 512 + lane * 4];
      qstep(5);
      hload(3, 5); phik(26, 32); kvmma(5, 8); hload(5, 8);
      qstep(6);
      pin<36>(dkv);
      mbar_arrive_if(bar(B_KVM), lane == 0);
      kvred(0);
      mbar_wait(bar(B_U2), 1);
      s1(su[0], RU);
      hmax(); hstore(0, 1); kvred(1);
      qstep(7);
      hstore(1, 4); kvred(2);
      qstep(8);
      hstore(4, 6); kvred(3);
      qstep(9);
      hstore(6, 8);
      publish(B_VST);
      mbar_wait(bar(B_F2M), 0);
      half2(x0 + 2, su[0]);
      qstep(10);
      mbar_wait(bar(B_VST), 1);
      s1(sh[0], RB);
      half2(x1 + 2, su[0] + 16);
      qstep(11);
      half2(x0, sh[0]); half2(x1, sh[0] + 16);
      qstep(12);
      product(p0, x0, 0);
      qstep(13);
      product(p0, x0, 2);
      kvload();
      qstep(14);
      product(p1, x1, 0);
      qstep(15);
      product(p1, x1, 2);
    }

    float acc[64];
    {
      uint32_t pq[4][8];
      float dn[4][20];
      Desc dO(z64, sbq + dlo(0, 128), 512, 0);
      auto phiq = [&](int h) INL {
        pin<16>(aq + 16 * h);
#pragma unroll
        for (int i = 0; i < 8; i++) pq[h][i] = phi2(aq[16 * h + 2 * i], aq[16 * h + 2 * i + 1]);
        pin<8>(pq[h]);
      };
      auto omma = [&](int h) INL {
        wg_fence();
        mma_o_init(dn[h], pq[h], dO.at(kv_off(h) >> 4));
        mma_o(dn[h], pq[h] + 4, dO.at((kv_off(h) + 256) >> 4));
        wg_commit();
      };
      auto onorm = [&](int h) INL {
        pin<20>(dn[h]);
        const float i0 = rcp(dn[h][16] + 1e-6f), i1 = rcp(dn[h][18] + 1e-6f);
#pragma unroll
        for (int hf = 0; hf < 2; hf++) {
          const float* a = dn[h] + 8 * hf;
          stsm4(sb + (h >> 1) * ST2 + (stm ^ (((h & 1) * 2 + hf) << 5)), pack_bf16(a[0] * i0, a[1] * i0), pack_bf16(a[2] * i1, a[3] * i1),
                pack_bf16(a[4] * i0, a[5] * i0), pack_bf16(a[6] * i1, a[7] * i1));
        }
        if (h & 1) publish(B_OW + (h >> 1));
      };
      s1(su[1], RU + 8192);
      kvstore();
      wg_wait<1>();
      release2(15);
      TSTAMP(tid == 0, 6);
      uint32_t gf[4][4];
      auto gdup = [&]() INL {
#pragma unroll
        for (int i = 0; i < 4; i += 2) {
          pin<4>(gf[i + 1]);
          gf[i][0] = gf[i][1] = gf[i + 1][0]; gf[i][2] = gf[i][3] = gf[i + 1][1];
          gf[i + 1][0] = gf[i + 1][1] = gf[i + 1][2]; gf[i + 1][2] = gf[i + 1][3];
          pin<4>(gf[i]); pin<4>(gf[i + 1]);
        }
      };
      const uint32_t qa = sb + RA + warp * 4096 + lane * 32 + ((rho ^ g) & 1) * 16;
      uint32_t qv[4][4];
      auto qload = [&]() INL {
#pragma unroll
        for (int i = 0; i < 4; i++) lds128(qv[i], qa + i * 1024);
      };
      phiq(0);
      const uint32_t kvok = mbar_test(bar(B_KVI), 0);
      phiq(1);
      mbar_wait_unless(kvok, bar(B_KVI), 0);
      omma(0); omma(1);
      wg_wait<1>(); onorm(0);
      wg_wait<0>(); onorm(1);
      TSTAMP(tid == 0, 8);
      s1(sh[1], RB + 8192);
      phiq(2); omma(2); phiq(3);
      wg_wait<0>(); onorm(2);
      omma(3); inv1(z0, p0);
      wg_wait<1>(); onorm(3);
      TSTAMP(tid == 0, 9);
      inv1(z1, p1); fwd2(x0, 2);
      wg_wait<1>();
      mbar_wait4(bar(B_OW + 1), bar(B_F2), bar(B_F2 + 1), bar(B_Q));
      zstore(z0, 0); zstore(z1, 1);
      wg_wait<0>();
      dA.renew(z64); dB.renew(z64);
      stage2(acc, 16, true, false);
      fwd2(x1, 3);
      product(p0, x0, 0); product(p0, x0, 2);
      inv1(z0, p0);
      stage2(acc, 17, false, false);
      wg_wait<2>();
      release2(16);
      ldg128(gf[1], P.tab + 1536 + (tid & 127) * 4); ldg128(gf[3], P.tab + 2048 + (tid & 127) * 4);
      product(p1, x1, 0); product(p1, x1, 2);
      inv1(z1, p1);
      wg_wait<2>();
      zstore(z0, 2);
      gdup();
      wg_wait<0>();
      release2(17);
      zstore(z1, 3);
      publish(B_ZST);
      TSTAMP(tid == 0, 10);
      qload();
      mbar_wait(bar(B_ZST), 0);
      float y[64];
      {
        Desc db(z64, sbq + wgu * ((RU + 16 - RB) >> 4) + dlo(RB, 128), 2048, 0);
        wg_fence();
        mma_i2_init(y, gf[0], db.v, 0xEEEE4444u);
#pragma unroll
        for (int i = 1; i < 4; i++) mma_i2(y, gf[i], db.at(i * (512 >> 4)), 0xEEEE4444u);
        wg_commit();
      }
      uint32_t sc[4];
      lds128(sc, sb + SM_SCALE);
      TSTAMP(tid == 0, 11);
      stage2(acc, 18, false);
      TSTAMP(tid == 0, 13);
      wg_wait<1>();
      QSTAMP(18);
      arrive_both(bar(B_I2), lane);
      pin<64>(y);
      uint32_t yv[8][4];
#pragma unroll
      for (int i = 0; i < 8; i++)
#pragma unroll
        for (int m = 0; m < 4; m++) yv[i][m] = bmul2(pack_bf16(y[32 * (i >> 2) + (i & 3) + 8 * m], y[32 * (i >> 2) + (i & 3) + 8 * m + 4]), sc[m]);
      pin<32>(&yv[0][0]);
      stage2(acc, 19, false);
      wg_wait<1>();
      QSTAMP(19);
      release2(18);
      mbar_wait(bar(B_I2), 0);
      const uint32_t yr = mapa(sb + Y_IN + tid * 16 + warp * 1536, rho ^ 1), yb = mapa(bar(B_Y), rho ^ 1);
      dA.renew(z64); dB.renew(z64);
#pragma unroll
      for (int i = 0; i < 4; i++) {
        if (i) { stage2(acc, 19 + i, false); wg_wait<1>(); QSTAMP(19 + i); release2(18 + i); }
        pin<4>(qv[i]);
        sts128(qa + i * 1024, bmul2(yv[i][0], qv[i][0]), bmul2(yv[i][1], qv[i][1]), bmul2(yv[i][2], qv[i][2]), bmul2(yv[i][3], qv[i][3]));
        st_async4(yr + i * 512, yv[4 + i][0], yv[4 + i][1], yv[4 + i][2], yv[4 + i][3], yb + 8 * (i >> 1));
        if (i & 1) { __syncwarp(); mbar_arrive_if(bar(B_Y + (i >> 1)), lane == 0); }
      }
      TSTAMP(tid == 0, 12);
    }
#pragma unroll 1
    for (int n = 23; n < 32 - TAIL; n++) {
      stage2(acc, n, false);
      TSTAMP(tid == 0 && n == 26, 14);
      wg_wait<1>();
      release2(n - 1);
      QSTAMP(n);
    }
    {
      const Tile T = tile_of();
      dA.renew(z64); dB.renew(z64);
      mbar_wait(bar(B_STG), wgu ^ 1);
#pragma unroll
      for (int n = 32 - TAIL; n < 32; n++) {
        stage2(acc, n, false);
        if (n == 28) { wg_wait<1>(); release2(27); }
      }
      mbar_wait(bar(wgu ? B_E2 + 5 : B_STG), 1);
      mbar_arrive_if(bar(B_STG), wgu == 0 && lane == 0);
      const uint32_t stg = sb + (wgu ? RB - 8192 : RU + 16384);
      wg_wait<0>();
      TSTAMP(tid == 0, 17); TSTAMP(tid == 128, 15);
      pin<64>(acc);
#pragma unroll
      for (int c = 0; c < 2; c++) {
#pragma unroll
        for (int t = 0; t < 4; t++) {
          const float* a = acc + 32 * c + 8 * t;
          stsm4(stg + c * 8192 + (stm ^ (t << 5)), pack_bf16(a[0], a[1]), pack_bf16(a[2], a[3]), pack_bf16(a[4], a[5]), pack_bf16(a[6], a[7]));
        }
        fence_async_smem();
        __syncwarp();
        tma2d_store_e(&P.outa, stg + c * 8192 + warpu * 2048, 128 * T.j + 64 * c, 128 * T.r + 16 * warpu);
      }
      bulk_wait_read();
      TSTAMP(tid == 128, 16);
    }
  } else {
    asm volatile("setmaxnreg.dec.sync.aligned.u32 %0;" :: "n"(40));
    const Tile T = tile_of();
    const int j = T.j, r = T.r;
    auto kcol = [&](int n) INL {
      return n < 20 ? 128 * (j ^ ((n >> 1) & 1)) + 64 * (n & 1) : 128 * (((j & 6) + n - (n < 26 ? 18 : 24)) & 7) + (n < 26 ? 0 : 64);
    };
    if (warpu == 8) {
      uint32_t ph = 0;
      int s = slot1(EARLY);
#pragma unroll 1
      for (int it = EARLY; it < 32; ++it, s = s + 1 == NS1 ? 0 : s + 1) {
        if (it >= NS1) { mbar_wait(bar(B_E1 + s), (ph >> s) & 1); ph ^= 1u << s; }
        if (elect()) load1(it, s, j, r, true);
      }
      int qn = 0;
      auto loadq = [&](int n) INL {
        if ((0x9c000 >> n) & 1) { if (elect()) tma5d(sb + RA + qn * 8192, &P.q, 16 * cl, 2 * rho, 2 * (qn & 2), 2 * (qn & 1), bar(B_Q)); qn++; }
      };
#pragma unroll 1
      for (int n = 0; n < 16; ++n) {
        const int s = n & 3, i = n + (n >> 1);
        mbar_wait(bar(n < 4 ? B_E1 + i : B_E2 + s), n < 4 ? (ph >> i) & 1 : ((n >> 2) - 1) & 1);
        const uint32_t st = sb + s * ST2, fb = bar(B_F2 + s);
        if (elect()) {
          mbar_expect(fb, ST2);
          tma4d(st + 16384, &P.w2, 64 * n, 2 * j, 0, fb);
          tma2d_mc(st + rho * 8192, &P.x, 64 * n, 128 * r + 64 * rho, fb);
        }
        loadq(n);
      }
      auto loadw = [&](int n) INL {
        const int s = n & 3;
        mbar_wait(bar(B_E2 + s), ((n >> 2) - 1) & 1);
        if (elect()) { mbar_expect(bar(B_F2 + s), n < 18 ? 16384 : ST2); tma4d(sb + s * ST2 + 16384, &P.wo, kcol(n), 2 * j, 0, bar(B_F2 + s)); }
      };
#pragma unroll 1
      for (int n = 16; n < 20; ++n) {
        loadw(n);
        loadq(n);
      }
#pragma unroll 1
      for (int n = 18; n < 20; ++n) {
        const uint32_t st = sb + (n & 3) * ST2, fb = bar(B_F2 + (n & 3));
        mbar_wait(bar(B_RDY + n - 18), 0);
        asm volatile("fence.proxy.async.global;" ::: "memory");
        if (elect()) { tma2d(st, &P.o, kcol(n), 128 * r, fb); tma2d(st + 8192, &P.o, kcol(n), 128 * r + 64, fb); }
      }
      mbar_wait(bar(B_OFREE), 0);
      uint64_t slots = 0x103251032510ull, frees = 0x103251032410ull;
      uint32_t pars = 0xc9f, kc = 128 * (j & 6) + 256;
#pragma unroll 1
      for (int n = 20; n < 32; ++n, slots >>= 4, frees >>= 4, pars >>= 1, kc += n == 26 ? 448 : 128) {
        const uint32_t s = slots & 7, st = sb + s * ST2, fb = bar(B_F2 + s);
        mbar_wait(bar(B_RDY + n - 18), 0);
        mbar_wait(bar(B_E2 + (frees & 7)), ~pars & 1);
        if (elect()) {
          mbar_expect(fb, ST2);
          tma4d(st + 16384, &P.wo, kc & 1023, 2 * j, 0, fb);
          tma2d_mc(st + rho * 8192, &P.o, kc & 1023, 128 * r + 64 * rho, fb);
        }
      }
    } else {
      const int at = tid - 288, aw = warpu - 9;
      const unsigned epoch = ld_relaxed(&P.g->epoch[cta]);
      if (aw < 2) {
        float4* zp = reinterpret_cast<float4*>(&P.g->kv[j][r * (KV_WORDS / 16)]) + at;
        zp[0] = zp[2] = make_float4(0.f, 0.f, 0.f, 0.f);
        sts128(sb + SM_ONES + (at & 15) * 128 + (at & 7) * 16, 0x3f803f80u, 0x3f803f80u, 0x3f803f80u, 0x3f803f80u);
        fence_async_smem();
        bar_sync(4, 64);
        if (at == 0) {
          asm volatile("fence.release.gpu;\nred.relaxed.gpu.global.add.u32 [%0], 1;" :: "l"(&P.g->zflag[j * 32]) : "memory");
          flag_wait(&P.g->zflag[j * 32], 16u * (epoch + 1));
          mbar_arrive(bar(B_ZERO));
        }
        __syncwarp();
      } else {
#pragma unroll 1
        for (int m = -1; m < 16; m++) {
          const int s = (m >> 1) & 7;
          pace(tstart, PREP0 + (m + 1) * PREPGAP);
          if (m == 14) mbar_wait(bar(B_KVE), 0);
          if (elect()) {
            if (m < 0 || !(m & 1)) mbar_expect(bar(B_KVL + s), m < 0 ? 4096 : 8192);
            tma3d(sb + RB + (m < 0 ? 14 : m) * 4096, m > 0 && (m & 1) ? &P.v : &P.k, 16 * cl, 32 * rho + (m >> 31), 2 * (m & 14), bar(B_KVL + s));
          }
        }
#pragma unroll 1
        for (int m = 0; m < 8; m++) {
          pace(tstart, HT0 + m * HGAP);
          if (elect()) bulk_load(sb + RB + m * 4096, P.ssm_k + (size_t)(8 * cta + m) * 2048, 4096, bar(B_H));
        }
      }
      if (aw == 1) {
        if (cta < 3) pf_line(P.tab + cta * 768 + lane * 32);
#pragma unroll 1
        for (int m = 0; m < 16; m++) {
          pace(tstart, m < 4 ? WQT + m * 500 : QT + (m - 4) * QGAP);
          pf_line(m < 4 ? P.w_ptr + (size_t)(cta + (2 * m + (lane >> 4)) * 128) * 3072 + (lane & 15) * 64
                        : (m < 12 ? P.q_ptr + cta * 16384 - 8192 : P.wo_ptr + cta * 8192 - 24576) + m * 2048 + lane * 64);
        }
      }
      uint32_t f2[4];
      ldg128(f2, P.tab + 2560 + at * 4);
      if (at == 0) { mbar_wait_long(bar(B_U), 0); fence_async_smem(); mbar_arrive(bar(B_U2)); }
      mbar_wait_long(bar(B_KVM), 0);
      sts128(sb + SM_F2 + at * 16, f2[0], f2[1], f2[2], f2[3]);
      fence_async_smem();
      __syncwarp();
      mbar_arrive_if(bar(B_F2M), lane == 0);
      if (aw == 2 && elect()) {
        mbar_wait(bar(B_KVP), 0);
        asm volatile("fence.release.gpu;\nred.relaxed.gpu.global.add.u32 [%0], 1;" :: "l"(&P.g->kvflag[j * 32]) : "memory");
        flag_wait(&P.g->kvflag[j * 32], 16u * (epoch + 1));
        mbar_arrive(bar(B_KV));
        TSTAMP(true, 19);
      }
      __syncwarp();
      if (aw < 2) {
        {
          const int c = aw;
          if (c == 1) {
            mbar_wait_long(bar(B_KVI), 0);
            if (elect()) { prefetch_map(&P.o); prefetch_map(&P.outb); prefetch_map(&P.outa); }
          }
          mbar_wait_long(bar(B_OW + c), 0);
          if (c == 1) mbar_wait(bar(B_ZERO), 1);
          if (elect()) {
            const uint32_t src = sb + c * ST2;
            tma2d_store(&P.o, src, 128 * j + 64 * c, 128 * r);
            tma2d_store(&P.o, src + 8192, 128 * j + 64 * c, 128 * r + 64);
            bulk_commit();
            bulk_wait_all();
            TSTAMP(c == 0, 21); TSTAMP(c == 1, 26);
            if (c == 0) mbar_arrive(bar(B_ZERO));
            asm volatile("mbarrier.arrive.shared::cluster.b64 _, [%0];\nmbarrier.arrive.shared::cluster.b64 _, [%1];"
                         :: "r"(mapa(bar(B_OFREE), 0)), "r"(mapa(bar(B_OFREE), 1)) : "memory");
            asm volatile("fence.release.gpu;\nst.relaxed.gpu.global.u32 [%0], %1;\nmbarrier.arrive.shared::cluster.b64 _, [%2];"
                         :: "l"(&P.g->oflag[r * 32 + 2 * j + c]), "r"(epoch + 1), "r"(mapa(bar(B_RDY + c), rho ^ 1)) : "memory");
            TSTAMP(c == 0, 22); TSTAMP(c == 1, 23);
          }
          __syncwarp();
        }
      } else {
        const unsigned* fp = &P.g->oflag[r * 32 + (kcol(18 + min(lane, 13)) >> 6)];
        bool done = lane > 13 || lane < 2;
        mbar_wait_long(bar(B_OW), 0);
        for (int i = 0; !__all_sync(0xffffffffu, done) && i < kSpinLimit; i++) {
          const bool now = !done && (int)(ld_relaxed(fp) - epoch) > 0;
          if (__any_sync(0xffffffffu, now)) {
            asm volatile("fence.acquire.gpu;\nfence.proxy.async.global;" ::: "memory");
            mbar_arrive_if(bar(B_RDY + lane), now);
            TSTAMP(lane == 2 && now, 24);
          }
          done |= now;
        }
        if (lane == 0) P.g->epoch[cta] = epoch + 1;
        TSTAMP(lane == 0, 25);
      }
#pragma unroll 1
      for (int m = aw; m < 16; m += 3) {
        const int u = 4 * (m & 7) + 2 * (m >> 3);
        mbar_wait_long(bar(B_Y + (m >> 3)), 0);
        TSTAMP(at == 0 && m == 0, 20);
        const uint32_t t0 = clock32();
        const uint32_t qa = sb + RA + u * 1024 + lane * 32 + ((rho ^ 1 ^ (lane >> 2)) & 1) * 16, ya = sb + Y_IN + u * 512 + lane * 16;
        uint32_t qv[2][4], yv[2][4];
#pragma unroll
        for (int h = 0; h < 2; h++) { lds128(qv[h], qa + h * 1024); lds128(yv[h], ya + h * 512); }
#pragma unroll
        for (int h = 0; h < 2; h++) sts128(qa + h * 1024, bmul2(qv[h][0], yv[h][0]), bmul2(qv[h][1], yv[h][1]), bmul2(qv[h][2], yv[h][2]), bmul2(qv[h][3], yv[h][3]));
        fence_async_smem();
        __syncwarp();
        if (elect()) tma5d_store(&P.outb, sb + RA + u * 1024, 1024 + 16 * cl, 2 * rho, (u >> 4) * 4 + (u & 3), (u >> 2) & 3);
        if (m < PSW) pace(t0, POSTGAP);
      }
      bulk_wait_read();
      TSTAMP(at == 0, 27);
    }
  }
  TSTAMP(tid == 128, 61); GSTAMP(tid == 128, 63);
}

typedef CUresult (*EncodeFn)(CUtensorMap*, CUtensorMapDataType, cuuint32_t, void*, const cuuint64_t*, const cuuint64_t*,
                             const cuuint32_t*, const cuuint32_t*, CUtensorMapInterleave, CUtensorMapSwizzle,
                             CUtensorMapL2promotion, CUtensorMapFloatOOBfill);

void encode(EncodeFn fn, CUtensorMap* m, const void* p, int rank, const cuuint64_t* dims, const cuuint64_t* strides,
            const cuuint32_t* box, CUtensorMapSwizzle sw) {
  const cuuint32_t es[5] = {1, 1, 1, 1, 1};
  fn(m, CU_TENSOR_MAP_DATA_TYPE_BFLOAT16, rank, const_cast<void*>(p), dims, strides, box, es, CU_TENSOR_MAP_INTERLEAVE_NONE, sw,
     CU_TENSOR_MAP_L2_PROMOTION_NONE, CU_TENSOR_MAP_FLOAT_OOB_FILL_NONE);
}
void encode2d(EncodeFn fn, CUtensorMap* m, const void* p, uint64_t cols, uint64_t rows, uint32_t bc, uint32_t br, CUtensorMapSwizzle sw) {
  const cuuint64_t dims[2] = {cols, rows}, strides[1] = {cols * 2};
  const cuuint32_t box[2] = {bc, br};
  encode(fn, m, p, 2, dims, strides, box, sw);
}
void encode3d(EncodeFn fn, CUtensorMap* m, const void* p) {
  const cuuint64_t dims[3] = {1024, 64, 32}, strides[2] = {2048 * 32, 2048};
  const cuuint32_t box[3] = {16, 32, 4};
  encode(fn, m, p, 3, dims, strides, box, CU_TENSOR_MAP_SWIZZLE_32B);
}
void encode4d(EncodeFn fn, CUtensorMap* m, const void* p, uint64_t cols, uint32_t rows, uint32_t nmat) {
  const cuuint64_t dims[4] = {64, 1024, 16, cols / 1024}, strides[3] = {cols * 2, 128, 2048};
  const cuuint32_t box[4] = {64, rows, 2, nmat};
  encode(fn, m, p, 4, dims, strides, box, CU_TENSOR_MAP_SWIZZLE_128B);
}
void encode5d(EncodeFn fn, CUtensorMap* m, const void* p, uint64_t cols, uint32_t n, uint32_t nw) {
  const cuuint64_t dims[5] = {cols, 4, 16, 8, 4}, strides[4] = {cols * 2 * 512, cols * 2 * 8, cols * 2, cols * 2 * 128};
  const cuuint32_t box[5] = {16, 2, 16, n, nw};
  encode(fn, m, p, 5, dims, strides, box, CU_TENSOR_MAP_SWIZZLE_32B);
}

}

extern "C" void kernel_launch(void* const* d_in, const int* in_sizes, int n_in, void* d_out, int out_size) {
  static EncodeFn fn = nullptr;
  static void *o_ptr = nullptr, *g_ptr = nullptr, *tab_ptr = nullptr;
  if (!fn) {
    cudaDriverEntryPointQueryResult qr;
    cudaGetDriverEntryPoint("cuTensorMapEncodeTiled", (void**)&fn, cudaEnableDefault, &qr);
    cudaGetSymbolAddress(&o_ptr, g_o);
    cudaGetSymbolAddress(&g_ptr, g_scratch);
    cudaGetSymbolAddress(&tab_ptr, d_tab);
    cudaFuncSetAttribute(fused_kernel, cudaFuncAttributeMaxDynamicSharedMemorySize, SM_TOTAL);
  }
  Params P;
  encode4d(fn, &P.w1, d_in[1], 3072, 32, 2);
  encode2d(fn, &P.x, d_in[0], 1024, 2048, 64, 64, CU_TENSOR_MAP_SWIZZLE_128B);
  encode4d(fn, &P.w2, d_in[1], 3072, 64, 1);
  encode4d(fn, &P.wo, d_in[2], 1024, 64, 1);
  encode2d(fn, &P.o, o_ptr, 1024, 2048, 64, 64, CU_TENSOR_MAP_SWIZZLE_128B);
  encode2d(fn, &P.outa, d_out, 2048, 2048, 64, 16, CU_TENSOR_MAP_SWIZZLE_128B);
  encode3d(fn, &P.k, d_in[4]);
  encode3d(fn, &P.v, d_in[5]);
  encode5d(fn, &P.q, d_in[3], 1024, 4, 2);
  encode5d(fn, &P.outb, d_out, 2048, 2, 1);
  P.shift_k = (const __nv_bfloat16*)d_in[6];
  P.ssm_k = (const __nv_bfloat16*)d_in[7];
  P.ssm_d = (const __nv_bfloat16*)d_in[8];
  P.q_ptr = (const __nv_bfloat16*)d_in[3];
  P.w_ptr = (const __nv_bfloat16*)d_in[1];
  P.wo_ptr = (const __nv_bfloat16*)d_in[2];
  P.zero = 0;
  P.g = (Scratch*)g_ptr;
  P.tab = (const uint32_t*)tab_ptr;
  fused_kernel<<<kCtas, kThreads, SM_TOTAL>>>(P);
}
```

```cpp
#include <cuda.h>
#include <cuda_runtime.h>
#include <cuda_bf16.h>
#include <stdint.h>

#define DEVI __device__ __forceinline__
#define INL __attribute__((always_inline))

namespace {

DEVI void mma_kt_init(float* d, uint64_t da, uint64_t db) {
  asm volatile("{\nwgmma.mma_async.sync.aligned.m64n128k16.f32.bf16.bf16 {%0, %1, %2, %3, %4, %5, %6, %7, %8, %9, %10, %11, %12, %13, %14, %15, %16, %17, %18, %19, %20, %21, %22, %23, %24, %25, %26, %27, %28, %29, %30, %31, %32, %33, %34, %35, %36, %37, %38, %39, %40, %41, %42, %43, %44, %45, %46, %47, %48, %49, %50, %51, %52, %53, %54, %55, %56, %57, %58, %59, %60, %61, %62, %63}, %64, %65, 0, 1, 1, 1, 0;\n}\n"
    : "=f"(d[0]), "=f"(d[1]), "=f"(d[2]), "=f"(d[3]), "=f"(d[4]), "=f"(d[5]), "=f"(d[6]), "=f"(d[7]), "=f"(d[8]), "=f"(d[9]), "=f"(d[10]), "=f"(d[11]), "=f"(d[12]), "=f"(d[13]), "=f"(d[14]), "=f"(d[15]), "=f"(d[16]), "=f"(d[17]), "=f"(d[18]), "=f"(d[19]), "=f"(d[20]), "=f"(d[21]), "=f"(d[22]), "=f"(d[23]), "=f"(d[24]), "=f"(d[25]), "=f"(d[26]), "=f"(d[27]), "=f"(d[28]), "=f"(d[29]), "=f"(d[30]), "=f"(d[31]), "=f"(d[32]), "=f"(d[33]), "=f"(d[34]), "=f"(d[35]), "=f"(d[36]), "=f"(d[37]), "=f"(d[38]), "=f"(d[39]), "=f"(d[40]), "=f"(d[41]), "=f"(d[42]), "=f"(d[43]), "=f"(d[44]), "=f"(d[45]), "=f"(d[46]), "=f"(d[47]), "=f"(d[48]), "=f"(d[49]), "=f"(d[50]), "=f"(d[51]), "=f"(d[52]), "=f"(d[53]), "=f"(d[54]), "=f"(d[55]), "=f"(d[56]), "=f"(d[57]), "=f"(d[58]), "=f"(d[59]), "=f"(d[60]), "=f"(d[61]), "=f"(d[62]), "=f"(d[63])
    : "l"(da), "l"(db));
}
DEVI void mma_kt(float* d, uint64_t da, uint64_t db) {
  asm volatile("{\nwgmma.mma_async.sync.aligned.m64n128k16.f32.bf16.bf16 {%0, %1, %2, %3, %4, %5, %6, %7, %8, %9, %10, %11, %12, %13, %14, %15, %16, %17, %18, %19, %20, %21, %22, %23, %24, %25, %26, %27, %28, %29, %30, %31, %32, %33, %34, %35, %36, %37, %38, %39, %40, %41, %42, %43, %44, %45, %46, %47, %48, %49, %50, %51, %52, %53, %54, %55, %56, %57, %58, %59, %60, %61, %62, %63}, %64, %65, 1, 1, 1, 1, 0;\n}\n"
    : "+f"(d[0]), "+f"(d[1]), "+f"(d[2]), "+f"(d[3]), "+f"(d[4]), "+f"(d[5]), "+f"(d[6]), "+f"(d[7]), "+f"(d[8]), "+f"(d[9]), "+f"(d[10]), "+f"(d[11]), "+f"(d[12]), "+f"(d[13]), "+f"(d[14]), "+f"(d[15]), "+f"(d[16]), "+f"(d[17]), "+f"(d[18]), "+f"(d[19]), "+f"(d[20]), "+f"(d[21]), "+f"(d[22]), "+f"(d[23]), "+f"(d[24]), "+f"(d[25]), "+f"(d[26]), "+f"(d[27]), "+f"(d[28]), "+f"(d[29]), "+f"(d[30]), "+f"(d[31]), "+f"(d[32]), "+f"(d[33]), "+f"(d[34]), "+f"(d[35]), "+f"(d[36]), "+f"(d[37]), "+f"(d[38]), "+f"(d[39]), "+f"(d[40]), "+f"(d[41]), "+f"(d[42]), "+f"(d[43]), "+f"(d[44]), "+f"(d[45]), "+f"(d[46]), "+f"(d[47]), "+f"(d[48]), "+f"(d[49]), "+f"(d[50]), "+f"(d[51]), "+f"(d[52]), "+f"(d[53]), "+f"(d[54]), "+f"(d[55]), "+f"(d[56]), "+f"(d[57]), "+f"(d[58]), "+f"(d[59]), "+f"(d[60]), "+f"(d[61]), "+f"(d[62]), "+f"(d[63])
    : "l"(da), "l"(db));
}
DEVI void mma_n128_init(float* d, uint64_t da, uint64_t db) {
  asm volatile("{\nwgmma.mma_async.sync.aligned.m64n128k16.f32.bf16.bf16 {%0, %1, %2, %3, %4, %5, %6, %7, %8, %9, %10, %11, %12, %13, %14, %15, %16, %17, %18, %19, %20, %21, %22, %23, %24, %25, %26, %27, %28, %29, %30, %31, %32, %33, %34, %35, %36, %37, %38, %39, %40, %41, %42, %43, %44, %45, %46, %47, %48, %49, %50, %51, %52, %53, %54, %55, %56, %57, %58, %59, %60, %61, %62, %63}, %64, %65, 0, 1, 1, 0, 1;\n}\n"
    : "=f"(d[0]), "=f"(d[1]), "=f"(d[2]), "=f"(d[3]), "=f"(d[4]), "=f"(d[5]), "=f"(d[6]), "=f"(d[7]), "=f"(d[8]), "=f"(d[9]), "=f"(d[10]), "=f"(d[11]), "=f"(d[12]), "=f"(d[13]), "=f"(d[14]), "=f"(d[15]), "=f"(d[16]), "=f"(d[17]), "=f"(d[18]), "=f"(d[19]), "=f"(d[20]), "=f"(d[21]), "=f"(d[22]), "=f"(d[23]), "=f"(d[24]), "=f"(d[25]), "=f"(d[26]), "=f"(d[27]), "=f"(d[28]), "=f"(d[29]), "=f"(d[30]), "=f"(d[31]), "=f"(d[32]), "=f"(d[33]), "=f"(d[34]), "=f"(d[35]), "=f"(d[36]), "=f"(d[37]), "=f"(d[38]), "=f"(d[39]), "=f"(d[40]), "=f"(d[41]), "=f"(d[42]), "=f"(d[43]), "=f"(d[44]), "=f"(d[45]), "=f"(d[46]), "=f"(d[47]), "=f"(d[48]), "=f"(d[49]), "=f"(d[50]), "=f"(d[51]), "=f"(d[52]), "=f"(d[53]), "=f"(d[54]), "=f"(d[55]), "=f"(d[56]), "=f"(d[57]), "=f"(d[58]), "=f"(d[59]), "=f"(d[60]), "=f"(d[61]), "=f"(d[62]), "=f"(d[63])
    : "l"(da), "l"(db));
}
DEVI void mma_n128(float* d, uint64_t da, uint64_t db) {
  asm volatile("{\nwgmma.mma_async.sync.aligned.m64n128k16.f32.bf16.bf16 {%0, %1, %2, %3, %4, %5, %6, %7, %8, %9, %10, %11, %12, %13, %14, %15, %16, %17, %18, %19, %20, %21, %22, %23, %24, %25, %26, %27, %28, %29, %30, %31, %32, %33, %34, %35, %36, %37, %38, %39, %40, %41, %42, %43, %44, %45, %46, %47, %48, %49, %50, %51, %52, %53, %54, %55, %56, %57, %58, %59, %60, %61, %62, %63}, %64, %65, 1, 1, 1, 0, 1;\n}\n"
    : "+f"(d[0]), "+f"(d[1]), "+f"(d[2]), "+f"(d[3]), "+f"(d[4]), "+f"(d[5]), "+f"(d[6]), "+f"(d[7]), "+f"(d[8]), "+f"(d[9]), "+f"(d[10]), "+f"(d[11]), "+f"(d[12]), "+f"(d[13]), "+f"(d[14]), "+f"(d[15]), "+f"(d[16]), "+f"(d[17]), "+f"(d[18]), "+f"(d[19]), "+f"(d[20]), "+f"(d[21]), "+f"(d[22]), "+f"(d[23]), "+f"(d[24]), "+f"(d[25]), "+f"(d[26]), "+f"(d[27]), "+f"(d[28]), "+f"(d[29]), "+f"(d[30]), "+f"(d[31]), "+f"(d[32]), "+f"(d[33]), "+f"(d[34]), "+f"(d[35]), "+f"(d[36]), "+f"(d[37]), "+f"(d[38]), "+f"(d[39]), "+f"(d[40]), "+f"(d[41]), "+f"(d[42]), "+f"(d[43]), "+f"(d[44]), "+f"(d[45]), "+f"(d[46]), "+f"(d[47]), "+f"(d[48]), "+f"(d[49]), "+f"(d[50]), "+f"(d[51]), "+f"(d[52]), "+f"(d[53]), "+f"(d[54]), "+f"(d[55]), "+f"(d[56]), "+f"(d[57]), "+f"(d[58]), "+f"(d[59]), "+f"(d[60]), "+f"(d[61]), "+f"(d[62]), "+f"(d[63])
    : "l"(da), "l"(db));
}
DEVI void mma_kv_init(float* d, const uint32_t* a, uint64_t db, uint32_t meta) {
  asm volatile("{\nwgmma.mma_async.sp.sync.aligned.m64n40k32.f32.bf16.bf16 {%0, %1, %2, %3, %4, %5, %6, %7, %8, %9, %10, %11, %12, %13, %14, %15, %16, %17, %18, %19}, {%20,%21,%22,%23}, %24, %25, 0, 0, 1, 1, 1;\n}\n"
    : "=f"(d[0]), "=f"(d[1]), "=f"(d[2]), "=f"(d[3]), "=f"(d[4]), "=f"(d[5]), "=f"(d[6]), "=f"(d[7]), "=f"(d[8]), "=f"(d[9]), "=f"(d[10]), "=f"(d[11]), "=f"(d[12]), "=f"(d[13]), "=f"(d[14]), "=f"(d[15]), "=f"(d[16]), "=f"(d[17]), "=f"(d[18]), "=f"(d[19])
    : "r"(a[0]), "r"(a[1]), "r"(a[2]), "r"(a[3]), "l"(db), "r"(meta));
}
DEVI void mma_kv(float* d, const uint32_t* a, uint64_t db, uint32_t meta) {
  asm volatile("{\nwgmma.mma_async.sp.sync.aligned.m64n40k32.f32.bf16.bf16 {%0, %1, %2, %3, %4, %5, %6, %7, %8, %9, %10, %11, %12, %13, %14, %15, %16, %17, %18, %19}, {%20,%21,%22,%23}, %24, %25, 0, 1, 1, 1, 1;\n}\n"
    : "+f"(d[0]), "+f"(d[1]), "+f"(d[2]), "+f"(d[3]), "+f"(d[4]), "+f"(d[5]), "+f"(d[6]), "+f"(d[7]), "+f"(d[8]), "+f"(d[9]), "+f"(d[10]), "+f"(d[11]), "+f"(d[12]), "+f"(d[13]), "+f"(d[14]), "+f"(d[15]), "+f"(d[16]), "+f"(d[17]), "+f"(d[18]), "+f"(d[19])
    : "r"(a[0]), "r"(a[1]), "r"(a[2]), "r"(a[3]), "l"(db), "r"(meta));
}
DEVI void mma_o_init(float* d, const uint32_t* a, uint64_t db) {
  asm volatile("{\nwgmma.mma_async.sync.aligned.m64n40k16.f32.bf16.bf16 {%0, %1, %2, %3, %4, %5, %6, %7, %8, %9, %10, %11, %12, %13, %14, %15, %16, %17, %18, %19}, {%20,%21,%22,%23}, %24, 0, 1, 1, 1;\n}\n"
    : "=f"(d[0]), "=f"(d[1]), "=f"(d[2]), "=f"(d[3]), "=f"(d[4]), "=f"(d[5]), "=f"(d[6]), "=f"(d[7]), "=f"(d[8]), "=f"(d[9]), "=f"(d[10]), "=f"(d[11]), "=f"(d[12]), "=f"(d[13]), "=f"(d[14]), "=f"(d[15]), "=f"(d[16]), "=f"(d[17]), "=f"(d[18]), "=f"(d[19])
    : "r"(a[0]), "r"(a[1]), "r"(a[2]), "r"(a[3]), "l"(db));
}
DEVI void mma_o(float* d, const uint32_t* a, uint64_t db) {
  asm volatile("{\nwgmma.mma_async.sync.aligned.m64n40k16.f32.bf16.bf16 {%0, %1, %2, %3, %4, %5, %6, %7, %8, %9, %10, %11, %12, %13, %14, %15, %16, %17, %18, %19}, {%20,%21,%22,%23}, %24, 1, 1, 1, 1;\n}\n"
    : "+f"(d[0]), "+f"(d[1]), "+f"(d[2]), "+f"(d[3]), "+f"(d[4]), "+f"(d[5]), "+f"(d[6]), "+f"(d[7]), "+f"(d[8]), "+f"(d[9]), "+f"(d[10]), "+f"(d[11]), "+f"(d[12]), "+f"(d[13]), "+f"(d[14]), "+f"(d[15]), "+f"(d[16]), "+f"(d[17]), "+f"(d[18]), "+f"(d[19])
    : "r"(a[0]), "r"(a[1]), "r"(a[2]), "r"(a[3]), "l"(db));
}
DEVI void mma_s1_init(uint32_t* d, const uint32_t* a, uint64_t db) {
  asm volatile("{\nwgmma.mma_async.sync.aligned.m64n128k16.f16.f16.f16 {%0, %1, %2, %3, %4, %5, %6, %7, %8, %9, %10, %11, %12, %13, %14, %15, %16, %17, %18, %19, %20, %21, %22, %23, %24, %25, %26, %27, %28, %29, %30, %31}, {%32,%33,%34,%35}, %36, 0, 1, 1, 1;\n}\n"
    : "=r"(d[0]), "=r"(d[1]), "=r"(d[2]), "=r"(d[3]), "=r"(d[4]), "=r"(d[5]), "=r"(d[6]), "=r"(d[7]), "=r"(d[8]), "=r"(d[9]), "=r"(d[10]), "=r"(d[11]), "=r"(d[12]), "=r"(d[13]), "=r"(d[14]), "=r"(d[15]), "=r"(d[16]), "=r"(d[17]), "=r"(d[18]), "=r"(d[19]), "=r"(d[20]), "=r"(d[21]), "=r"(d[22]), "=r"(d[23]), "=r"(d[24]), "=r"(d[25]), "=r"(d[26]), "=r"(d[27]), "=r"(d[28]), "=r"(d[29]), "=r"(d[30]), "=r"(d[31])
    : "r"(a[0]), "r"(a[1]), "r"(a[2]), "r"(a[3]), "l"(db));
}
DEVI void mma_s1(uint32_t* d, const uint32_t* a, uint64_t db) {
  asm volatile("{\nwgmma.mma_async.sync.aligned.m64n128k16.f16.f16.f16 {%0, %1, %2, %3, %4, %5, %6, %7, %8, %9, %10, %11, %12, %13, %14, %15, %16, %17, %18, %19, %20, %21, %22, %23, %24, %25, %26, %27, %28, %29, %30, %31}, {%32,%33,%34,%35}, %36, 1, 1, 1, 1;\n}\n"
    : "+r"(d[0]), "+r"(d[1]), "+r"(d[2]), "+r"(d[3]), "+r"(d[4]), "+r"(d[5]), "+r"(d[6]), "+r"(d[7]), "+r"(d[8]), "+r"(d[9]), "+r"(d[10]), "+r"(d[11]), "+r"(d[12]), "+r"(d[13]), "+r"(d[14]), "+r"(d[15]), "+r"(d[16]), "+r"(d[17]), "+r"(d[18]), "+r"(d[19]), "+r"(d[20]), "+r"(d[21]), "+r"(d[22]), "+r"(d[23]), "+r"(d[24]), "+r"(d[25]), "+r"(d[26]), "+r"(d[27]), "+r"(d[28]), "+r"(d[29]), "+r"(d[30]), "+r"(d[31])
    : "r"(a[0]), "r"(a[1]), "r"(a[2]), "r"(a[3]), "l"(db));
}
DEVI void mma_s2_init(uint32_t* d, const uint32_t* a, uint64_t db) {
  asm volatile("{\nwgmma.mma_async.sync.aligned.m64n32k16.f16.f16.f16 {%0, %1, %2, %3, %4, %5, %6, %7}, {%8,%9,%10,%11}, %12, 0, 1, 1, 0;\n}\n"
    : "=r"(d[0]), "=r"(d[1]), "=r"(d[2]), "=r"(d[3]), "=r"(d[4]), "=r"(d[5]), "=r"(d[6]), "=r"(d[7])
    : "r"(a[0]), "r"(a[1]), "r"(a[2]), "r"(a[3]), "l"(db));
}
DEVI void mma_s2(uint32_t* d, const uint32_t* a, uint64_t db) {
  asm volatile("{\nwgmma.mma_async.sync.aligned.m64n32k16.f16.f16.f16 {%0, %1, %2, %3, %4, %5, %6, %7}, {%8,%9,%10,%11}, %12, 1, 1, 1, 0;\n}\n"
    : "+r"(d[0]), "+r"(d[1]), "+r"(d[2]), "+r"(d[3]), "+r"(d[4]), "+r"(d[5]), "+r"(d[6]), "+r"(d[7])
    : "r"(a[0]), "r"(a[1]), "r"(a[2]), "r"(a[3]), "l"(db));
}
DEVI void mma_s2_neg(uint32_t* d, const uint32_t* a, uint64_t db) {
  asm volatile("{\nwgmma.mma_async.sync.aligned.m64n32k16.f16.f16.f16 {%0, %1, %2, %3, %4, %5, %6, %7}, {%8,%9,%10,%11}, %12, 1, -1, 1, 0;\n}\n"
    : "+r"(d[0]), "+r"(d[1]), "+r"(d[2]), "+r"(d[3]), "+r"(d[4]), "+r"(d[5]), "+r"(d[6]), "+r"(d[7])
    : "r"(a[0]), "r"(a[1]), "r"(a[2]), "r"(a[3]), "l"(db));
}
DEVI void mma_i2_init(float* d, const uint32_t* a, uint64_t db, uint32_t meta) {
  asm volatile("{\nwgmma.mma_async.sp.sync.aligned.m64n128k32.f32.f16.f16 {%0, %1, %2, %3, %4, %5, %6, %7, %8, %9, %10, %11, %12, %13, %14, %15, %16, %17, %18, %19, %20, %21, %22, %23, %24, %25, %26, %27, %28, %29, %30, %31, %32, %33, %34, %35, %36, %37, %38, %39, %40, %41, %42, %43, %44, %45, %46, %47, %48, %49, %50, %51, %52, %53, %54, %55, %56, %57, %58, %59, %60, %61, %62, %63}, {%64,%65,%66,%67}, %68, %69, 0, 0, 1, 1, 1;\n}\n"
    : "=f"(d[0]), "=f"(d[1]), "=f"(d[2]), "=f"(d[3]), "=f"(d[4]), "=f"(d[5]), "=f"(d[6]), "=f"(d[7]), "=f"(d[8]), "=f"(d[9]), "=f"(d[10]), "=f"(d[11]), "=f"(d[12]), "=f"(d[13]), "=f"(d[14]), "=f"(d[15]), "=f"(d[16]), "=f"(d[17]), "=f"(d[18]), "=f"(d[19]), "=f"(d[20]), "=f"(d[21]), "=f"(d[22]), "=f"(d[23]), "=f"(d[24]), "=f"(d[25]), "=f"(d[26]), "=f"(d[27]), "=f"(d[28]), "=f"(d[29]), "=f"(d[30]), "=f"(d[31]), "=f"(d[32]), "=f"(d[33]), "=f"(d[34]), "=f"(d[35]), "=f"(d[36]), "=f"(d[37]), "=f"(d[38]), "=f"(d[39]), "=f"(d[40]), "=f"(d[41]), "=f"(d[42]), "=f"(d[43]), "=f"(d[44]), "=f"(d[45]), "=f"(d[46]), "=f"(d[47]), "=f"(d[48]), "=f"(d[49]), "=f"(d[50]), "=f"(d[51]), "=f"(d[52]), "=f"(d[53]), "=f"(d[54]), "=f"(d[55]), "=f"(d[56]), "=f"(d[57]), "=f"(d[58]), "=f"(d[59]), "=f"(d[60]), "=f"(d[61]), "=f"(d[62]), "=f"(d[63])
    : "r"(a[0]), "r"(a[1]), "r"(a[2]), "r"(a[3]), "l"(db), "r"(meta));
}
DEVI void mma_i2(float* d, const uint32_t* a, uint64_t db, uint32_t meta) {
  asm volatile("{\nwgmma.mma_async.sp.sync.aligned.m64n128k32.f32.f16.f16 {%0, %1, %2, %3, %4, %5, %6, %7, %8, %9, %10, %11, %12, %13, %14, %15, %16, %17, %18, %19, %20, %21, %22, %23, %24, %25, %26, %27, %28, %29, %30, %31, %32, %33, %34, %35, %36, %37, %38, %39, %40, %41, %42, %43, %44, %45, %46, %47, %48, %49, %50, %51, %52, %53, %54, %55, %56, %57, %58, %59, %60, %61, %62, %63}, {%64,%65,%66,%67}, %68, %69, 0, 1, 1, 1, 1;\n}\n"
    : "+f"(d[0]), "+f"(d[1]), "+f"(d[2]), "+f"(d[3]), "+f"(d[4]), "+f"(d[5]), "+f"(d[6]), "+f"(d[7]), "+f"(d[8]), "+f"(d[9]), "+f"(d[10]), "+f"(d[11]), "+f"(d[12]), "+f"(d[13]), "+f"(d[14]), "+f"(d[15]), "+f"(d[16]), "+f"(d[17]), "+f"(d[18]), "+f"(d[19]), "+f"(d[20]), "+f"(d[21]), "+f"(d[22]), "+f"(d[23]), "+f"(d[24]), "+f"(d[25]), "+f"(d[26]), "+f"(d[27]), "+f"(d[28]), "+f"(d[29]), "+f"(d[30]), "+f"(d[31]), "+f"(d[32]), "+f"(d[33]), "+f"(d[34]), "+f"(d[35]), "+f"(d[36]), "+f"(d[37]), "+f"(d[38]), "+f"(d[39]), "+f"(d[40]), "+f"(d[41]), "+f"(d[42]), "+f"(d[43]), "+f"(d[44]), "+f"(d[45]), "+f"(d[46]), "+f"(d[47]), "+f"(d[48]), "+f"(d[49]), "+f"(d[50]), "+f"(d[51]), "+f"(d[52]), "+f"(d[53]), "+f"(d[54]), "+f"(d[55]), "+f"(d[56]), "+f"(d[57]), "+f"(d[58]), "+f"(d[59]), "+f"(d[60]), "+f"(d[61]), "+f"(d[62]), "+f"(d[63])
    : "r"(a[0]), "r"(a[1]), "r"(a[2]), "r"(a[3]), "l"(db), "r"(meta));
}
__device__ const __align__(128) uint32_t d_tab[2944] = {
  0x3bf13bff,0x2fbd25e4,0x38ee3986,0x3a4d39c9,0x3b9a3bcf,0x34ff32f7,0x3737384a,0x3b243ac1,0x3af73b52,0x37dd3676,0x344b35c8,0x3bb53b76,
  0x3a113a8c,0x39373899,0x2cce3185,0x3bfa3be1,0x3a933bf2,0x388e2f59,0xb1b6b8f8,0xbbdfba45,0xa452374e,0x3c003b1e,0x39c034e7,0xb990bb9e,
  0xbabab7c8,0x38553afe,0x3bd23bb2,0x32c6b463,0xbb57bbf9,0xb65f2d33,0x35df3a19,0x3b71392e,0x37643bd4,0x3b183294,0xb4cf385f,0x3ba13ab3,
  0xbbaeb648,0x347b3b5c,0xbb04bb6c,0xb7b235f7,0xad97ba9b,0xbbf8b884,0x3924b1e8,0xba21bbdd,0x3bf439b8,0x2ef5b999,0x39023c00,0x3a3d217f,
  0x9cb63ba5,0x3c0034b7,0x39afb77a,0xb9a1bb13,0xb86abbab,0xbaac3493,0xb2633b0a,0x3bd7379b,0x3b60391b,0x3631ba29,0xb60ebbf7,0xbb682dfb,
  0xbbdaae91,0x32193bf5,0x3aa23a35,0x387ab90c,0xb7853b65,0x3b10361a,0xbba73625,0x34ab3b63,0x3911baa9,0xba31b86f,0x3bf6b24b,0xae5fbbd8,
  0xba2d39aa,0x391639a6,0xbbf61648,0xae2d3c00,0x3b0db874,0xb790baa5,0x3ba93232,0x349fbbd9,0xba9e3b16,0x387f376f,0x3bdcb4c3,0x3201bba3,
  0x3b6aaec3,0x3602bbf5,0xb63cb907,0xbb5e3a39,0xb27cba25,0xbbd6391f,0xb8653bf8,0x3ab02dc9,0xb99d3bac,0x39b33487,0x3c00b7a6,0x9fdbbb07,
  0xbbf33ab6,0x2f27385a,0xba4132ad,0xb8fd3bd3,0xad653994,0x3bf9b9bc,0xba1d3c00,0x3929a311,0x3bb0b889,0x346fba97,0x37bd31cf,0x3b01bbde,
  0x3759bb59,0xbb1b3654,0x3b9fbb6f,0xb4dbb5eb,0xbb733a49,0xb5d438f3,0x366baf8b,0x3b54bbf2,0xbbd03bfa,0x32de2d00,0x3abdb933,0x3850ba15,
  0xb98b3afb,0x39c5b7d2,0x3c00bbb3,0xa51bb457,0xb19e3742,0x3be0bb21,0x3a90bb9c,0xb89434f3,0xb93c39cd,0xba0d3982,0x2c9c26ad,0xbbfb3bff,
  0xb7e8389e,0xbaf43a89,0x343eb16c,0xbbb73be2,0xb50b3682,0xbb983b4f,0x372cb5bc,0xbb273b78,0xafef330f,0xbbf03bce,0x38eab845,0xba503ac4,
  0xb3403946,0xbbcb3a04,0xb83a2c38,0x3acbbbfc,0x3979b426,0xb9d63bba,0xbbff3aee,0x281fb7fe,0x3be4bb94,0x313b3523,0xb8a83b2c,0xba813715,
  0x3699ba58,0x3b4ab8e0,0x35a53029,0xbb7c3bef,0x340e38b2,0xbbbd3a7a,0x3ae8b109,0xb80a3be6,0x3b32bb45,0x36ff36af,0x353abb81,0x3b90b58d,
  0xb8d6b371,0x3a60bbc8,0xbbed3830,0x305bbad1,0xb94f3bfe,0xb9fca8e8,0x2ba739df,0xbbfc3970,0x39663815,0xb9e73ae1,0xbbfe33eb,0x29b1bbc0,
  0xb0d7bb37,0x3be8b6e8,0x3a733552,0xb8bc3b8b,0xb6c63beb,0xbb3fb08d,0xb576ba67,0x3b85b8cc,0x3ad8b9f4,0x38253958,0xb3a23bfd,0xbbc52ade,
  0x3b8736dd,0xb56a3b3a,0x3b3db55e,0x36d23b89,0xbbe9b3d3,0x30bebbc2,0xba6f381a,0xb8c1bade,0x3bfe2a7a,0x2a163bfd,0x3962b95d,0x39eb39f0,
  0xbbc330a6,0xb3babbea,0xb8203a6b,0xbadbb8c7,0x3bec3581,0x30743b83,0xb8d136bb,0xba64bb42,0xb6f438b7,0xbb35ba76,0xb546bbe7,0x3b8e30f0,
  0xb80fbbfe,0x3ae5a94d,0x3bbf396b,0xb40239e3,0x3bfd382a,0xab433ad5,0xb9f83389,0xb954bbc6,0x3a7e341a,0x38ad3bbc,0x3122b805,0x3be53aeb,
  0x39da3bfc,0xb974ac06,0x3bff3a00,0x2884394a,0xb8353042,0xbacebbee,0x33593a5c,0xbbc9b8db,0xbb7fbb92,0x3599b52f,0xbb47b70a,0xb6a4bb2f,
  0x37213153,0x3b2a3be3,0x351738a3,0xbb96ba85,0x3af1397d,0x37f339d2,0xb4322776,0xbbb8bbff,0x3bfb3bcc,0xac6a3328,0xba09b840,0xb941bac7,
  0x3a543b7a,0xb8e5b5b1,0xbbefbb4c,0xb010b68d,0x32f72fbd,0xbbcfbbf1,0x3ac13a4d,0xb84ab8ee,0x367634ff,0xbb52bb9a,0x3b763b24,0xb5c8b737,
  0x389937dd,0xba8cbaf7,0x3be13bb5,0xb185b44b,0x39c93937,0xb986ba11,0x3bff3bfa,0x25e4acce,0x392e32c6,0xba19bbd2,0xbbf9baba,0x2d333855,
  0x3bf23b71,0x2f59b5df,0xb8f8bb57,0xba45b65f,0x374e3a93,0x3b1e388e,0x34e7b1b6,0xbb9ebbdf,0xb7c8a452,0x3afe3c00,0x3bb239c0,0xb463b990,
  0x3b6c34cf,0xb5f7bba1,0x3b5c3b18,0x3648b764,0x31e83b04,0x3bdd37b2,0xb884347b,0x3a9b3bae,0xbc00b924,0xa17f3a21,0xb999bbf8,0xb9b82d97,
  0x3294b902,0xbbd4ba3d,0x3ab32ef5,0xb85fbbf4,0x3bf53631,0x2e91bb60,0xb90cbb68,0xba35360e,0xbb133219,0x377a3bda,0x3ba5387a,0x34b7baa2,
  0x379bb9a1,0xbb0ab9af,0xbbab9cb6,0x34933c00,0x2dfb3bd7,0x3bf73263,0x391bb86a,0xba29baac,0x3aa93785,0x386fbb10,0x324b3ba7,0x3bd8b4ab,
  0xb9aab911,0xb9a63a31,0x9648bbf6,0xbc002e5f,0x38743a2d,0x3aa5b916,0xb2323bf6,0x3bd92e2d,0xb625bb0d,0xbb633790,0x361abba9,0xbb65b49f,
  0x37a63865,0x3b07bab0,0x3487bbd6,0xbbac327c,0x376fbc00,0xbb161fdb,0xbba339b3,0x34c3399d,0xbbf5387f,0x2ec33a9e,0x3a393201,0x3907bbdc,
  0x391f3602,0x3a25bb6a,0x2dc9bb5e,0xbbf8363c,0x231138fd,0x3c00ba41,0xb9943bf3,0x39bcaf27,0x3bdeb929,0x31cfba1d,0x38892d65,0x3a97bbf9,
  0x35ebbb01,0xbb6f37bd,0x3b59bbb0,0xb654b46f,0xbab634db,0xb85a3b9f,0xb2adb759,0xbbd33b1b,0xb742398b,0x3b21b9c5,0x3b9cbc00,0xb4f3251b,
  0x2f8b319e,0x3bf2bbe0,0x38f3ba90,0xba493894,0x3933b66b,0x3a15bb54,0x2d00b5d4,0xbbfa3b73,0x3bb3babd,0x3457b850,0xb7d232de,0xbafb3bd0,
  0xba893a0d,0x389eb93c,0xbbe23bfb,0xb16c2c9c,0xbb4f3af4,0x3682b7e8,0xbb783bb7,0xb5bc343e,0xbbce3b98,0x330fb50b,0xbac43b27,0xb845372c,
  0xbbff3bf0,0x26adafef,0xb9cd3a50,0xb98238ea,0xbbef3a81,0x3029b8a8,0x3a58bbe4,0x38e0b13b,0xb9463b7c,0xba0435a5,0xac38b699,0x3bfcbb4a,
  0x34263340,0xbbba3bcb,0xbaee383a,0x37febacb,0x3b94b979,0xb52339d6,0xbb2c3bff,0xb715a81f,0xbb813ae8,0xb58db80a,0xb6af3bbd,0xbb45340e,
  0x3830353a,0xbad13b90,0x3bc8b6ff,0xb3713b32,0x39dfbbed,0x3970305b,0x28e8ba60,0x3bfeb8d6,0xba7a2ba7,0x38b2bbfc,0xbbe639fc,0xb109b94f,
  0xb9583b3f,0xb9f4b6c6,0xaadebb85,0x3bfdb576,0x3bc0b825,0x33eb3ad8,0xb8153bc5,0xbae1b3a2,0xbb8ba9b1,0x3552bbfe,0x3b37b966,0x36e839e7,
  0x38cc38bc,0xba673a73,0xbbeb30d7,0x308dbbe8,0xb3d33b87,0xbbc2b56a,0x381a3b3d,0xbade36d2,0x2a7abbe9,0x3bfd30be,0xb95dba6f,0x39f0b8c1,
  0x30a63bfe,0xbbea2a16,0x3a6b3962,0xb8c739eb,0xb55ebbc3,0x3b89b3ba,0xbb3ab820,0x36ddbadb,0x33893bbf,0xbbc6b402,0xbad5bae5,0x382ab80f,
  0xbb83b9f8,0x3581b954,0x3b422b43,0x36bb3bfd,0x3a76b074,0x38b73bec,0xb0f03a64,0xbbe7b8d1,0x294d3b35,0xbbfeb6f4,0xb9e3bb8e,0x396bb546,
  0x394a3be5,0xba00b122,0x3bfc3a7e,0xac0638ad,0xb8db2884,0xba5cbbff,0x304239da,0xbbeeb974,0xbb2fbbc9,0x370ab359,0xbb92b835,0xb52fbace,
  0x341ab6a4,0x3bbc3b47,0xb805bb7f,0x3aeb3599,0x3b7a3bfb,0xb5b1ac6a,0xbb4cba09,0xb68db941,0x38a33a54,0xba85b8e5,0xbbe3bbef,0x3153b010,
  0x27763517,0xbbffbb96,0xb9d2bb2a,0x397d3721,0xb840b432,0xbac7bbb8,0xb328b7f3,0x3bcc3af1,0x3be23bfb,0x316c2c9c,0x389e393c,0x3a893a0d,
  0x3b783bb7,0x35bc343e,0x368237e8,0x3b4f3af4,0x3ac43b27,0x3845372c,0x330f350b,0x3bce3b98,0x39cd3a50,0x398238ea,0x26ad2fef,0x3bff3bf0,
  0x39463b7c,0x3a0435a5,0x2c38b699,0xbbfcbb4a,0xb4263340,0x3bba3bcb,0x3aee383a,0xb7febacb,0xbb94b979,0x352339d6,0x3b2c3bff,0x3715a81f,
  0xba58bbe4,0xb8e0b13b,0x302938a8,0x3bef3a81,0x28e83a60,0x3bfe38d6,0xb970305b,0x39df3bed,0xbbe6b9fc,0xb109394f,0xb8b2bbfc,0xba7aaba7,
  0x358db80a,0xbb81bae8,0x3b45340e,0xb6afbbbd,0x3ad13b90,0x3830b53a,0x33713b32,0x3bc836ff,0xb8cc38bc,0x3a673a73,0x3beb30d7,0xb08dbbe8,
  0x2adebb85,0xbbfdb576,0xb9f436c6,0x39583b3f,0x38153bc5,0x3ae1b3a2,0x33ebbad8,0xbbc0b825,0xbb37b966,0xb6e839e7,0x35523bfe,0x3b8ba9b1,
  0xbbc2356a,0x33d33b87,0xbadeb6d2,0xb81a3b3d,0x3bfdb0be,0xaa7abbe9,0x39f038c1,0x395dba6f,0xbbeaaa16,0xb0a63bfe,0xb8c7b9eb,0xba6b3962,
  0x3b8933ba,0x355ebbc3,0x36dd3adb,0x3b3ab820,0xbb422b43,0xb6bb3bfd,0x35813954,0x3b83b9f8,0x30f03a64,0x3be7b8d1,0x38b7bbec,0xba76b074,
  0x39e3bb8e,0xb96bb546,0xbbfe36f4,0xa94d3b35,0xbbc63402,0xb3893bbf,0x382a380f,0x3ad5bae5,0xb70ab359,0xbb2f3bc9,0x352fbace,0xbb923835,
  0xbbbc3b47,0x341a36a4,0xbaeb3599,0xb8053b7f,0x2c0638ad,0x3bfcba7e,0xb94a3be5,0x3a00b122,0x3beeb974,0x3042b9da,0x38db2884,0x3a5cbbff,
  0x3328b7f3,0xbbcc3af1,0xbac73bb8,0x3840b432,0xb5b12c6a,0xbb7a3bfb,0xb68d3941,0x3b4cba09,0xba8538e5,0xb8a33a54,0x31533010,0x3be3bbef,
  0xbbff3b96,0xa7763517,0x397db721,0x39d2bb2a,0x3a4db9c9,0xb8ee3986,0x3bf1bbff,0x2fbda5e4,0x3b24bac1,0xb737384a,0x3b9abbcf,0x34ffb2f7,
  0x3bb5bb76,0xb44b35c8,0x3af7bb52,0x37ddb676,0x3bfabbe1,0xacce3185,0x3a11ba8c,0x3937b899,0x3c00bb1e,0x2452374e,0xb9903b9e,0xb9c034e7,
  0x3855bafe,0x3abab7c8,0x32c63463,0xbbd23bb2,0xb65fad33,0x3b57bbf9,0x3b71b92e,0xb5df3a19,0xbbdf3a45,0x31b6b8f8,0x3a93bbf2,0x388eaf59,
  0x3a21bbdd,0x392431e8,0x2d97ba9b,0x3bf8b884,0xba3d217f,0x3902bc00,0xbbf439b8,0xaef5b999,0xb7643bd4,0xbb183294,0x34cf385f,0xbba13ab3,
  0x3baeb648,0xb47b3b5c,0x3b04bb6c,0x37b235f7,0x3219bbf5,0x3bdaae91,0x387a390c,0xbaa23a35,0xb9a13b13,0xb9afb77a,0x9cb6bba5,0x3c00b4b7,
  0x3bd7b79b,0x32633b0a,0xb86a3bab,0xbaacb493,0xbb68adfb,0x360ebbf7,0x3b60b91b,0x36313a29,0xb785bb65,0x3b10b61a,0xbba7b625,0x34abbb63,
  0x39113aa9,0xba31386f,0x3bf6324b,0xae5f3bd8,0xba2db9aa,0x3916b9a6,0xbbf69648,0xae2dbc00,0x3b0d3874,0xb7903aa5,0x3ba9b232,0x349f3bd9,
  0xbb5eba39,0x363cb907,0x3b6a2ec3,0x36023bf5,0x3ab0adc9,0x38653bf8,0xb27c3a25,0xbbd6b91f,0x9fdb3b07,0xbc00b7a6,0xb99dbbac,0x39b3b487,
  0xba9ebb16,0x387fb76f,0x3bdc34c3,0x32013ba3,0xbbb0b889,0xb46fba97,0xb7bd31cf,0xbb01bbde,0xb759bb59,0x3b1b3654,0xbb9fbb6f,0x34dbb5eb,
  0x3a4132ad,0x38fd3bd3,0x2f27b85a,0x3bf33ab6,0x3a1d3c00,0xb929a311,0x3bf939bc,0x2d653994,0xb894b4f3,0xba90bb9c,0xb19eb742,0x3be03b21,
  0xbb73ba49,0xb5d4b8f3,0x366b2f8b,0x3b543bf2,0xbbd0bbfa,0x32dead00,0x3abd3933,0x38503a15,0xb98bbafb,0x39c537d2,0x3c003bb3,0xa51b3457,
  0xb43eb16c,0x3bb73be2,0xbaf4ba89,0x37e8389e,0xb72cb5bc,0x3b273b78,0xbb98bb4f,0x350b3682,0xb8eab845,0x3a503ac4,0xbbf0bbce,0x2fef330f,
  0xba0db982,0x393c39cd,0xbbfbbbff,0xac9c26ad,0xba81b715,0x38a83b2c,0x3be43b94,0x313bb523,0xbb7cbbef,0xb5a53029,0x36993a58,0x3b4a38e0,
  0xb340b946,0xbbcbba04,0xb83aac38,0x3acb3bfc,0x39793426,0xb9d6bbba,0xbbffbaee,0x281f37fe,0xbbfcb970,0xaba739df,0xb94fbbfe,0xb9fc28e8,
  0x340eb8b2,0xbbbdba7a,0x3ae83109,0xb80abbe6,0x3b323b45,0x36ffb6af,0x353a3b81,0x3b90358d,0xb8d63371,0x3a603bc8,0xbbedb830,0x305b3ad1,
  0xb9e7bae1,0xb9663815,0x29b13bc0,0x3bfe33eb,0x3be836e8,0x30d7bb37,0xb8bcbb8b,0xba733552,0xbb3f308d,0x36c63beb,0x3b8538cc,0x3576ba67,
  0x3825b958,0xbad8b9f4,0xbbc5aade,0x33a23bfd,0xb0bebbc2,0xbbe933d3,0x38c1bade,0xba6fb81a,0xaa163bfd,0x3bfeaa7a,0xb9eb39f0,0x3962395d,
  0x33babbea,0xbbc3b0a6,0x3adbb8c7,0xb820ba6b,0xb6d23b89,0x3b3d355e,0xbb8736dd,0x356a3b3a,0x380fbbfe,0xbae5a94d,0xbbbf396b,0x340239e3,
  0xbbfd382a,0x2b433ad5,0x39f83389,0x3954bbc6,0x38d136bb,0x3a64bb42,0x3074bb83,0xbbec3581,0x3546bbe7,0xbb8e30f0,0xbb353a76,0x36f438b7,
  0x3b7fbb92,0xb599b52f,0x3b47b70a,0x36a4bb2f,0xb122b805,0xbbe53aeb,0x38adbbbc,0xba7e341a,0xbbff3a00,0xa884394a,0xb9742c06,0xb9da3bfc,
  0xb3593a5c,0x3bc9b8db,0xbace3bee,0x38353042,0x3b96ba85,0x3517b8a3,0xb7213153,0xbb2a3be3,0x3bb8bbff,0xb432a776,0xbaf1397d,0xb7f339d2,
  0x3941bac7,0xba093840,0xbbfb3bcc,0x2c6a3328,0x3010b68d,0xbbef3b4c,0xba543b7a,0x38e5b5b1,0x384ab8ee,0x3ac1ba4d,0xb2f72fbd,0x3bcfbbf1,
  0x35c8b737,0x3b76bb24,0xb67634ff,0x3b52bb9a,0x3185b44b,0x3be1bbb5,0xb89937dd,0x3a8cbaf7,0xa5e4acce,0x3bffbbfa,0xb9c93937,0x3986ba11,
  0xaf59b5df,0x3bf2bb71,0x3a45b65f,0xb8f83b57,0xbb1e388e,0x374eba93,0x3b9ebbdf,0x34e731b6,0xbafe3c00,0xb7c82452,0x3463b990,0x3bb2b9c0,
  0xad333855,0xbbf93aba,0xb92e32c6,0x3a19bbd2,0xb9b8ad97,0x3999bbf8,0xbc003924,0xa17fba21,0xb85f3bf4,0xbab32ef5,0x32943902,0xbbd43a3d,
  0x3b6cb4cf,0xb5f73ba1,0x3b5cbb18,0x36483764,0x31e8bb04,0x3bddb7b2,0xb884b47b,0x3a9bbbae,0xbbf73263,0x2dfbbbd7,0x3a29baac,0x391b386a,
  0x3a35360e,0xb90c3b68,0xbbf53631,0xae91bb60,0xb4b7baa2,0x3ba5b87a,0x3b133219,0xb77a3bda,0xb4933c00,0xbbab1cb6,0xb79bb9a1,0x3b0ab9af,
  0xbaa93785,0xb86fbb10,0xb24b3ba7,0xbbd8b4ab,0x39aab911,0x39a63a31,0x1648bbf6,0x3c002e5f,0xb8743a2d,0xbaa5b916,0x32323bf6,0xbbd92e2d,
  0x3625bb0d,0x3b633790,0xb61abba9,0x3b65b49f,0xb4c3399d,0xbba3b9b3,0xb76fbc00,0x3b161fdb,0xb907bbdc,0x3a39b201,0x3bf5387f,0xaec33a9e,
  0x3bf8363c,0x2dc93b5e,0xb91f3602,0xba25bb6a,0xb7a63865,0xbb07bab0,0xb487bbd6,0x3bac327c,0x35eb3b01,0xbb6fb7bd,0x3b593bb0,0xb654346f,
  0xbab6b4db,0xb85abb9f,0xb2ad3759,0xbbd3bb1b,0xb994bbf3,0x39bc2f27,0xbc00ba41,0x2311b8fd,0x3889ad65,0x3a973bf9,0xb1cfba1d,0x3bde3929,
  0x3afb3bd0,0xb7d2b2de,0xbbb3babd,0xb457b850,0x3742398b,0xbb21b9c5,0xbb9cbc00,0x34f3251b,0xaf8b319e,0xbbf2bbe0,0xb8f3ba90,0x3a493894,
  0xb933b66b,0xba15bb54,0xad00b5d4,0x3bfa3b73,0x211b21e4,0xa51ba5e4,0x98b69248,0x1cb61648,0x1f122052,0xa311a452,0x9d7f9bdb,0x217f1fdb,
  0x1bdb1d7f,0x9fdba17f,0xa0529f12,0x24522311,0x124818b6,0x96489cb6,0xa1e4a11b,0x25e4251b,0x2a632b5f,0xae5faf59,0xa1e49bdb,0x25e41fdb,
  0x286b2967,0xac6aad65,0xa6e0a4e9,0x2ade28e8,0x24e926e0,0xa8e8aade,0xa967a86b,0x2d652c6a,0x1bdb21e4,0x9fdba5e4,0xab5faa63,0x2f592e5f,
  0x2dc22ea7,0xb1b6b294,0xa54d9f12,0x294d2311,0x2bf62cde,0xafefb0d7,0xaa31a86b,0x2e2d2c6a,0x286b2a31,0xac6aae2d,0xacdeabf6,0x30d72fef,
  0x1f12254d,0xa311a94d,0xaea7adc2,0x329431b6,0x302c30d2,0xb41ab4b7,0xa7a9a11b,0x2ba7251b,0x2dc22f0c,0xb1b6b2f7,0xac79aa63,0x30742e5f,
  0x2a632c79,0xae5fb074,0xaf0cadc2,0x32f731b6,0x211b27a9,0xa51baba7,0xb0d2b02c,0x34b7341a,0x317a3257,0xb552b61a,0xa902a2ad,0x2d0026ad,
  0x2f8c309f,0xb371b487,0xaddcac2e,0x31cf3029,0x2c2e2ddc,0xb029b1cf,0xb09faf8c,0x34873371,0x22ad2902,0xa6adad00,0xb257b17a,0x361a3552,
  0x32cd33e3,0xb682b76f,0xaa31a420,0x2e2d281f,0x30ac31bb,0xb493b58d,0xaf3fad2a,0x33283122,0x2d2a2f3f,0xb122b328,0xb1bbb0ac,0x358d3493,
  0x24202a31,0xa81fae2d,0xb3e3b2cd,0x376f3682,0x341334bc,0xb7a6b85a,0xab5fa4e9,0x2f5928e8,0x319432da,0xb56ab68d,0xb052ae28,0x343e3219,
  0x2e283052,0xb219b43e,0xb2dab194,0x368d356a,0x24e92b5f,0xa8e8af59,0xb4bcb413,0x385a37a6,0x34c3358c,0xb85fb8f3,0xac47a5b2,0x304229b1,
  0x327e33fd,0xb63cb785,0xb106af26,0x34e7330f,0x2f263106,0xb30fb4e7,0xb3fdb27e,0x3785363c,0x25b22c47,0xa9b1b042,0xb58cb4c3,0x38f3385f,
  0x35773662,0xb8e5b982,0xacdea67b,0x30d72a7a,0x336b3493,0xb70ab83a,0xb1bbb012,0x358d3402,0x301231bb,0xb402b58d,0xb493b36b,0x383a370a,
  0x267b2cde,0xaa7ab0d7,0xb662b577,0x398238e5,0x36303741,0xb962ba04,0xad76a744,0x316c2b43,0x342e352a,0xb7d2b8ad,0xb271b092,0x3631347b,
  0x30923271,0xb47bb631,0xb52ab42e,0x38ad37d2,0x27442d76,0xab43b16c,0xb741b630,0x3a043962,0x36ee3815,0xb9d6ba7a,0xae0ea807,0x32012c06,
  0x34a735c4,0xb84ab91b,0xb329b113,0x36d234f3,0x31133329,0xb4f3b6d2,0xb5c4b4a7,0x391b384a,0x28072e0e,0xac06b201,0xb815b6ee,0x3a7a39d6,
  0x37b4388e,0xba41bae1,0xaea7a86b,0x32942c6a,0x35233662,0xb8a8b982,0xb3e3b194,0x376f356a,0x319433e3,0xb56ab76f,0xb662b523,0x398238a8,
  0x286b2ea7,0xac6ab294,0xb88eb7b4,0x3ae13a41,0x3841390f,0xbaa2bb3a,0xaf3fa8d0,0x33282cce,0x35a13705,0xb902b9e3,0xb44fb216,0x380535df,
  0x3216344f,0xb5dfb805,0xb705b5a1,0x39e33902,0x28d02f3f,0xacceb328,0xb90fb841,0x3b3a3aa2,0x38ac3997,0xbaf7bb83,0xafd8a935,0x33ba2d33,
  0x362137ac,0xb958ba3d,0xb4aeb298,0x38503654,0x329834ae,0xb654b850,0xb7acb621,0x3a3d3958,0x29352fd8,0xad33b3ba,0xb997b8ac,0x3b833af7,
  0x391c3a28,0xbb42bbbc,0xb039a999,0x34262d97,0x36a4382d,0xb9aaba90,0xb50eb31c,0x389936c6,0x331c350e,0xb6c6b899,0xb82db6a4,0x3a9039aa,
  0x29993039,0xad97b426,0xba28b91c,0x3bbc3b42,0x39923ac3,0xbb81bbe3,0xb085a9fe,0x346f2dfb,0x372a3886,0xb9f8badb,0xb570b3a0,0x38e03737,
  0x33a03570,0xb737b8e0,0xb886b72a,0x3adb39f8,0x29fe3085,0xadfbb46f,0xbac3b992,0x3be33b81,0xb9cfbb16,0x3b9c3bf1,0x30ac2a31,0xb493ae2d,
  0xb76fb8b4,0x3a1d3afe,0x35a133e3,0xb902b76f,0xb3e3b5a1,0x376f3902,0x38b4376f,0xbafeba1d,0xaa31b0ac,0x2e2d3493,0x3b1639cf,0xbbf1bb9c,
  0xb956ba74,0x3b633bd2,0x305f29cc,0xb44badc9,0xb6e7b859,0x39d23ab6,0x353f335e,0xb8bcb6ff,0xb35eb53f,0x36ff38bc,0x385936e7,0xbab6b9d2,
  0xa9ccb05f,0x2dc9344b,0x3a743956,0xbbd2bb63,0xb8e3b9de,0x3b1e3ba1,0x30122967,0xb402ad65,0xb662b801,0x39823a67,0x34de32da,0xb874b68d,
  0xb2dab4de,0x368d3874,0x38013662,0xba67b982,0xa967b012,0x2d653402,0x39de38e3,0xbba1bb1e,0xb876b952,0x3ace3b60,0x2f8c2902,0xb371ad00,
  0xb5e1b758,0x392e3a11,0x347e3257,0xb82ab61a,0xb257b47e,0x361a382a,0x375835e1,0xba11b92e,0xa902af8c,0x2d003371,0x39523876,0xbb60bace,
  0xb80db8ce,0x3a733b10,0x2ef3289e,0xb2deac9c,0xb562b6b3,0x38d639b3,0x342031d5,0xb7bdb5a5,0xb1d5b420,0x35a537bd,0x36b33562,0xb9b3b8d6,
  0xa89eaef3,0x2c9c32de,0x38ce380d,0xbb10ba73,0xb750b851,0x3a0d3ab0,0x2e5a2839,0xb24bac38,0xb4e5b613,0x387a394f,0x33863153,0xb721b52f,
  0xb153b386,0x352f3721,0x361334e5,0xb94fb87a,0xa839ae5a,0x2c38324b,0x38513750,0xbab0ba0d,0xb68eb7b4,0x399d3a41,0x2dc227a9,0xb1b6aba7,
  0xb46ab577,0x381a38e5,0x32cd30d2,0xb682b4b7,0xb0d2b2cd,0x34b73682,0x3577346a,0xb8e5b81a,0xa7a9adc2,0x2ba731b6,0x37b4368e,0xba41b99d,
  0xb5d2b6d1,0x392439c5,0x2d2a26e0,0xb122aade,0xb3e3b4de,0x376f3874,0x32163052,0xb5dfb43e,0xb052b216,0x343e35df,0x34de33e3,0xb874b76f,
  0xa6e0ad2a,0x2ade3122,0x36d135d2,0xb9c5b924,0xb51cb5f6,0x38a3393c,0x2c932617,0xb08daa16,0xb2f4b448,0x36a437fe,0x31602fa5,0xb53ab389,
  0xafa5b160,0x3389353a,0x344832f4,0xb7feb6a4,0xa617ac93,0x2a16308d,0x35f6351c,0xb93cb8a3,0xb46ab523,0x381a38a8,0x2bf6254d,0xafefa94d,
  0xb209b36b,0x35d4370a,0x30ac2ea7,0xb493b294,0xaea7b0ac,0x32943493,0x336b3209,0xb70ab5d4,0xa54dabf6,0x294d2fef,0x3523346a,0xb8a8b81a,
  0xb378b456,0x3715380a,0x2ac82484,0xaec3a884,0xb120b24a,0x34ff360e,0x2ff22da9,0xb3d3b19e,0xada9aff2,0x319e33d3,0x324a3120,0xb60eb4ff,
  0xa484aac8,0x28842ec3,0x34563378,0xb80ab715,0xb223b31c,0x35eb36c6,0x29992376,0xad97a776,0xb039b12d,0x3426350b,0x2e8d2cac,0xb27cb0a6,
  0xacacae8d,0x30a6327c,0x312d3039,0xb50bb426,0xa376a999,0x27762d97,0x331c3223,0xb6c6b5eb,0xb0d2b194,0x34b7356a,0x286b21e4,0xac6aa5e4,
  0xaea7b012,0x32943402,0x2d2a2b5f,0xb122af59,0xab5fad2a,0x2f593122,0x30122ea7,0xb402b294,0xa1e4a86b,0x25e42c6a,0x319430d2,0xb56ab4b7,
  0xaf0cb012,0x32f73402,0x267b2052,0xaa7aa452,0xacdeadf5,0x30d731e8,0x2b912967,0xaf8bad65,0xa967ab91,0x2d652f8b,0x2df52cde,0xb1e8b0d7,
  0xa052a67b,0x24522a7a,0x30122f0c,0xb402b2f7,0xac79ad2a,0x30743122,0x24201d7f,0xa81fa17f,0xaa31ab91,0x2e2d2f8b,0x28d026e0,0xacceaade,
  0xa6e0a8d0,0x2ade2cce,0x2b912a31,0xaf8bae2d,0x9d7fa420,0x217f281f,0x2d2a2c79,0xb122b074,0xa7a9a86b,0x2ba72c6a,0x1f1218b6,0xa3119cb6,
  0xa54da67b,0x294d2a7a,0x242021e4,0xa81fa5e4,0xa1e4a420,0x25e4281f,0x267b254d,0xaa7aa94d,0x98b69f12,0x1cb62311,0x286b27a9,0xac6aaba7,
  0xa5e43bff,0xb61a3b65,0xb98239cd,0xbb3a36dd,0xaf593bf2,0xb76f3b16,0xba043946,0xbb833581,0xb2943bd4,0xb85a3ab6,0xba7a38b2,0xbbbc341a,
  0xb4b73ba5,0xb8f33a49,0xbae13815,0xbbe33153,0xac9c3bfb,0xbb87356a,0xb986b9c9,0x361abb65,0xb5a53b7c,0xbbfd2b43,0xb74ebb1e,0x3907ba39,
  0xb8d63a60,0xbbc9b359,0xb1e8bbdd,0x3a97b889,0xba7338bc,0xbaf1b7f3,0x2e91bbf5,0x3b9cb4f3,0xafbd3bf1,0xbb10b785,0x3a0db93c,0x356a3b87,
  0xb88e3a93,0xb87fba9e,0x3bcbb340,0xb0743bec,0xbb183764,0xaf27bbf3,0x3bbd340e,0xb8ad3a7e,0xbc009cb6,0x35d4bb73,0x39e73966,0xbb2a3721,
  0xb16c3be2,0xb3d3bbc2,0x38ee3a4d,0xbb10b785,0xba043946,0x36bbbb42,0xa4523c00,0xb63cbb5e,0xbbfe28e8,0x3b2fb70a,0xb9243a21,0x346fbbb0,
  0xba67b8cc,0x3bcc3328,0xbbda3219,0x3a90b894,0xb2f73bcf,0x386fbaa9,0xba89389e,0x3bc2b3d3,0xbb1e374e,0x3bf5aec3,0xbbbab426,0x3a7638b7,
  0xbb5cb648,0x39bc3994,0xb6afbb45,0x2c063bfc,0xb493bbab,0xad003bfa,0x36e8bb37,0xb9d2397d,0xb43e3bb7,0x3be9b0be,0xb84abac1,0xb86f3aa9,
  0xbbcb3340,0x38d13a64,0x37c8bafe,0xbbf8adc9,0xb94fb9fc,0xb6a43b47,0x3c00217f,0xb654bb59,0x3576bb85,0xbbfb2c6a,0x377a3b13,0x38f3ba49,
  0xb4ff3b9a,0x3a313911,0x3af4b7e8,0xb0bebbe9,0xbc00a452,0xb6023b6a,0x39d63979,0x3b35b6f4,0xb47bbbae,0xbbf9ad65,0xb6ff3b32,0x397439da,
  0x3aacb86a,0xb2debbd0,0xbbe8b0d7,0xb7f33af1,0xb5bc3b78,0x2a7a3bfd,0x37373b24,0x3a313911,0xbbbab426,0xbbe730f0,0xbaba3855,0xb8653ab0,
  0x3109bbe6,0xb41abbbc,0xb902ba3d,0xbb1bb759,0x3bfd2ade,0x3b7ab5b1,0x39afb9a1,0x35d4bb73,0xb6763b52,0xb9a639aa,0xbb4f3682,0xbbfd2a7a,
  0xbafeb7c8,0xb91fba25,0xb523bb94,0x294dbbfe,0x3884ba9b,0x3a97b889,0x3bc8b371,0x3bee3042,0x3a29391b,0x37d23afb,0x308d3beb,0xb3283bcc,
  0xb72c3b27,0xbbfeaa16,0xb5c8bb76,0x39a6b9aa,0xb9d6b979,0x3546bb8e,0x3bf9ad33,0x37a63b07,0x3ae8b80a,0x3a7e38ad,0xb2943bd4,0xbbd332ad,
  0x33a23bc5,0xba5438e5,0xbb0ab79b,0x2d00bbfa,0xb7dd3af7,0xb916ba2d,0x3b98b50b,0xaa163bfe,0xb855baba,0x3bd6b27c,0xb13b3be4,0xbae5b80f,
  0x3bf8ad97,0xb46f3bb0,0xba60b8d6,0x3aceb835,0xb6313b60,0xb9c5b98b,0x3b3fb6c6,0x2c6a3bfb,0xb8453ac4,0x30a6bbea,0x344b3bb5,0xb916ba2d,
  0xb523bb94,0x396b39e3,0xbb57b65f,0x3c009fdb,0x3b81358d,0xbbfc2c06,0x3b18b764,0xb8fd3a41,0xbae13815,0x38a3ba85,0xb2633bd7,0xb2debbd0,
  0xb8993a8c,0x3aa5b874,0xbbce330f,0x3bea30a6,0xad33bbf9,0xb4873bac,0x38e0ba58,0xbad5382a,0x399939b8,0xb654bb59,0x28e83bfe,0x352fbb92,
  0xbbf5ae91,0x3b213742,0xb958b9f4,0x35b13b7a,0xb8ea3a50,0x3bc333ba,0xb185bbe1,0xbaa53874,0x313bbbe4,0xbbbf3402,0x38f83a45,0x376fbb16,
  0x353a3b90,0x39dab974,0xbb5cb648,0x23113c00,0xb9e7b966,0xb5173b96,0x3bf7adfb,0xb7d2bafb,0xb9373a11,0x37903b0d,0x3bf0afef,0x33babbc3,
  0x365fbb57,0xb9b3b99d,0xbb4a3699,0x2b433bfd,0xaef53bf4,0x3b1b3759,0x39fcb94f,0xb599bb7f,0xb219bbda,0xbbe0b19e,0xb8253ad8,0x38e53a54,
  0xb98239cd,0xb55e3b89,0x2cce3bfa,0x37903b0d,0x38e0ba58,0x3389bbc6,0xb1b6bbdf,0xb87fba9e,0xb8303ad1,0xb0423bee,0x347b3bae,0x39293a1d,
  0x36e8bb37,0x2776bbff,0xb60ebb68,0xb9c5b98b,0xb9c93986,0xbb633625,0xbbff26ad,0xbb89b55e,0x3a45b8f8,0x3ba3b4c3,0x3bfc2c38,0x3b4236bb,
  0xbab3385f,0xbbd332ad,0xbbe6b109,0xbaebb805,0x3b13b77a,0x3bf2af8b,0x3bc033eb,0x3a8538a3,0xba0d393c,0xbb3db6d2,0x25e4bbff,0x3b63b625,
  0x3b4ab699,0x39f83954,0xb4e73b9e,0xbbf52ec3,0xbbed305b,0xb835bace,0x3884ba9b,0x3bde31cf,0x3be830d7,0x34323bb8,0xba35390c,0xbb21b742,
  0xba4d38ee,0xb4abbba7,0x3bfb2c9c,0xb6d23b3d,0x3bdfb1b6,0xb2013bdc,0xbacbb83a,0x3a64b8d1,0xbba1b4cf,0x38fdba41,0x380a3ae8,0xbbe53122,
  0x39a139af,0xbb54366b,0xa9b1bbfe,0x3b963517,0xba89389e,0x381abade,0xafbd3bf1,0xb4abbba7,0x3bfc2c38,0xbb833581,0x39c0b990,0xb6023b6a,
  0xb9dfb970,0x3b92352f,0xbbf82d97,0x3b01b7bd,0x308d3beb,0xb840bac7,0x3aa2387a,0xbbe0b19e,0xbac1384a,0x3bd8b24b,0xbbe2b16c,0x3ade381a,
  0x3b9e34e7,0xba39b907,0x37fe3aee,0xb0f0bbe7,0xb5f7bb6c,0x23113c00,0x358dbb81,0xb94a3a00,0xb79b3b0a,0x3a15b933,0xbb8b3552,0x3bff2776,
  0xbaf437e8,0x3a6f38c1,0x32f7bbcf,0xbbd8324b,0x3acb383a,0x3074bbec,0xbbb23463,0x391f3a25,0x2ba7bbfc,0xbb7f3599,0x399939b8,0x35ebbb6f,
  0xbb3f36c6,0x3a093941,0x34b7bba5,0xbbf22f8b,0xbb243737,0x2e5f3bf6,0x3bb7343e,0x38c1ba6f,0x399039c0,0x3b5eb63c,0xa81fbbff,0xbb8eb546,
  0x37b2bb04,0xb929ba1d,0xbb90353a,0xa8843bff,0xbbd7b263,0xb8503abd,0x38bc3a73,0x3bb8b432,0xbb4f3682,0xb95d39f0,0xb4ff3b9a,0x2e5f3bf6,
  0x37fe3aee,0x3a7638b7,0x3bd232c6,0x3bd6b27c,0x3a7ab8b2,0x3805baeb,0x2ef5bbf4,0xb4dbbb9f,0xb958b9f4,0xbb4cb68d,0xbc009cb6,0xbb54366b,
  0xbb7635c8,0xbc001648,0xbb78b5bc,0xb9f0b95d,0x34633bb2,0xadc93bf8,0xb7153b2c,0xb9e3396b,0x3bddb1e8,0x3bde31cf,0x3ad13830,0x38db3a5c,
  0xadfbbbf7,0x3457bbb3,0x38ccba67,0x3ac7b840,0xbb98350b,0xb962b9eb,0x3676bb52,0x3c009648,0x281f3bff,0xbb3536f4,0xba19b92e,0x3487bbac,
  0x3bbd340e,0x31223be5,0xbab3385f,0xbab6b85a,0x3825bad8,0x3bef3010,0x34933bab,0xba153933,0xbbb5344b,0x2e2dbbf6,0x3b27372c,0xb9eb3962,
  0xb2c63bd2,0xbab0b865,0x3a81b8a8,0x34023bbf,0x3a213924,0xbb0137bd,0xb05bbbed,0x3bc93359,0x3b68b60e,0x251b3c00,0xbb85b576,0x3941ba09,
  0xbbce330f,0x3a6bb8c7,0xb7dd3af7,0x2e2dbbf6,0xb7153b2c,0x294dbbfe,0x35df3b71,0xb9b3b99d,0x36af3b45,0xba00b94a,0x3ba134cf,0xbbf32f27,
  0x3bc033eb,0xbbe33153,0x3aacb86a,0xb8503abd,0xbbe13185,0x3bd93232,0xbac4b845,0x38c73a6b,0xb92e3a19,0x3b07b7a6,0xbbef3029,0x3bc63389,
  0xa17f3c00,0x35ebbb6f,0xb97039df,0x3b2fb70a,0x390c3a35,0xb4f3bb9c,0xaade3bfd,0x368dbb4c,0xbbf02fef,0x38203adb,0x3899ba8c,0xbbd9b232,
  0xba8138a8,0x3ae5380f,0x2f59bbf2,0xbba334c3,0xb6ff3b32,0x3bff2884,0xb5f7bb6c,0xb99439bc,0x29b13bfe,0x3b2ab721,0xba29b91b,0xb4573bb3,
  0xbbfa2cce,0xb49f3ba9,0x3a5038ea,0x3adbb820,0xbb7135df,0x1fdb3c00,0x3b7c35a5,0x3954b9f8,0xba3d3902,0x34db3b9f,0x3bfc2ba7,0x36a4bb47,
  0xb87a3aa2,0x38943a90,0x3bc5b3a2,0x3010bbef,0xbbff26ad,0xbb3a36dd,0xb9373a11,0xb49f3ba9,0xbbef3029,0xbad5382a,0xb88e3a93,0xb2013bdc,
  0xbbc83371,0xba5c38db,0xb7b23b04,0xad653bf9,0xbb8b3552,0xb9d2397d,0xb6313b60,0x251b3c00,0x3bf12fbd,0x3b103785,0x393c3a0d,0x356a3b87,
  0x3bd232c6,0x3ab03865,0x38a83a81,0x34023bbf,0x3ba134cf,0x3a4138fd,0x380a3ae8,0x31223be5,0x3b603631,0x39c5398b,0x36c63b3f,0x2c6a3bfb,
  0xbbe2b16c,0xb3d3bbc2,0x3a4db8ee,0x3b103785,0xbb2cb715,0x294dbbfe,0x3b71b5df,0x39b3399d,0xb9dfb970,0x352fbb92,0x3bf8ad97,0x37bd3b01,
  0xb815bae1,0x38a3ba85,0x3bd73263,0x32de3bd0,0x3bcf32f7,0xb86f3aa9,0xb89eba89,0x3bc2b3d3,0x3a19392e,0xbb0737a6,0xb029bbef,0x3bc63389,
  0x35f73b6c,0xbc002311,0x358dbb81,0x3a00394a,0xae913bf5,0xbb21b742,0x39f4b958,0x35b13b7a,0xbbb7b43e,0x3be9b0be,0xbac1384a,0x386fbaa9,
  0xb8a8ba81,0x3ae5380f,0xbbf2af59,0x3ba3b4c3,0x2ba7bbfc,0x35993b7f,0xb999b9b8,0x3b6f35eb,0x3966b9e7,0xb5173b96,0xadfbbbf7,0x37d23afb,
  0x3b9a34ff,0xba31b911,0x37e83af4,0xb0bebbe9,0x35df3b71,0x9fdbbc00,0xb5a53b7c,0x3954b9f8,0xb7b23b04,0x3a1db929,0xbb90353a,0x3bff2884,
  0xbbda3219,0x3be0319e,0xbad8b825,0x38e53a54,0xbb78b5bc,0x2a7a3bfd,0x3b24b737,0xba31b911,0xb029bbef,0xbad5382a,0x3a93388e,0x3201bbdc,
  0x3a7ab8b2,0xbaebb805,0xaef53bf4,0x3b9fb4db,0x3b3736e8,0x2776bbff,0xbb68360e,0x39c5398b,0x3b523676,0x39a6b9aa,0xb682bb4f,0xbbfd2a7a,
  0xaf593bf2,0x3b16376f,0x3a04b946,0xb581bb83,0xbbdd31e8,0xb1cf3bde,0x3ad13830,0x3a5cb8db,0xb77abb13,0xbbf22f8b,0xb3eb3bc0,0x3a8538a3,
  0xbb27b72c,0xbbfeaa16,0xbb7635c8,0xb9a639aa,0x35a5bb7c,0xab43bbfd,0xb74ebb1e,0xba39b907,0x3bbd340e,0x3be5b122,0x3ab3b85f,0x385abab6,
  0xb0d73be8,0x34323bb8,0x390c3a35,0x3b213742,0x3af737dd,0x39163a2d,0x350b3b98,0xaa163bfe,0xb88e3a93,0xba9e387f,0xbbcb3340,0xbbecb074,
  0xba21b924,0xb7bdbb01,0xb05bbbed,0x3359bbc9,0x39afb9a1,0x3b54b66b,0x3bfea9b1,0x3b963517,0xbac4b845,0x30a6bbea,0x3bb5b44b,0x39163a2d,
  0x3a04b946,0x3b4236bb,0xa4523c00,0xbb5e363c,0x36af3b45,0xb94a3a00,0xbba1b4cf,0xaf27bbf3,0xbbeb308d,0xb840bac7,0x387abaa2,0x3be0319e,
  0x3a8c3899,0xbaa53874,0xb30fbbce,0x3bea30a6,0xbb1e374e,0xaec3bbf5,0x3bba3426,0xb8b73a76,0x217fbc00,0x3b6f35eb,0xb97039df,0xb70abb2f,
  0x3b0a379b,0xba153933,0xb552bb8b,0x3bff2776,0xba50b8ea,0x3bc333ba,0xbbe13185,0x3aa5b874,0x3bcbb340,0xba6438d1,0x37c8bafe,0xadc93bf8,
  0xb6ff3b32,0x2884bbff,0x35f73b6c,0xb9bcb994,0xb6c6bb3f,0x3a093941,0xbba5b4b7,0x3bf2af8b,0x3a113937,0xb790bb0d,0x2fef3bf0,0x33babbc3,
  0xbc00a452,0x3b6a3602,0xb9d6b979,0x36f43b35,0x3a3db902,0xbb9f34db,0x3bfc2ba7,0xbb47b6a4,0xb2633bd7,0x3850babd,0xba7338bc,0x3bb8b432,
  0xb9cdb982,0xb55e3b89,0x3bfaacce,0xb790bb0d,0x3bba3426,0xb0f0bbe7,0xbaba3855,0x3ab03865,0xbbc83371,0x38db3a5c,0x37b2bb04,0xbbf9ad65,
  0x39f4b958,0xbb4cb68d,0x9cb63c00,0x3b54b66b,0x398639c9,0x3b63b625,0xa6adbbff,0xbb89b55e,0xbafeb7c8,0xba25391f,0x35233b94,0x3bfe294d,
  0x3bd43294,0x385abab6,0xb8b2ba7a,0xbbbc341a,0xbbf72dfb,0xb4573bb3,0x3a6738cc,0x3ac7b840,0xb93cba0d,0xbb3db6d2,0xbbffa5e4,0xbb633625,
  0x39d63979,0x3b8e3546,0x3bf9ad33,0x3b07b7a6,0xba60b8d6,0xbbc9b359,0xbbdd31e8,0xba973889,0x3ad83825,0x3bef3010,0x3babb493,0x3a15b933,
  0x38ee3a4d,0x34ab3ba7,0xac9c3bfb,0xb6d23b3d,0xb855baba,0xb27cbbd6,0x313bbbe4,0x380fbae5,0x37643b18,0x2f273bf3,0xb40e3bbd,0xb8ad3a7e,
  0xb60ebb68,0xa51bbc00,0x3576bb85,0x3941ba09,0xb89eba89,0x381abade,0x3bf12fbd,0x34ab3ba7,0x35233b94,0xb9e3396b,0xbb57b65f,0x9fdbbc00,
  0xa8e8bbfe,0x3b2fb70a,0x3a213924,0xb46f3bb0,0xb3eb3bc0,0xbbe33153,0xb86abaac,0x3850babd,0x384a3ac1,0xbbd8324b,0x316cbbe2,0x3ade381a,
  0xad33bbf9,0x3bac3487,0xb8e03a58,0xb82abad5,0xb6483b5c,0xb9bcb994,0x3b45b6af,0x2c063bfc,0x3a35b90c,0x34f33b9c,0xbbfdaade,0x368dbb4c,
  0xb7e8baf4,0x3a6f38c1,0xbbcfb2f7,0x3bd8b24b,0xb13b3be4,0xb402bbbf,0x38f83a45,0xbb16b76f,0x39fcb94f,0xb6a43b47,0x217fbc00,0x36543b59,
  0xbbfe29b1,0x3b2ab721,0xb91b3a29,0x3457bbb3,0x37373b24,0xae5fbbf6,0xb43e3bb7,0x38c1ba6f,0x365fbb57,0xb99d39b3,0x3b4ab699,0xbbfd2b43,
  0xbbae347b,0x3bf92d65,0xbb32b6ff,0x397439da,0x3aa2387a,0xb894ba90,0x33a23bc5,0x3010bbef,0xb682bb4f,0xb95d39f0,0x3b9a34ff,0xae5fbbf6,
  0xb8e03a58,0x3bc63389,0xb1b6bbdf,0xba9e387f,0x3be63109,0xb41abbbc,0xba3d3902,0x3b1b3759,0xb552bb8b,0xb9d2397d,0x3b603631,0xa51bbc00,
  0x35c83b76,0x3c009648,0x35bcbb78,0xb9f0b95d,0x3a45b8f8,0xb4c3bba3,0xbbfcac38,0xb6bb3b42,0xba9bb884,0xba973889,0x33713bc8,0x3bee3042,
  0xb4b73ba5,0x3a4938f3,0x3ae1b815,0xb153bbe3,0xb50bbb98,0xb962b9eb,0xbb52b676,0xbc001648,0xbb4a3699,0xb95439f8,0xb4e73b9e,0x2ec33bf5,
  0x380a3ae8,0x3a7e38ad,0x3bd43294,0x3bd3b2ad,0x3a73b8bc,0x37f3baf1,0x2e91bbf5,0xb4f3bb9c,0x344b3bb5,0xae2d3bf6,0xb72c3b27,0xb9eb3962,
  0x3bdfb1b6,0x3bdc3201,0x3acb383a,0x38d13a64,0xad97bbf8,0x346fbbb0,0x38d6ba60,0x3aceb835,0xbc009cb6,0xbb73b5d4,0xb9e7b966,0xb721bb2a,
  0xb30fbbce,0x3a6bb8c7,0x3af737dd,0xae2d3bf6,0xbbfcac38,0xb581bb83,0x39c0b990,0x3b6a3602,0xb58d3b81,0xbbfc2c06,0xb764bb18,0x38fdba41,
  0x3a6738cc,0xb3283bcc,0xbbda3219,0xb894ba90,0x31853be1,0xbbd9b232,0x3845bac4,0x38c73a6b,0x3b9e34e7,0xb9073a39,0xb7febaee,0x3be7b0f0,
  0x39b8b999,0x36543b59,0xbbfe28e8,0x352fbb92,0xb493bbab,0x3bfa2d00,0xb6e83b37,0xb97db9d2,0xafefbbf0,0x38203adb,0xba8cb899,0x3bd93232,
  0xbacbb83a,0x3bec3074,0xbbb23463,0x3a25b91f,0xbb90353a,0x39dab974,0xb6483b5c,0xa311bc00,0xb5763b85,0xac6abbfb,0x377a3b13,0xba49b8f3,
  0x2cce3bfa,0x349fbba9,0xb8ea3a50,0x3adbb820,0x399039c0,0xb63cbb5e,0x281f3bff,0x3546bb8e,0x3bf42ef5,0xbb1bb759,0x394f39fc,0xb599bb7f,
  0x3aacb86a,0xbbd032de,0x3be830d7,0xbaf1b7f3,0xa6adbbff,0xbb3a36dd,0x3a113937,0x349fbba9,0xb7febaee,0xb8b73a76,0x3bd232c6,0xb27cbbd6,
  0xbad1b830,0xb0423bee,0x3baeb47b,0xb929ba1d,0xbbfdaade,0x35b13b7a,0x39afb9a1,0xbb73b5d4,0xa5e43bff,0x3b65361a,0x3982b9cd,0xb6ddbb3a,
  0x34633bb2,0x3bf82dc9,0x3715bb2c,0xb96bb9e3,0x385f3ab3,0x3bd3b2ad,0x3109bbe6,0xbaebb805,0x3a29391b,0x3afbb7d2,0xb08dbbeb,0xbbccb328,
  0x2c9cbbfb,0xb56abb87,0xb986b9c9,0xbb65b61a,0xa81fbbff,0xb6f4bb35,0xba19b92e,0xbbacb487,0xb05bbbed,0xb835bace,0xba9bb884,0xbbdeb1cf,
  0xb3a2bbc5,0xb8e5ba54,0xbb0ab79b,0xbbfaad00,0x00000000,0x00000000,0x00000000,0x00000000,0xaa1f0000,0xaf64ada8,0xaf64b000,0xaa1fada8,
  0xada80000,0xada8b000,0x2da88000,0x2da83000,0xaf640000,0x2a1fada8,0x2a1f3000,0xaf64ada8,0xb0000000,0x30008000,0xb0000000,0x30008000,
  0xaf640000,0x2a1f2da8,0x2a1fb000,0xaf642da8,0xada80000,0xada83000,0x2da88000,0x2da8b000,0xaa1f0000,0xaf642da8,0xaf643000,0xaa1f2da8,
  0x00000000,0x00000000,0x00000000,0x00000000,0x2a1f8000,0x2f642da8,0x2f643000,0x2a1f2da8,0xada80000,0xada8b000,0x2da88000,0x2da83000,
  0x2f648000,0xaa1f2da8,0xaa1fb000,0x2f642da8,0xb0000000,0x30008000,0xb0000000,0x30008000,0x2f648000,0xaa1fada8,0xaa1f3000,0x2f64ada8,
  0xada80000,0xada83000,0x2da88000,0x2da8b000,0x2a1f8000,0x2f64ada8,0x2f64b000,0x2a1fada8,0x80000000,0x80000000,0x80000000,0x80000000,
  0x2a1f0000,0x2f64ada8,0x2f64b000,0x2a1fada8,0x2da80000,0x2da8b000,0xada88000,0xada83000,0x2f640000,0xaa1fada8,0xaa1f3000,0x2f64ada8,
  0x30000000,0xb0008000,0x30000000,0xb0008000,0x2f640000,0xaa1f2da8,0xaa1fb000,0x2f642da8,0x2da80000,0x2da83000,0xada88000,0xada8b000,
  0x2a1f0000,0x2f642da8,0x2f643000,0x2a1f2da8,0x80000000,0x80000000,0x80000000,0x80000000,0xaa1f8000,0xaf642da8,0xaf643000,0xaa1f2da8,
  0x2da80000,0x2da8b000,0xada88000,0xada83000,0xaf648000,0x2a1f2da8,0x2a1fb000,0xaf642da8,0x30000000,0xb0008000,0x30000000,0xb0008000,
  0xaf648000,0x2a1fada8,0x2a1f3000,0xaf64ada8,0x2da80000,0x2da83000,0xada88000,0xada8b000,0xaa1f8000,0xaf64ada8,0xaf64b000,0xaa1fada8,
  0x30003000,0x30003000,0x30003000,0x30003000,0x2f643000,0x2a1f2da8,0xaa1f0000,0xaf64ada8,0x2da83000,0xada80000,0xada8b000,0x2da88000,
  0x2a1f3000,0xaf64ada8,0x2f648000,0xaa1f2da8,0x00003000,0x8000b000,0x00003000,0x8000b000,0xaa1f3000,0x2f64ada8,0xaf640000,0x2a1f2da8,
  0xada83000,0x2da88000,0x2da8b000,0xada80000,0xaf643000,0xaa1f2da8,0x2a1f8000,0x2f64ada8,0x30003000,0x30003000,0x30003000,0x30003000,
  0xaf64b000,0xaa1fada8,0x2a1f8000,0x2f642da8,0x2da83000,0xada80000,0xada8b000,0x2da88000,0xaa1fb000,0x2f642da8,0xaf640000,0x2a1fada8,
  0x00003000,0x8000b000,0x00003000,0x8000b000,0x2a1fb000,0xaf642da8,0x2f648000,0xaa1fada8,0xada83000,0x2da88000,0x2da8b000,0xada80000,
  0x2f64b000,0x2a1fada8,0xaa1f0000,0xaf642da8,0xb0003000,0xb0003000,0xb0003000,0xb0003000,0xaf643000,0xaa1f2da8,0x2a1f0000,0x2f64ada8,
  0xada83000,0x2da80000,0x2da8b000,0xada88000,0xaa1f3000,0x2f64ada8,0xaf648000,0x2a1f2da8,0x80003000,0x0000b000,0x80003000,0x0000b000,
  0x2a1f3000,0xaf64ada8,0x2f640000,0xaa1f2da8,0x2da83000,0xada88000,0xada8b000,0x2da80000,0x2f643000,0x2a1f2da8,0xaa1f8000,0xaf64ada8,
  0xb0003000,0xb0003000,0xb0003000,0xb0003000,0x2f64b000,0x2a1fada8,0xaa1f8000,0xaf642da8,0xada83000,0x2da80000,0x2da8b000,0xada88000,
  0x2a1fb000,0xaf642da8,0x2f640000,0xaa1fada8,0x80003000,0x0000b000,0x80003000,0x0000b000,0xaa1fb000,0x2f642da8,0xaf648000,0x2a1fada8,
  0x2da83000,0xada88000,0xada8b000,0x2da80000,0xaf64b000,0xaa1fada8,0x2a1f0000,0x2f642da8,0x80008000,0x80008000,0x80008000,0x80008000,
  0x2a1f8000,0x2f642da8,0x2f643000,0x2a1f2da8,0x2da88000,0x2da83000,0xada80000,0xada8b000,0x2f648000,0xaa1f2da8,0xaa1fb000,0x2f642da8,
  0x30008000,0xb0000000,0x30008000,0xb0000000,0x2f648000,0xaa1fada8,0xaa1f3000,0x2f64ada8,0x2da88000,0x2da8b000,0xada80000,0xada83000,
  0x2a1f8000,0x2f64ada8,0x2f64b000,0x2a1fada8,0x80008000,0x80008000,0x80008000,0x80008000,0xaa1f0000,0xaf64ada8,0xaf64b000,0xaa1fada8,
  0x2da88000,0x2da83000,0xada80000,0xada8b000,0xaf640000,0x2a1fada8,0x2a1f3000,0xaf64ada8,0x30008000,0xb0000000,0x30008000,0xb0000000,
  0xaf640000,0x2a1f2da8,0x2a1fb000,0xaf642da8,0x2da88000,0x2da8b000,0xada80000,0xada83000,0xaa1f0000,0xaf642da8,0xaf643000,0xaa1f2da8,
  0x00008000,0x00008000,0x00008000,0x00008000,0xaa1f8000,0xaf642da8,0xaf643000,0xaa1f2da8,0xada88000,0xada83000,0x2da80000,0x2da8b000,
  0xaf648000,0x2a1f2da8,0x2a1fb000,0xaf642da8,0xb0008000,0x30000000,0xb0008000,0x30000000,0xaf648000,0x2a1fada8,0x2a1f3000,0xaf64ada8,
  0xada88000,0xada8b000,0x2da80000,0x2da83000,0xaa1f8000,0xaf64ada8,0xaf64b000,0xaa1fada8,0x00008000,0x00008000,0x00008000,0x00008000,
  0x2a1f0000,0x2f64ada8,0x2f64b000,0x2a1fada8,0xada88000,0xada83000,0x2da80000,0x2da8b000,0x2f640000,0xaa1fada8,0xaa1f3000,0x2f64ada8,
  0xb0008000,0x30000000,0xb0008000,0x30000000,0x2f640000,0xaa1f2da8,0xaa1fb000,0x2f642da8,0xada88000,0xada8b000,0x2da80000,0x2da83000,
  0x2a1f0000,0x2f642da8,0x2f643000,0x2a1f2da8,
};

constexpr int kThreads = 384;
constexpr int kCtas = 128;

#define PREP0 1600
#define PREPGAP 650
#define HT0 13800
#define HGAP 500
#define WQT 11800
#define QT 17800
#define QGAP 400
#define POSTGAP 1000
#define TAIL 3
#define PSW 6
constexpr int EARLY = 2, L0 = 2;

constexpr int NS1 = 6;
__host__ __device__ constexpr int slot1(int it) { return (it + 4) % NS1; }
__host__ __device__ constexpr uint32_t w1_off(int s) { return (1 + s + (s >> 1)) * 16384; }
__host__ __device__ constexpr uint32_t x1_off(int it) { return ((it >> 1) & 3) * 49152; }
constexpr uint32_t ST2 = 32768;
constexpr uint32_t RA = 131072;
constexpr uint32_t RB = 163840;
constexpr uint32_t RU = 196608;
constexpr uint32_t Y_IN = RU;
constexpr uint32_t SM_ONES = 229376;
constexpr uint32_t SM_F2 = SM_ONES + 128;
constexpr uint32_t SM_BAR = 231424;
constexpr uint32_t SM_SCALE = SM_ONES + 1792;
constexpr uint32_t SM_MAX = SM_BAR + 512;
constexpr uint32_t SM_TOTAL = 232448;
constexpr uint32_t SM_BASE = 1024;
__host__ __device__ constexpr uint32_t kv_off(int h) { return RB + (h >> 1) * 16384 + (h & 1) * 2560; }

enum Bar { B_F1 = 0, B_F2 = 6, B_H = B_F2 + 4, B_KVL = 12, B_RDY = 20, B_Q = 34, B_MAX, B_ZERO, B_U, B_KV,
           B_E1 = 39, B_E2 = 45, B_I2 = B_E2 + 4,
           B_KVE = 51, B_VST, B_KVM, B_KVP, B_KVI, B_OW, B_ZST = 58,
           B_OFREE = 59, B_F2M, B_STG, B_Y, B_COUNT = 64, B_U2 = B_KVL };
__host__ __device__ constexpr int slot2(int n) { return n < 22 ? n & 3 : (0x1032510325ull >> (4 * (n - 22))) & 7; }
__host__ __device__ constexpr int par2(int n) { return n < 22 ? (n >> 2) & 1 : (0x326 >> (n - 22)) & 1; }

constexpr int KV_WORDS = 4096 + 128;
struct Scratch {
  float kv[8][KV_WORDS];
  unsigned kvflag[8 * 32], zflag[8 * 32], oflag[16 * 32], epoch[kCtas];
};
struct Params {
  CUtensorMap w1, x, k, v, w2, wo, o, outa, q, outb;
  const __nv_bfloat16* shift_k;
  const __nv_bfloat16* ssm_k;
  const __nv_bfloat16* ssm_d;
  const __nv_bfloat16* q_ptr;
  const __nv_bfloat16* w_ptr;
  const __nv_bfloat16* wo_ptr;
  uint64_t zero;
  Scratch* g;
  const uint32_t* tab;
};

__device__ __align__(128) Scratch g_scratch;
__device__ __align__(128) __nv_bfloat16 g_o[2048 * 1024];

#define TSTAMP(cond, i) do { } while (0)
#define GSTAMP(cond, i) do { } while (0)
#define KSTAMP(n) do { } while (0)
#define QSTAMP(n) do { } while (0)

#define JIT() do { } while (0)
constexpr int kSpinLimit = 1 << 16;

DEVI void mbar_init(uint32_t a, uint32_t c) { asm volatile("mbarrier.init.shared::cta.b64 [%0], %1;" :: "r"(a), "r"(c) : "memory"); }
DEVI void mbar_expect(uint32_t a, uint32_t b) { asm volatile("mbarrier.arrive.expect_tx.shared::cta.b64 _, [%0], %1;" :: "r"(a), "r"(b) : "memory"); }
DEVI void mbar_arrive(uint32_t a) { asm volatile("mbarrier.arrive.shared::cta.b64 _, [%0];" :: "r"(a) : "memory"); }
DEVI void mbar_arrive_if(uint32_t a, bool pred) {
  asm volatile("{\n.reg .pred p;\nsetp.ne.b32 p, %1, 0;\n@p mbarrier.arrive.shared::cta.b64 _, [%0];\n}" :: "r"(a), "r"((int)pred) : "memory");
}
DEVI void mbar_wait(uint32_t a, uint32_t parity) {
  asm volatile("{\n.reg .pred p;\n.reg .u32 n;\nmov.u32 n, 0;\nW_LOOP:\n"
               "mbarrier.try_wait.parity.shared::cta.b64 p, [%0], %1;\n@p bra W_DONE;\n"
               "add.u32 n, n, 1;\nsetp.lt.u32 p, n, %2;\n@p bra W_LOOP;\nW_DONE:\n}"
               :: "r"(a), "r"(parity), "n"(kSpinLimit) : "memory");
  JIT();
}
DEVI void mbar_wait4(uint32_t a, uint32_t b, uint32_t c, uint32_t d) {
  asm volatile("{\n.reg .pred p, q, r, s;\n.reg .u32 n;\nmov.u32 n, 0;\nW_LOOP:\n"
               "mbarrier.try_wait.parity.shared::cta.b64 p, [%0], 0;\nmbarrier.try_wait.parity.shared::cta.b64 q, [%1], 0;\n"
               "mbarrier.try_wait.parity.shared::cta.b64 r, [%2], 0;\nmbarrier.try_wait.parity.shared::cta.b64 s, [%3], 0;\n"
               "and.pred p, p, q;\nand.pred r, r, s;\nand.pred p, p, r;\n@p bra W_DONE;\n"
               "add.u32 n, n, 1;\nsetp.lt.u32 p, n, %4;\n@p bra W_LOOP;\nW_DONE:\n}"
               :: "r"(a), "r"(b), "r"(c), "r"(d), "n"(kSpinLimit) : "memory");
  JIT();
}
DEVI uint32_t mbar_test(uint32_t a, uint32_t parity) {
  uint32_t ok; asm volatile("{\n.reg .pred p;\nmbarrier.test_wait.parity.shared::cta.b64 p, [%1], %2;\nselp.u32 %0, 1, 0, p;\n}" : "=r"(ok) : "r"(a), "r"(parity) : "memory"); return ok;
}
DEVI void mbar_wait_unless(uint32_t ok, uint32_t a, uint32_t parity) {
  asm volatile("{\n.reg .pred p;\n.reg .u32 n;\nsetp.ne.u32 p, %3, 0;\n@p bra W_DONE;\nmov.u32 n, 0;\nW_LOOP:\n"
               "mbarrier.try_wait.parity.shared::cta.b64 p, [%0], %1;\n@p bra W_DONE;\n"
               "add.u32 n, n, 1;\nsetp.lt.u32 p, n, %2;\n@p bra W_LOOP;\nW_DONE:\n}"
               :: "r"(a), "r"(parity), "n"(kSpinLimit), "r"(ok) : "memory");
  JIT();
}
DEVI void mbar_wait_long(uint32_t a, uint32_t parity) {
  asm volatile("{\n.reg .pred p;\n.reg .u32 n;\nmov.u32 n, 0;\nW_LOOP:\n"
               "mbarrier.try_wait.parity.shared::cta.b64 p, [%0], %1, %3;\n@p bra W_DONE;\n"
               "add.u32 n, n, 1;\nsetp.lt.u32 p, n, %2;\n@p bra W_LOOP;\nW_DONE:\n}"
               :: "r"(a), "r"(parity), "n"(kSpinLimit), "r"(4000) : "memory");
  JIT();
}
DEVI void flag_wait(const unsigned* p, unsigned target) {
  int n = 0; unsigned v;
  do {
    asm volatile("ld.relaxed.gpu.global.u32 %0, [%1];" : "=r"(v) : "l"(p) : "memory");
  } while ((int)(v - target) < 0 && ++n < kSpinLimit);
  asm volatile("fence.acquire.gpu;" ::: "memory");
}
DEVI unsigned ld_relaxed(const unsigned* p) { unsigned v; asm volatile("ld.relaxed.gpu.global.u32 %0, [%1];" : "=r"(v) : "l"(p) : "memory"); return v; }
DEVI uint32_t clock32() { uint32_t t; asm volatile("mov.u32 %0, %%clock;" : "=r"(t)); return t; }
DEVI void pace(uint32_t t0, uint32_t n) { while (clock32() - t0 < n) __nanosleep(20); }
DEVI bool elect() { uint32_t p; asm volatile("{\n.reg .pred p;\nelect.sync _|p, 0xffffffff;\nselp.u32 %0, 1, 0, p;\n}" : "=r"(p)); return p; }
DEVI void fence_async_smem() { asm volatile("fence.proxy.async.shared::cta;" ::: "memory"); }
DEVI void bar_sync(int id, int n) { asm volatile("bar.sync %0, %1;" :: "r"(id), "r"(n) : "memory"); }
DEVI void cluster_sync() { asm volatile("barrier.cluster.arrive.relaxed.aligned;\nbarrier.cluster.wait.aligned;" ::: "memory"); }
DEVI void wg_fence() { asm volatile("wgmma.fence.sync.aligned;" ::: "memory"); }
DEVI void wg_commit() { asm volatile("wgmma.commit_group.sync.aligned;" ::: "memory"); }
template <int N> DEVI void wg_wait() { asm volatile("wgmma.wait_group.sync.aligned %0;" :: "n"(N) : "memory"); }
template <int N> DEVI void pin(uint32_t* r) {
#pragma unroll
  for (int i = 0; i < N; i++) asm volatile("" : "+r"(r[i]));
}
template <int N> DEVI void pin(float* r) {
#pragma unroll
  for (int i = 0; i < N; i++) asm volatile("" : "+f"(r[i]));
}

DEVI void tma2d(uint32_t dst, const CUtensorMap* m, int c0, int c1, uint32_t bar) {
  asm volatile("cp.async.bulk.tensor.2d.shared::cluster.global.mbarrier::complete_tx::bytes [%0], [%1, {%3, %4}], [%2];"
               :: "r"(dst), "l"(m), "r"(bar), "r"(c0), "r"(c1) : "memory");
}
DEVI void tma2d_mc(uint32_t dst, const CUtensorMap* m, int c0, int c1, uint32_t bar) {
  asm volatile("cp.async.bulk.tensor.2d.shared::cluster.global.mbarrier::complete_tx::bytes.multicast::cluster [%0], [%1, {%3, %4}], [%2], %5;"
               :: "r"(dst), "l"(m), "r"(bar), "r"(c0), "r"(c1), "h"((uint16_t)3) : "memory");
}
DEVI void tma3d(uint32_t dst, const CUtensorMap* m, int c0, int c1, int c2, uint32_t bar) {
  asm volatile("cp.async.bulk.tensor.3d.shared::cluster.global.mbarrier::complete_tx::bytes [%0], [%1, {%3, %4, %5}], [%2];"
               :: "r"(dst), "l"(m), "r"(bar), "r"(c0), "r"(c1), "r"(c2) : "memory");
}
DEVI void tma4d(uint32_t dst, const CUtensorMap* m, int c1, int c2, int c3, uint32_t bar) {
  asm volatile("cp.async.bulk.tensor.4d.shared::cluster.global.mbarrier::complete_tx::bytes [%0], [%1, {%3, %4, %5, %6}], [%2];"
               :: "r"(dst), "l"(m), "r"(bar), "r"(0), "r"(c1), "r"(c2), "r"(c3) : "memory");
}
DEVI void tma5d(uint32_t dst, const CUtensorMap* m, int c0, int c1, int c3, int c4, uint32_t bar) {
  asm volatile("cp.async.bulk.tensor.5d.shared::cluster.global.mbarrier::complete_tx::bytes [%0], [%1, {%3, %4, %5, %6, %7}], [%2];"
               :: "r"(dst), "l"(m), "r"(bar), "r"(c0), "r"(c1), "r"(0), "r"(c3), "r"(c4) : "memory");
}
DEVI void tma2d_store(const CUtensorMap* m, uint32_t src, int c0, int c1) {
  asm volatile("cp.async.bulk.tensor.2d.global.shared::cta.bulk_group [%0, {%2, %3}], [%1];" :: "l"(m), "r"(src), "r"(c0), "r"(c1) : "memory");
}
DEVI void tma2d_store_e(const CUtensorMap* m, uint32_t src, int c0, int c1) {
  asm volatile("{\n.reg .pred e;\nelect.sync _|e, 0xffffffff;\n@e cp.async.bulk.tensor.2d.global.shared::cta.bulk_group [%0, {%2, %3}], [%1];\n"
               "@e cp.async.bulk.commit_group;\n}" :: "l"(m), "r"(src), "r"(c0), "r"(c1) : "memory");
}
DEVI void tma5d_store(const CUtensorMap* m, uint32_t src, int c0, int c1, int c3, int c4) {
  asm volatile("cp.async.bulk.tensor.5d.global.shared::cta.bulk_group [%0, {%2, %3, %4, %5, %6}], [%1];\ncp.async.bulk.commit_group;"
               :: "l"(m), "r"(src), "r"(c0), "r"(c1), "r"(0), "r"(c3), "r"(c4) : "memory");
}
DEVI void bulk_load(uint32_t dst, const void* src, uint32_t bytes, uint32_t bar) {
  asm volatile("cp.async.bulk.shared::cluster.global.mbarrier::complete_tx::bytes [%0], [%1], %2, [%3];" :: "r"(dst), "l"(src), "r"(bytes), "r"(bar) : "memory");
}
DEVI uint32_t mapa(uint32_t a, int rank) { uint32_t r; asm("mapa.shared::cluster.u32 %0, %1, %2;" : "=r"(r) : "r"(a), "r"(rank)); return r; }
DEVI void st_async4(uint32_t dst, uint32_t a, uint32_t b, uint32_t c, uint32_t d, uint32_t bar) {
  asm volatile("st.async.weak.shared::cluster.mbarrier::complete_tx::bytes.v4.b32 [%0], {%1,%2,%3,%4}, [%5];"
               :: "r"(dst), "r"(a), "r"(b), "r"(c), "r"(d), "r"(bar) : "memory");
}
DEVI void st_either8(bool local, uint32_t dst, uint32_t bar, uint32_t a, uint32_t b, uint32_t c, uint32_t d, uint32_t e, uint32_t f, uint32_t g, uint32_t h) {
  asm volatile("{\n.reg .pred p;\nsetp.ne.b32 p, %10, 0;\n@p st.shared.v4.b32 [%0], {%2,%3,%4,%5};\n@p st.shared.v4.b32 [%0 + 4096], {%6,%7,%8,%9};\n@p bra.uni E_DONE;\n"
               "st.async.weak.shared::cluster.mbarrier::complete_tx::bytes.v4.b32 [%0], {%2,%3,%4,%5}, [%1];\n"
               "st.async.weak.shared::cluster.mbarrier::complete_tx::bytes.v4.b32 [%0 + 4096], {%6,%7,%8,%9}, [%1];\nE_DONE:\n}"
               :: "r"(dst), "r"(bar), "r"(a), "r"(b), "r"(c), "r"(d), "r"(e), "r"(f), "r"(g), "r"(h), "r"((int)local) : "memory");
}
DEVI void red_async_max(uint32_t dst, uint32_t a, uint32_t bar) {
  asm volatile("red.async.relaxed.cluster.shared::cluster.mbarrier::complete_tx::bytes.max.u32 [%0], %1, [%2];" :: "r"(dst), "r"(a), "r"(bar) : "memory");
}
DEVI void pf_line(const void* p) { asm volatile("prefetch.global.L2 [%0];" :: "l"(p) : "memory"); }
DEVI void bulk_commit() { asm volatile("cp.async.bulk.commit_group;" ::: "memory"); }
DEVI void bulk_wait_all() { asm volatile("cp.async.bulk.wait_group 0;" ::: "memory"); }
DEVI void bulk_wait_read() { asm volatile("cp.async.bulk.wait_group.read 0;" ::: "memory"); }
DEVI void prefetch_map(const CUtensorMap* m) { asm volatile("prefetch.tensormap [%0];" :: "l"(m) : "memory"); }

__host__ __device__ constexpr uint32_t dlo(uint32_t off, uint32_t lbo) { return (off >> 4) + ((lbo >> 4) << 16); }
struct Desc {
  uint64_t v;
  DEVI Desc(uint64_t z, uint32_t base, uint32_t sbo, uint32_t mode) : v(z + (base | (uint64_t)((sbo >> 4) | (mode << 30)) << 32)) { asm volatile("" : "+l"(v)); }
  DEVI void renew(uint64_t z) { asm volatile("add.s64 %0, %0, %1;" : "+l"(v) : "l"(z)); }
  DEVI uint64_t at(uint32_t lo) const { uint64_t r; asm volatile("add.s64 %0, %1, %2;" : "=l"(r) : "l"(v), "l"((int64_t)(int32_t)lo)); return r; }
};
DEVI uint32_t pack_bf16(float lo, float hi) { uint32_t r; asm("cvt.rn.bf16x2.f32 %0, %1, %2;" : "=r"(r) : "f"(hi), "f"(lo)); return r; }
DEVI uint32_t pack_f16(float lo, float hi) { uint32_t r; asm("cvt.rn.f16x2.f32 %0, %1, %2;" : "=r"(r) : "f"(hi), "f"(lo)); return r; }
DEVI void stsm4(uint32_t addr, uint32_t r0, uint32_t r1, uint32_t r2, uint32_t r3) {
  asm volatile("stmatrix.sync.aligned.m8n8.x4.shared.b16 [%0], {%1,%2,%3,%4};" :: "r"(addr), "r"(r0), "r"(r1), "r"(r2), "r"(r3) : "memory");
}
DEVI void stsm4_t(uint32_t addr, uint32_t r0, uint32_t r1, uint32_t r2, uint32_t r3) {
  asm volatile("stmatrix.sync.aligned.m8n8.x4.trans.shared.b16 [%0], {%1,%2,%3,%4};" :: "r"(addr), "r"(r0), "r"(r1), "r"(r2), "r"(r3) : "memory");
}
DEVI void sts128(uint32_t addr, uint32_t a, uint32_t b, uint32_t c, uint32_t d) {
  asm volatile("st.shared.v4.b32 [%0], {%1,%2,%3,%4};" :: "r"(addr), "r"(a), "r"(b), "r"(c), "r"(d) : "memory");
}
DEVI void sts32(uint32_t addr, uint32_t v) { asm volatile("st.shared.b32 [%0], %1;" :: "r"(addr), "r"(v) : "memory"); }
DEVI uint32_t lds32(uint32_t a) { uint32_t v; asm volatile("ld.shared.b32 %0, [%1];" : "=r"(v) : "r"(a)); return v; }
DEVI void lds128(uint32_t* v, uint32_t a) {
  asm volatile("ld.shared.v4.b32 {%0,%1,%2,%3}, [%4];" : "=r"(v[0]), "=r"(v[1]), "=r"(v[2]), "=r"(v[3]) : "r"(a));
}
DEVI void ldg128(uint32_t* v, const void* p) {
  asm volatile("ld.global.nc.L1::no_allocate.v4.b32 {%0,%1,%2,%3}, [%4];" : "=r"(v[0]), "=r"(v[1]), "=r"(v[2]), "=r"(v[3]) : "l"(p));
}
DEVI float rcp(float x) { float r; asm("rcp.approx.ftz.f32 %0, %1;" : "=f"(r) : "f"(x)); return r; }
DEVI float exp_sat(float t) {
  float e, s;
  asm("ex2.approx.ftz.f32 %0, %1;" : "=f"(e) : "f"(t * 1.4426950408889634f));
  asm("add.sat.f32 %0, %1, 0f358637BD;" : "=f"(s) : "f"(e));
  return s;
}
DEVI uint32_t phi2(float a, float b) {
  uint32_t r, o;
  asm("cvt.rn.relu.bf16x2.f32 %0, %1, %2;" : "=r"(r) : "f"(b), "f"(a));
  asm("add.rn.bf16x2 %0, %1, %2;" : "=r"(o) : "r"(r), "r"(pack_bf16(exp_sat(a), exp_sat(b))));
  return o;
}
DEVI void arrive_both(uint32_t bar, int lane, bool pred = true) {
  asm volatile("{\n.reg .pred p;\n.reg .b32 r;\nsetp.ne.b32 p, %2, 0;\nmapa.shared::cluster.u32 r, %0, %1;\n@p mbarrier.arrive.shared::cluster.b64 _, [r];\n}"
               :: "r"(bar), "r"(lane & 1), "r"((int)(pred && lane < 2)) : "memory");
}
DEVI uint32_t bmul2(uint32_t a, uint32_t b) { uint32_t r; asm("mul.rn.bf16x2 %0, %1, %2;" : "=r"(r) : "r"(a), "r"(b)); return r; }
DEVI uint32_t badd2(uint32_t a, uint32_t b) { uint32_t r; asm("add.rn.bf16x2 %0, %1, %2;" : "=r"(r) : "r"(a), "r"(b)); return r; }
DEVI uint32_t bamax2(uint32_t a, uint32_t b) { uint32_t r; asm("max.NaN.xorsign.abs.bf16x2 %0, %1, %2;" : "=r"(r) : "r"(a), "r"(b)); return r; }
DEVI uint32_t hmul2(uint32_t a, uint32_t b) { uint32_t r; asm("mul.rn.f16x2 %0, %1, %2;" : "=r"(r) : "r"(a), "r"(b)); return r; }
DEVI uint32_t hadd2(uint32_t a, uint32_t b) { uint32_t r; asm("add.rn.f16x2 %0, %1, %2;" : "=r"(r) : "r"(a), "r"(b)); return r; }
DEVI uint32_t hsub2(uint32_t a, uint32_t b) { uint32_t r; asm("sub.rn.f16x2 %0, %1, %2;" : "=r"(r) : "r"(a), "r"(b)); return r; }
DEVI uint32_t hfma2(uint32_t a, uint32_t b, uint32_t c) { uint32_t r; asm("fma.rn.f16x2 %0, %1, %2, %3;" : "=r"(r) : "r"(a), "r"(b), "r"(c)); return r; }
DEVI uint32_t hfnma2(uint32_t a, uint32_t b, uint32_t c) {
  uint32_t r; asm("{\n.reg .b32 n;\nneg.f16x2 n, %1;\nfma.rn.f16x2 %0, n, %2, %3;\n}" : "=r"(r) : "r"(a), "r"(b), "r"(c)); return r;
}
DEVI float bf_lo(uint32_t w) { return __uint_as_float(w << 16); }
DEVI float bf_hi(uint32_t w) { return __uint_as_float(w & 0xffff0000u); }

DEVI uint32_t chan_exponent(const uint32_t* w) {
  uint32_t m[4];
#pragma unroll
  for (int i = 0; i < 4; i++) m[i] = bamax2(w[i], w[i + 4]);
#pragma unroll
  for (int i = 8; i < 32; i++) m[i & 3] = bamax2(m[i & 3], w[i]);
  uint32_t x = bamax2(bamax2(m[0], m[1]), bamax2(m[2], m[3])) & 0x7fff7fffu;
  x = max(x >> 16, x & 0xffffu);
  x = __reduce_max_sync(0xffffffffu, x);
  return min(x >> 7, 251u);
}
DEVI uint32_t to_f16(uint32_t w, uint32_t mul) { const uint32_t y = bmul2(w, mul); return pack_f16(bf_lo(y), bf_hi(y)); }

struct Tile { int j, r; };
DEVI Tile tile_of() {
  int cta; asm volatile("mov.u32 %0, %%ctaid.x;" : "=r"(cta));
  const int cl = cta >> 1, lo = (cl - 4) >> 31, hi = (35 - cl) >> 31;
  const int p = cl - 4 + (lo & (36 + 7 * cl)) + (hi & ((((cl - 36) * 37) >> 8) + 1)), g = p & 7, rr = p >> 3;
  return Tile{(g & 6) | (cta & 1), 2 * rr + (g & 1)};
}

static_assert(TAIL <= 4, "the releases up to stage 26 feed the ring");
__host__ __device__ constexpr bool prew(int it) { return it >= 28 && it < 31; }

DEVI void twiddle(uint32_t& ore, uint32_t& oim, uint32_t re, uint32_t im, uint32_t t, uint32_t s) {
  re = hfma2(t, im, re);
  oim = hfma2(s, re, im);
  ore = hfma2(t, oim, re);
}

__global__ void __cluster_dims__(2, 1, 1) __launch_bounds__(kThreads, 1)
fused_kernel(const __grid_constant__ Params P) {
  extern __shared__ __align__(1024) uint8_t smem[];
  const int tid = threadIdx.x, lane = tid & 31;
  const int warp = tid >> 5, warpu = __shfl_sync(0xffffffffu, tid >> 5, 0);
  const int cta = blockIdx.x, rho = cta & 1, cl = cta >> 1;
  const uint32_t sb = SM_BASE + (rho << 24);
  const uint32_t tstart = clock32();
  auto bar = [&](int i) INL { return sb + SM_BAR + 8u * i; };
  auto load1 = [&](int it, int s, int j, int r, bool mc) INL {
    const uint32_t fb = bar(B_F1 + s), xs = sb + x1_off(it);
    mbar_expect(fb, (it & 1) ? 16384 : 32768);
    tma4d(sb + w1_off(s), &P.w1, 32 * it, 2 * j, 1, fb);
    if (!(it & 1)) {
      if (mc) tma2d_mc(xs + rho * 8192, &P.x, 32 * it, 128 * r + 64 * rho, fb);
      else { tma2d(xs, &P.x, 32 * it, 128 * r, fb); tma2d(xs + 8192, &P.x, 32 * it, 128 * r + 64, fb); }
    }
  };
  TSTAMP(tid == 0, 0); GSTAMP(tid == 0, 62);

  if (warpu == 8 && elect()) {
    prefetch_map(&P.w1); prefetch_map(&P.x);
    for (int i = 0; i < EARLY; i++) mbar_init(bar(B_F1 + slot1(i)), 1);
    const Tile T = tile_of();
    for (int i = 0; i < EARLY; i++) load1(i, slot1(i), T.j, T.r, false);
    TSTAMP(true, 18);
    for (int i = EARLY; i < NS1; i++) mbar_init(bar(B_F1 + slot1(i)), 1);
    asm volatile("fence.mbarrier_init.release.cluster;" ::: "memory");
  }
  if (warpu == 9 && elect()) {
    if (sb != (uint32_t)__cvta_generic_to_shared(smem)) __trap();
#pragma unroll
    for (int i = B_F2; i < B_Q; i++) mbar_init(bar(i), 1);
    mbar_expect(bar(B_H), 32768);
    asm volatile("fence.mbarrier_init.release.cluster;" ::: "memory");
  }
  if (warpu == 10 && elect()) {
#pragma unroll
    for (int i = B_Q; i < B_KVE; i++) mbar_init(bar(i), i < B_E1 ? 1 : 16);
    mbar_expect(bar(B_Q), 32768); mbar_expect(bar(B_U), 16384); mbar_expect(bar(B_MAX), 1024);
    asm volatile("fence.mbarrier_init.release.cluster;" ::: "memory");
  }
  if (warpu == 11 && elect()) {
#pragma unroll
    for (int i = B_KVE; i < B_COUNT; i++) mbar_init(bar(i), i < B_OFREE ? 8 : i == B_F2M ? 3 : i < B_Y ? 4 : 9);
    mbar_expect(bar(B_Y), 8192); mbar_expect(bar(B_Y + 1), 8192);
    asm volatile("fence.mbarrier_init.release.cluster;" ::: "memory");
  }
  __syncwarp();
  cluster_sync();

  if (warpu < 8) {
    asm volatile("setmaxnreg.inc.sync.aligned.u32 %0;" :: "n"(232));
    const int wg = warp >> 2, wq = warp & 3, g = lane >> 2, q = lane & 3;
    constexpr uint32_t sbq = SM_BASE >> 4;
    const uint32_t wgu = warpu >> 2;
    const uint64_t z64 = P.zero;
    Desc dA(z64, sbq + wgu * 512, 1024, 1), dB(z64, sbq, 1024, 1);
    const int srow = wg * 64 + wq * 16 + (lane & 15);
    const uint32_t stm = srow * 128 + (((lane >> 4) ^ (srow & 7)) << 4);
    auto stage2 = [&](float* acc, int n, bool first, bool wait = true) INL {
      const int s = slot2(n);
      if (wait) mbar_wait(bar(B_F2 + s), par2(n));
      const uint32_t da = s * (ST2 >> 4) + dlo(0, 16), db = s * (ST2 >> 4) + dlo(16384, 8192);
      wg_fence();
      const uint64_t a0 = dA.at(da), b0 = dB.at(db);
      if (first) mma_n128_init(acc, a0, b0); else mma_n128(acc, a0, b0);
#pragma unroll
      for (int kk = 1; kk < 4; kk++) mma_n128(acc, a0 + 2 * kk, b0 + kk * (2048 >> 4));
      wg_commit();
    };
    auto release2 = [&](int n) INL { arrive_both(bar(B_E2 + slot2(n)), lane); };
    auto publish = [&](int b) INL { fence_async_smem(); __syncwarp(); mbar_arrive_if(bar(b), lane == 0); };

    float aq[64];
    uint32_t f1[8], tw[4];
    uint32_t su[2][32], sh[2][32];
    uint32_t x0[4][8], x1[4][8], p0[2][8], p1[2][8], z0[2][8], z1[2][8];
    auto s1 = [&](uint32_t* d, uint32_t base) INL {
      Desc db(z64, sbq + wgu * 1024 + dlo(base, 128), 512, 0);
      wg_fence();
      mma_s1_init(d, f1, db.v);
      mma_s1(d, f1 + 4, db.at(256 >> 4));
      wg_commit();
    };
    const uint64_t dre = Desc(z64, sbq + dlo(SM_F2 + 512, 128), 256, 0).v, dim = Desc(z64, sbq + dlo(SM_F2, 128), 256, 0).v;
    auto fwd2 = [&](uint32_t (*x)[8], int c) INL {
      uint32_t a[4][8];
#pragma unroll
      for (int t = 0; t < 4; t++) {
        uint32_t* s = (t < 2 ? sh[c >> 1] : su[c >> 1]) + 16 * (c & 1) + 8 * (t & 1);
        pin<8>(s);
#pragma unroll
        for (int i = 0; i < 4; i++) twiddle(a[t][i], a[t][4 + i], s[4 * (i & 1) + (i & 2)], s[4 * (i & 1) + (i & 2) + 1], tw[i & 2], tw[(i & 2) + 1]);
      }
      wg_fence();
#pragma unroll
      for (int t = 0; t < 4; t++) { mma_s2_init(x[t], a[t], dre); mma_s2(x[t], a[t] + 4, dim); }
      wg_commit();
    };
    auto half2 = [&](uint32_t (*x)[8], uint32_t* s) INL {
      uint32_t a[2][8];
      pin<16>(s);
#pragma unroll
      for (int t = 0; t < 2; t++)
#pragma unroll
        for (int i = 0; i < 4; i++) twiddle(a[t][i], a[t][4 + i], s[8 * t + 4 * (i & 1) + (i & 2)], s[8 * t + 4 * (i & 1) + (i & 2) + 1], tw[i & 2], tw[(i & 2) + 1]);
      wg_fence();
#pragma unroll
      for (int t = 0; t < 2; t++) { mma_s2_init(x[t], a[t], dre); mma_s2(x[t], a[t] + 4, dim); }
      wg_commit();
    };
    auto product = [&](uint32_t (*a)[8], uint32_t (*x)[8], int i) INL {
#pragma unroll
      for (int t = 0; t < 4; t++) { pin<2>(x[t] + i); pin<2>(x[t] + 4 + i); }
      auto hr = [&](int l) INL { return x[l >> 1][i + (l & 1)]; };
      auto hi = [&](int l) INL { return x[l >> 1][4 + i + (l & 1)]; };
      auto ur = [&](int l) INL { return x[2 + (l >> 1)][i + (l & 1)]; };
      auto ui = [&](int l) INL { return x[2 + (l >> 1)][4 + i + (l & 1)]; };
      uint32_t gr[4], gi[4];
      gr[0] = hr(0); gi[0] = hi(0);
#pragma unroll
      for (int l = 1; l < 4; l++) { gr[l] = hadd2(hr(l), hi(l - 1)); gi[l] = hsub2(hi(l), hr(l - 1)); }
#pragma unroll
      for (int p = 0; p < 4; p++) {
        uint32_t re = hfnma2(gi[0], ui(p), hmul2(gr[0], ur(p))), im = hfma2(gi[0], ur(p), hmul2(gr[0], ui(p)));
#pragma unroll
        for (int l = 1; l <= p; l++) {
          re = hfnma2(gi[l], ui(p - l), hfma2(gr[l], ur(p - l), re));
          im = hfma2(gi[l], ur(p - l), hfma2(gr[l], ui(p - l), im));
        }
        a[p >> 1][i + (p & 1)] = re; a[p >> 1][4 + i + (p & 1)] = im;
      }
#pragma unroll
      for (int t = 0; t < 2; t++) { pin<2>(a[t] + i); pin<2>(a[t] + 4 + i); }
    };
    auto inv1 = [&](uint32_t (*z)[8], uint32_t (*a)[8]) INL {
      wg_fence();
#pragma unroll
      for (int t = 0; t < 2; t++) { mma_s2_init(z[t], a[t], dre); mma_s2_neg(z[t], a[t] + 4, dim); }
      wg_commit();
    };
    auto zstore = [&](uint32_t (*z)[8], int c) INL {
      const uint32_t zoff = sb + RB + (q >> 1) * (RU + 16 - RB) + (8 * rho + 4 * wg) * 2048 + (4 * (8 * wq + g) + 2 * (q & 1)) * 16;
#pragma unroll
      for (int t = 0; t < 2; t++) {
        uint32_t a[8];
        pin<8>(z[t]);
#pragma unroll
        for (int i = 0; i < 4; i++) twiddle(a[i], a[4 + i], z[t][i], z[t][4 + i], tw[i & 2], tw[(i & 2) + 1]);
        const uint32_t dst = zoff + t * (16384 - rho * 32768) + c * 2048;
        sts128(dst, a[0], a[1], a[2], a[3]);
        sts128(dst + 16, a[4], a[5], a[6], a[7]);
      }
    };
    float kvr[18];
    auto kvstore = [&]() INL {
      const uint32_t dst = sb + kv_off(warp >> 1) + (warp & 1) * 256 + lane * 4;
      pin<18>(kvr);
#pragma unroll
      for (int b = 0; b < 4; b++) { sts32(dst + b * 512, pack_bf16(kvr[4 * b], kvr[4 * b + 1])); sts32(dst + b * 512 + 128, pack_bf16(kvr[4 * b + 2], kvr[4 * b + 3])); }
      sts32(dst + 2048, pack_bf16(kvr[16], kvr[16])); sts32(dst + 2176, pack_bf16(kvr[17], kvr[17]));
      publish(B_KVI);
    };
    {
      float ak[64], av[64];
      Desc dK(z64, sbq + wgu * 256, 1024, 1);
      auto kstep = [&](int c, int i) INL {
        const int s = slot1(c);
        if (!prew(c - 1)) mbar_wait(bar(B_F1 + s), (c / NS1 + i) & 1);
        TSTAMP(tid == 0 && c == 0, 1);
        const uint32_t dx = dlo(x1_off(c + 6 * i), 16), dk = dlo(w1_off(s), 16);
        const uint64_t xb = dB.at(dx) + (c & 1) * 4;
        wg_fence();
        if (c == 0) { mma_kt_init(ak, dK.at(dk), xb); mma_kt_init(av, dK.at(dk + 512), xb); }
        else { mma_kt(ak, dK.at(dk), xb); mma_kt(av, dK.at(dk + 512), xb); }
        mma_kt(ak, dK.at(dk + 128), xb + 2);
        mma_kt(av, dK.at(dk + 640), xb + 2);
        wg_commit();
        wg_wait<1>();
        if (c > 0) arrive_both(bar(B_E1 + (s + NS1 - 1) % NS1), lane);
        if (prew(c)) mbar_wait(bar(B_F1 + slot1(c + 1)), ((c + 1) / NS1) & 1);
        KSTAMP(c + 6 * i);
      };
      auto renew = [&]() INL { dK.renew(z64); dB.renew(z64); };
      uint32_t kk[7], u[36], sw[4], mx[2], um = 0, eu;
      unsigned short dskip;
      const int cp = 4 * (warp & 1) + (lane >> 3), run = 8 * (warp >> 1) + (lane & 7);
      const uint32_t ua = sb + RB + run * 32 + ((warp ^ (lane >> 2)) & 1) * 16 + (lane >> 3) * 4;
      sts32(sb + SM_MAX + (lane & 15) * 4, 0);
      ldg128(sw, P.shift_k + (cl * 16 + 2 * cp) * 4);
      asm volatile("ld.global.nc.b16 %0, [%1];" : "=h"(dskip) : "l"(P.ssm_d + 8 * cta + warp));
#pragma unroll
      for (int c = 0; c < L0; c++) kstep(c, 0);
      {
        pin<4>(sw);
        const uint32_t t0 = __byte_perm(sw[0], sw[2], 0x5410), t1 = __byte_perm(sw[0], sw[2], 0x7632), t2 = __byte_perm(sw[1], sw[3], 0x5410);
        sw[3] = __byte_perm(sw[1], sw[3], 0x7632); sw[0] = t0; sw[1] = t1; sw[2] = t2;
        pin<4>(sw);
      }
      float tap0 = lane == 0 ? bf_lo(dskip) : 0.f;
      pin<1>(&tap0);
#pragma unroll
      for (int e = 0; e < 36; e++) u[e] = 0;
#pragma unroll
      for (int e = 0; e < 7; e++) kk[e] = 0;
      renew();
#pragma unroll
      for (int c = L0; c < L0 + 6; c++) kstep(c, 0);
      renew();
#pragma unroll 1
      for (int i = 1; i < 4; i++) {
#pragma unroll
        for (int h = 0; h < 3; h++) {
          kstep(L0 + 2 * h, i);
          {
            const int slot = (3 * i + h + 4) & 7;
#pragma unroll
            for (int e = 4 * h; e < 4 * h + 4; e++) { u[e] = u[e + 12]; u[e + 12] = u[e + 24]; }
            pin<4>(u + 4 * h); pin<4>(u + 4 * h + 12);
            mbar_wait(bar(B_KVL + slot), h == 2 && i == 3);
#pragma unroll
            for (int e = 0; e < 4; e++) { kk[3 + e] = lds32(ua + slot * 8192 + e * 1024); u[24 + 4 * h + e] = lds32(ua + slot * 8192 + 4096 + e * 1024); }
          }
          kstep(L0 + 2 * h + 1, i);
          pin<7>(kk); pin<4>(u + 24 + 4 * h);
#pragma unroll
          for (int e = 0; e < 4; e++) {
            uint32_t& y = u[24 + 4 * h + e];
            y = bmul2(badd2(badd2(badd2(bmul2(kk[e], sw[3]), bmul2(kk[1 + e], sw[2])), bmul2(kk[2 + e], sw[1])), bmul2(kk[3 + e], sw[0])), y);
            um = bamax2(um, y);
          }
          if (h == 0) um = i == 1 ? 0 : um;
          kk[0] = kk[4]; kk[1] = kk[5]; kk[2] = kk[6];
          pin<4>(u + 24 + 4 * h); pin<1>(&um);
          if (h == 1) mbar_arrive_if(bar(B_KVE), lane == 0 && i == 2);
        }
      }
      um = bamax2(um, __shfl_xor_sync(0xffffffffu, um, 1));
      um = bamax2(um, __shfl_xor_sync(0xffffffffu, um, 2));
      red_async_max(mapa(sb + SM_MAX + cp * 8 + (q & 1) * 4, q >> 1), min((um >> (7 + 16 * (q & 1))) & 0xffu, 251u), mapa(bar(B_MAX), q >> 1));
      renew();
#pragma unroll
      for (int c = L0 + 24; c < 28; c++) {
        kstep(c, 0);
        if (c == L0 + 24) { ldg128(f1, P.tab + (tid & 127) * 4); ldg128(f1 + 4, P.tab + 512 + (tid & 127) * 4); ldg128(tw, P.tab + 1024 + (tid & 127) * 4); }
      }
      mbar_wait(bar(B_MAX), 0);
      TSTAMP(tid == 0, 5);
      asm volatile("ld.shared.v2.b32 {%0,%1}, [%2];" : "=r"(mx[0]), "=r"(mx[1]) : "r"(sb + SM_MAX + cp * 8));
      eu = lds32(sb + SM_MAX + (8 * rho + warp) * 4);
      const uint32_t ud = mapa(sb + RU + (lane >> 3) * 8192 + (2 * rho + wg) * 1024 + (run & 15) * 16, warp & 1), ub = mapa(bar(B_U), rho ^ 1);
#pragma unroll
      for (int i = 0; i < 4; i++) {
        kstep(28 + i, 0);
        if (i == 0) { pin<2>(mx); mx[0] = (0x00fd00fdu - (mx[0] | mx[1] << 16)) << 7; }
        uint32_t* y = u + 4 + 8 * i;
        pin<8>(y);
#pragma unroll
        for (int e = 0; e < 8; e++) y[e] = bmul2(y[e], mx[0]);
        st_either8((warpu & 1) == rho, ud + (i & 1) * 512 + (i >> 1) * 256, ub,
                   pack_f16(bf_lo(y[0]), bf_lo(y[1])), pack_f16(bf_lo(y[2]), bf_lo(y[3])), pack_f16(bf_lo(y[4]), bf_lo(y[5])), pack_f16(bf_lo(y[6]), bf_lo(y[7])),
                   pack_f16(bf_hi(y[0]), bf_hi(y[1])), pack_f16(bf_hi(y[2]), bf_hi(y[3])), pack_f16(bf_hi(y[4]), bf_hi(y[5])), pack_f16(bf_hi(y[6]), bf_hi(y[7])));
      }
      auto qstep = [&](int n) INL {
        if ((n & 3) == 0) { dA.renew(z64); dB.renew(z64); }
        stage2(aq, n, n == 0);
        wg_wait<1>();
        if (n == 0) arrive_both(bar(B_E1 + NS1 - 1), lane); else release2(n - 1);
        QSTAMP(n);
      };
      uint32_t pk[32];
      auto phik = [&](int i0, int i1) INL {
#pragma unroll
        for (int i = i0; i < i1; i++) { pin<2>(ak + 2 * i); pk[i] = phi2(ak[2 * i], ak[2 * i + 1]); pin<1>(pk + i); }
      };
      const uint32_t rot = tile_of().r & 3;
      const uint32_t kr = 16 * (lane >> 4) + 2 * (lane & 6) + 2 * (((wq >> 1) ^ (lane >> 2)) & 1) + (lane & 1);
      const uint32_t stt = sb + RA + wg * 16384 + kr * 64 + ((((2 * wq + ((lane >> 3) & 1)) ^ rot ^ (kr >> 1)) & 3) << 4);
      auto vst = [&](int k0, int k1) INL {
#pragma unroll
        for (int kt = k0; kt < k1; kt++) {
          float* a = av + 8 * kt;
          pin<8>(a);
          stsm4_t(stt + kt * 2048, pack_bf16(a[0], a[1]), pack_bf16(a[2], a[3]), pack_bf16(a[4], a[5]), pack_bf16(a[6], a[7]));
        }
      };
      float dkv[20];
      uint32_t kvmeta;
      Desc dV(z64, sbq + wgu * (1024u - (1024u << 16)) + dlo(RA, SM_ONES - RA), 512, 2);
      auto kvmma = [&](int k0, int k1) INL {
        if (k0 == 0) asm volatile("shf.l.wrap.b32 %0, %1, %1, %2;" : "=r"(kvmeta) : "r"(0xEE44EE44u), "r"((tid >> 3) & 8));
        wg_fence();
#pragma unroll
        for (int ks = k0; ks < k1; ks++) {
          const uint64_t db = dV.at(ks * (128u - (128u << 16)));
          if (ks == 0) mma_kv_init(dkv, pk, db, kvmeta); else mma_kv(dkv, pk + 4 * ks, db, kvmeta);
        }
        wg_commit();
      };
      float* gacc;
      auto kvred = [&](int b) INL {
        asm volatile("red.relaxed.gpu.global.add.v4.f32 [%0], {%1,%2,%3,%4};" :: "l"(gacc + (b ^ rot) * 128), "f"(dkv[4 * b]), "f"(dkv[4 * b + 1]), "f"(dkv[4 * b + 2]), "f"(dkv[4 * b + 3]) : "memory");
        if (b == 3) {
          asm volatile("{\n.reg .pred p;\nsetp.eq.s32 p, %3, 0;\n@p red.relaxed.gpu.global.add.v2.f32 [%0], {%1,%2};\n}"
                       :: "l"(gacc + 4096 - warp * 496 - g * 14), "f"(dkv[16]), "f"(dkv[18]), "r"(q) : "memory");
          __syncwarp();
          mbar_arrive_if(bar(B_KVP), lane == 0);
          TSTAMP(tid == 0, 4);
        }
      };
      uint32_t w[32], hmul;
      auto hload = [&](int i0, int i1) INL {
        const uint32_t a = sb + RB + warp * 4096 + (((lane >> 2) & 1) + (lane & 2) + 4 * (lane & 1) + (((lane << 2) ^ lane) & 24)) * 16;
#pragma unroll
        for (int i = i0; i < i1; i++) lds128(w + 4 * i, a + i * 512);
      };
      auto hmax = [&]() INL {
        pin<32>(w);
        tap0 += bf_lo(w[0]);
        w[0] = pack_bf16(tap0, bf_hi(w[0]));
        hmul = (252u - chan_exponent(w)) * 0x00800080u;
        const int e = min(max((int)(eu + 128 - (hmul >> 23)), 0), 254);
        asm volatile("st.shared.b16 [%0], %1;" :: "r"(sb + SM_SCALE + 2 * warp), "h"((unsigned short)(e << 7)) : "memory");
      };
      auto hstore = [&](int i0, int i1) INL {
        const uint32_t dst = sb + RB + warp * 4096 + (lane & 6) * 128 + ((lane ^ ((lane >> 2) & 6)) & 7) * 16;
#pragma unroll
        for (int i = i0; i < i1; i++) {
          pin<4>(w + 4 * i);
          const uint32_t w0 = i == 0 ? pack_f16(tap0 * bf_lo(hmul), bf_hi(w[0]) * bf_lo(hmul)) : to_f16(w[4 * i], hmul);
          sts128(dst + (i >> 1) * 1024 + (i & 1) * 128, w0, to_f16(w[4 * i + 1], hmul), to_f16(w[4 * i + 2], hmul), to_f16(w[4 * i + 3], hmul));
        }
      };
      auto kvload = [&]() INL {
        mbar_wait(bar(B_KV), 0);
        TSTAMP(tid == 0, 7);
#pragma unroll
        for (int b = 0; b < 4; b++)
          asm volatile("ld.global.cg.v4.f32 {%0,%1,%2,%3}, [%4];" : "=f"(kvr[4 * b]), "=f"(kvr[4 * b + 1]), "=f"(kvr[4 * b + 2]), "=f"(kvr[4 * b + 3]) : "l"(gacc + b * 128) : "memory");
        asm volatile("ld.global.cg.v2.f32 {%0,%1}, [%2];" : "=f"(kvr[16]), "=f"(kvr[17]) : "l"(gacc + 4096 - warp * 496 - g * 14 - q * 4) : "memory");
      };
      qstep(0);
      TSTAMP(tid == 0, 2);
      phik(0, 5);
      qstep(1);
      mbar_wait(bar(B_E1 + NS1 - 1), 1);
      vst(0, 3); phik(5, 9);
      qstep(2);
      vst(3, 6); phik(9, 13);
      qstep(3);
      vst(6, 8);
      publish(B_VST);
      phik(13, 17);
      qstep(4);
      mbar_wait4(bar(B_ZERO), bar(B_VST), bar(B_H), bar(B_H));
      kvmma(0, 4); hload(0, 3); phik(17, 22);
      gacc = &P.g->kv[tile_of().j][warp * 512 + lane * 4];
      qstep(5);
      hload(3, 5); phik(22, 27);
      qstep(6);
      hload(5, 8); phik(27, 32); kvmma(4, 8);
      qstep(7);
      pin<20>(dkv);
      mbar_arrive_if(bar(B_KVM), lane == 0);
      kvred(0);
      mbar_wait(bar(B_U2), 1);
      s1(su[0], RU);
      hmax(); hstore(0, 2); kvred(1);
      qstep(8);
      hstore(2, 5); kvred(2);
      qstep(9);
      kvred(3); hstore(5, 8);
      publish(B_VST);
      qstep(10);
      mbar_wait(bar(B_VST), 1);
      s1(sh[0], RB);
      mbar_wait(bar(B_F2M), 0);
      half2(x0 + 2, su[0]); half2(x1 + 2, su[0] + 16);
      qstep(11);
      half2(x0, sh[0]); half2(x1, sh[0] + 16);
      qstep(12);
      product(p0, x0, 0);
      qstep(13);
      product(p0, x0, 2);
      kvload();
      qstep(14);
      product(p1, x1, 0);
      qstep(15);
      product(p1, x1, 2);
    }

    float acc[64];
    {
      uint32_t pq[4][8];
      float dn[4][20];
      Desc dO(z64, sbq + dlo(0, 128), 512, 0);
      auto phiq = [&](int h) INL {
        pin<16>(aq + 16 * h);
#pragma unroll
        for (int i = 0; i < 8; i++) pq[h][i] = phi2(aq[16 * h + 2 * i], aq[16 * h + 2 * i + 1]);
        pin<8>(pq[h]);
      };
      auto omma = [&](int h) INL {
        wg_fence();
        mma_o_init(dn[h], pq[h], dO.at(kv_off(h) >> 4));
        mma_o(dn[h], pq[h] + 4, dO.at((kv_off(h) + 256) >> 4));
        wg_commit();
      };
      auto onorm = [&](int h) INL {
        pin<20>(dn[h]);
        const float i0 = rcp(dn[h][16] + 1e-6f), i1 = rcp(dn[h][18] + 1e-6f);
#pragma unroll
        for (int hf = 0; hf < 2; hf++) {
          const float* a = dn[h] + 8 * hf;
          stsm4(sb + (h >> 1) * ST2 + (stm ^ (((h & 1) * 2 + hf) << 5)), pack_bf16(a[0] * i0, a[1] * i0), pack_bf16(a[2] * i1, a[3] * i1),
                pack_bf16(a[4] * i0, a[5] * i0), pack_bf16(a[6] * i1, a[7] * i1));
        }
        if (h & 1) publish(B_OW + (h >> 1));
      };
      s1(su[1], RU + 8192);
      kvstore();
      wg_wait<1>();
      release2(15);
      TSTAMP(tid == 0, 6);
      uint32_t gf[4][4];
      auto gdup = [&]() INL {
#pragma unroll
        for (int i = 0; i < 4; i += 2) {
          pin<4>(gf[i + 1]);
          gf[i][0] = gf[i][1] = gf[i + 1][0]; gf[i][2] = gf[i][3] = gf[i + 1][1];
          gf[i + 1][0] = gf[i + 1][1] = gf[i + 1][2]; gf[i + 1][2] = gf[i + 1][3];
          pin<4>(gf[i]); pin<4>(gf[i + 1]);
        }
      };
      const uint32_t qa = sb + RA + warp * 4096 + lane * 32 + ((rho ^ g) & 1) * 16;
      uint32_t qv[4][4];
      auto qload = [&]() INL {
#pragma unroll
        for (int i = 0; i < 4; i++) lds128(qv[i], qa + i * 1024);
      };
      phiq(0);
      const uint32_t kvok = mbar_test(bar(B_KVI), 0);
      phiq(1);
      mbar_wait_unless(kvok, bar(B_KVI), 0);
      omma(0); omma(1);
      wg_wait<1>(); onorm(0);
      wg_wait<0>(); onorm(1);
      TSTAMP(tid == 0, 8);
      s1(sh[1], RB + 8192);
      phiq(2); omma(2); phiq(3);
      wg_wait<0>(); onorm(2);
      omma(3); inv1(z0, p0);
      wg_wait<1>(); onorm(3);
      TSTAMP(tid == 0, 9);
      inv1(z1, p1); fwd2(x0, 2);
      wg_wait<1>();
      mbar_wait4(bar(B_OW + 1), bar(B_F2), bar(B_F2 + 1), bar(B_Q));
      zstore(z0, 0); zstore(z1, 1);
      wg_wait<0>();
      dA.renew(z64); dB.renew(z64);
      stage2(acc, 16, true, false);
      fwd2(x1, 3);
      product(p0, x0, 0); product(p0, x0, 2);
      inv1(z0, p0);
      stage2(acc, 17, false, false);
      wg_wait<2>();
      release2(16);
      ldg128(gf[1], P.tab + 1536 + (tid & 127) * 4); ldg128(gf[3], P.tab + 2048 + (tid & 127) * 4);
      product(p1, x1, 0); product(p1, x1, 2);
      inv1(z1, p1);
      wg_wait<2>();
      zstore(z0, 2);
      gdup();
      wg_wait<0>();
      release2(17);
      zstore(z1, 3);
      publish(B_ZST);
      TSTAMP(tid == 0, 10);
      qload();
      mbar_wait(bar(B_ZST), 0);
      float y[64];
      {
        Desc db(z64, sbq + wgu * ((RU + 16 - RB) >> 4) + dlo(RB, 128), 2048, 0);
        wg_fence();
        mma_i2_init(y, gf[0], db.v, 0xEEEE4444u);
#pragma unroll
        for (int i = 1; i < 4; i++) mma_i2(y, gf[i], db.at(i * (512 >> 4)), 0xEEEE4444u);
        wg_commit();
      }
      uint32_t sc[4];
      lds128(sc, sb + SM_SCALE);
      TSTAMP(tid == 0, 11);
      stage2(acc, 18, false);
      TSTAMP(tid == 0, 13);
      wg_wait<1>();
      QSTAMP(18);
      arrive_both(bar(B_I2), lane);
      pin<64>(y);
      uint32_t yv[8][4];
#pragma unroll
      for (int i = 0; i < 8; i++)
#pragma unroll
        for (int m = 0; m < 4; m++) yv[i][m] = bmul2(pack_bf16(y[32 * (i >> 2) + (i & 3) + 8 * m], y[32 * (i >> 2) + (i & 3) + 8 * m + 4]), sc[m]);
      pin<32>(&yv[0][0]);
      stage2(acc, 19, false);
      wg_wait<1>();
      QSTAMP(19);
      release2(18);
      mbar_wait(bar(B_I2), 0);
      const uint32_t yr = mapa(sb + Y_IN + tid * 16 + warp * 1536, rho ^ 1), yb = mapa(bar(B_Y), rho ^ 1);
      dA.renew(z64); dB.renew(z64);
#pragma unroll
      for (int i = 0; i < 4; i++) {
        if (i) { stage2(acc, 19 + i, false); wg_wait<1>(); QSTAMP(19 + i); release2(18 + i); }
        pin<4>(qv[i]);
        sts128(qa + i * 1024, bmul2(yv[i][0], qv[i][0]), bmul2(yv[i][1], qv[i][1]), bmul2(yv[i][2], qv[i][2]), bmul2(yv[i][3], qv[i][3]));
        st_async4(yr + i * 512, yv[4 + i][0], yv[4 + i][1], yv[4 + i][2], yv[4 + i][3], yb + 8 * (i >> 1));
        if (i & 1) { __syncwarp(); mbar_arrive_if(bar(B_Y + (i >> 1)), lane == 0); }
      }
      TSTAMP(tid == 0, 12);
    }
#pragma unroll 1
    for (int n = 23; n < 32 - TAIL; n++) {
      stage2(acc, n, false);
      TSTAMP(tid == 0 && n == 26, 14);
      wg_wait<1>();
      release2(n - 1);
      QSTAMP(n);
    }
    {
      const Tile T = tile_of();
      dA.renew(z64); dB.renew(z64);
      mbar_wait(bar(B_STG), wgu ^ 1);
#pragma unroll
      for (int n = 32 - TAIL; n < 32; n++) {
        stage2(acc, n, false);
        if (n == 28) { wg_wait<1>(); release2(27); }
      }
      mbar_wait(bar(wgu ? B_E2 + 5 : B_STG), 1);
      mbar_arrive_if(bar(B_STG), wgu == 0 && lane == 0);
      const uint32_t stg = sb + (wgu ? RB - 8192 : RU + 16384);
      wg_wait<0>();
      TSTAMP(tid == 0, 17); TSTAMP(tid == 128, 15);
      pin<64>(acc);
#pragma unroll
      for (int c = 0; c < 2; c++) {
#pragma unroll
        for (int t = 0; t < 4; t++) {
          const float* a = acc + 32 * c + 8 * t;
          stsm4(stg + c * 8192 + (stm ^ (t << 5)), pack_bf16(a[0], a[1]), pack_bf16(a[2], a[3]), pack_bf16(a[4], a[5]), pack_bf16(a[6], a[7]));
        }
        fence_async_smem();
        __syncwarp();
        tma2d_store_e(&P.outa, stg + c * 8192 + warpu * 2048, 128 * T.j + 64 * c, 128 * T.r + 16 * warpu);
      }
      bulk_wait_read();
      TSTAMP(tid == 128, 16);
    }
  } else {
    asm volatile("setmaxnreg.dec.sync.aligned.u32 %0;" :: "n"(40));
    const Tile T = tile_of();
    const int j = T.j, r = T.r;
    auto kcol = [&](int n) INL {
      return n < 20 ? 128 * (j ^ ((n >> 1) & 1)) + 64 * (n & 1) : 128 * (((j & 6) + n - (n < 26 ? 18 : 24)) & 7) + (n < 26 ? 0 : 64);
    };
    if (warpu == 8) {
      uint32_t ph = 0;
      int s = slot1(EARLY);
#pragma unroll 1
      for (int it = EARLY; it < 32; ++it, s = s + 1 == NS1 ? 0 : s + 1) {
        if (it >= NS1) { mbar_wait(bar(B_E1 + s), (ph >> s) & 1); ph ^= 1u << s; }
        if (elect()) load1(it, s, j, r, true);
      }
      int qn = 0;
      auto loadq = [&](int n) INL {
        if ((0x9c000 >> n) & 1) { if (elect()) tma5d(sb + RA + qn * 8192, &P.q, 16 * cl, 2 * rho, 2 * (qn & 2), 2 * (qn & 1), bar(B_Q)); qn++; }
      };
#pragma unroll 1
      for (int n = 0; n < 16; ++n) {
        const int s = n & 3, i = n + (n >> 1);
        mbar_wait(bar(n < 4 ? B_E1 + i : B_E2 + s), n < 4 ? (ph >> i) & 1 : ((n >> 2) - 1) & 1);
        const uint32_t st = sb + s * ST2, fb = bar(B_F2 + s);
        if (elect()) {
          mbar_expect(fb, ST2);
          tma4d(st + 16384, &P.w2, 64 * n, 2 * j, 0, fb);
          tma2d_mc(st + rho * 8192, &P.x, 64 * n, 128 * r + 64 * rho, fb);
        }
        loadq(n);
      }
      auto loadw = [&](int n) INL {
        const int s = n & 3;
        mbar_wait(bar(B_E2 + s), ((n >> 2) - 1) & 1);
        if (elect()) { mbar_expect(bar(B_F2 + s), n < 18 ? 16384 : ST2); tma4d(sb + s * ST2 + 16384, &P.wo, kcol(n), 2 * j, 0, bar(B_F2 + s)); }
      };
#pragma unroll 1
      for (int n = 16; n < 20; ++n) {
        loadw(n);
        loadq(n);
      }
#pragma unroll 1
      for (int n = 18; n < 20; ++n) {
        const uint32_t st = sb + (n & 3) * ST2, fb = bar(B_F2 + (n & 3));
        mbar_wait(bar(B_RDY + n - 18), 0);
        asm volatile("fence.proxy.async.global;" ::: "memory");
        if (elect()) { tma2d(st, &P.o, kcol(n), 128 * r, fb); tma2d(st + 8192, &P.o, kcol(n), 128 * r + 64, fb); }
      }
      mbar_wait(bar(B_OFREE), 0);
      uint64_t slots = 0x103251032510ull, frees = 0x103251032410ull;
      uint32_t pars = 0xc9f, kc = 128 * (j & 6) + 256;
#pragma unroll 1
      for (int n = 20; n < 32; ++n, slots >>= 4, frees >>= 4, pars >>= 1, kc += n == 26 ? 448 : 128) {
        const uint32_t s = slots & 7, st = sb + s * ST2, fb = bar(B_F2 + s);
        mbar_wait(bar(B_RDY + n - 18), 0);
        mbar_wait(bar(B_E2 + (frees & 7)), ~pars & 1);
        if (elect()) {
          mbar_expect(fb, ST2);
          tma4d(st + 16384, &P.wo, kc & 1023, 2 * j, 0, fb);
          tma2d_mc(st + rho * 8192, &P.o, kc & 1023, 128 * r + 64 * rho, fb);
        }
      }
    } else {
      const int at = tid - 288, aw = warpu - 9;
      const unsigned epoch = ld_relaxed(&P.g->epoch[cta]);
      if (aw < 2) {
        float4* zp = reinterpret_cast<float4*>(&P.g->kv[j][r * (KV_WORDS / 16)]) + at;
        zp[0] = zp[2] = make_float4(0.f, 0.f, 0.f, 0.f);
        sts128(sb + SM_ONES + lane * 64 + (lane & 6) * 8, 0x3f803f80u, 0x3f803f80u, 0x3f803f80u, 0x3f803f80u);
        fence_async_smem();
        bar_sync(4, 64);
        if (at == 0) {
          asm volatile("fence.release.gpu;\nred.relaxed.gpu.global.add.u32 [%0], 1;" :: "l"(&P.g->zflag[j * 32]) : "memory");
          flag_wait(&P.g->zflag[j * 32], 16u * (epoch + 1));
          mbar_arrive(bar(B_ZERO));
        }
        __syncwarp();
      } else {
#pragma unroll 1
        for (int m = -1; m < 16; m++) {
          const int s = (m >> 1) & 7;
          pace(tstart, PREP0 + (m + 1) * PREPGAP);
          if (m == 14) mbar_wait(bar(B_KVE), 0);
          if (elect()) {
            if (m < 0 || !(m & 1)) mbar_expect(bar(B_KVL + s), m < 0 ? 4096 : 8192);
            tma3d(sb + RB + (m < 0 ? 14 : m) * 4096, m > 0 && (m & 1) ? &P.v : &P.k, 16 * cl, 32 * rho + (m >> 31), 2 * (m & 14), bar(B_KVL + s));
          }
        }
#pragma unroll 1
        for (int m = 0; m < 8; m++) {
          pace(tstart, HT0 + m * HGAP);
          if (elect()) bulk_load(sb + RB + m * 4096, P.ssm_k + (size_t)(8 * cta + m) * 2048, 4096, bar(B_H));
        }
      }
      if (aw == 1) {
        if (cta < 3) pf_line(P.tab + cta * 768 + lane * 32);
#pragma unroll 1
        for (int m = 0; m < 16; m++) {
          pace(tstart, m < 4 ? WQT + m * 500 : QT + (m - 4) * QGAP);
          pf_line(m < 4 ? P.w_ptr + (size_t)(cta + (2 * m + (lane >> 4)) * 128) * 3072 + (lane & 15) * 64
                        : (m < 12 ? P.q_ptr + cta * 16384 - 8192 : P.wo_ptr + cta * 8192 - 24576) + m * 2048 + lane * 64);
        }
      }
      uint32_t f2[4];
      ldg128(f2, P.tab + 2560 + at * 4);
      if (at == 0) { mbar_wait_long(bar(B_U), 0); fence_async_smem(); mbar_arrive(bar(B_U2)); }
      mbar_wait_long(bar(B_KVM), 0);
      sts128(sb + SM_F2 + at * 16, f2[0], f2[1], f2[2], f2[3]);
      fence_async_smem();
      __syncwarp();
      mbar_arrive_if(bar(B_F2M), lane == 0);
      if (aw == 2 && elect()) {
        mbar_wait(bar(B_KVP), 0);
        asm volatile("fence.release.gpu;\nred.relaxed.gpu.global.add.u32 [%0], 1;" :: "l"(&P.g->kvflag[j * 32]) : "memory");
        flag_wait(&P.g->kvflag[j * 32], 16u * (epoch + 1));
        mbar_arrive(bar(B_KV));
        TSTAMP(true, 19);
      }
      __syncwarp();
      if (aw < 2) {
        {
          const int c = aw;
          if (c == 1) {
            mbar_wait_long(bar(B_KVI), 0);
            if (elect()) { prefetch_map(&P.o); prefetch_map(&P.outb); prefetch_map(&P.outa); }
          }
          mbar_wait_long(bar(B_OW + c), 0);
          if (c == 1) mbar_wait(bar(B_ZERO), 1);
          if (elect()) {
            const uint32_t src = sb + c * ST2;
            tma2d_store(&P.o, src, 128 * j + 64 * c, 128 * r);
            tma2d_store(&P.o, src + 8192, 128 * j + 64 * c, 128 * r + 64);
            bulk_commit();
            bulk_wait_all();
            TSTAMP(c == 0, 21); TSTAMP(c == 1, 26);
            if (c == 0) mbar_arrive(bar(B_ZERO));
            asm volatile("mbarrier.arrive.shared::cluster.b64 _, [%0];\nmbarrier.arrive.shared::cluster.b64 _, [%1];"
                         :: "r"(mapa(bar(B_OFREE), 0)), "r"(mapa(bar(B_OFREE), 1)) : "memory");
            asm volatile("fence.release.gpu;\nst.relaxed.gpu.global.u32 [%0], %1;\nmbarrier.arrive.shared::cluster.b64 _, [%2];"
                         :: "l"(&P.g->oflag[r * 32 + 2 * j + c]), "r"(epoch + 1), "r"(mapa(bar(B_RDY + c), rho ^ 1)) : "memory");
            TSTAMP(c == 0, 22); TSTAMP(c == 1, 23);
          }
          __syncwarp();
        }
      } else {
        const unsigned* fp = &P.g->oflag[r * 32 + (kcol(18 + min(lane, 13)) >> 6)];
        bool done = lane > 13 || lane < 2;
        mbar_wait_long(bar(B_OW), 0);
        for (int i = 0; !__all_sync(0xffffffffu, done) && i < kSpinLimit; i++) {
          const bool now = !done && (int)(ld_relaxed(fp) - epoch) > 0;
          if (__any_sync(0xffffffffu, now)) {
            asm volatile("fence.acquire.gpu;\nfence.proxy.async.global;" ::: "memory");
            mbar_arrive_if(bar(B_RDY + lane), now);
            TSTAMP(lane == 2 && now, 24);
          }
          done |= now;
        }
        if (lane == 0) P.g->epoch[cta] = epoch + 1;
        TSTAMP(lane == 0, 25);
      }
#pragma unroll 1
      for (int m = aw; m < 16; m += 3) {
        const int u = 4 * (m & 7) + 2 * (m >> 3);
        mbar_wait_long(bar(B_Y + (m >> 3)), 0);
        TSTAMP(at == 0 && m == 0, 20);
        const uint32_t t0 = clock32();
        const uint32_t qa = sb + RA + u * 1024 + lane * 32 + ((rho ^ 1 ^ (lane >> 2)) & 1) * 16, ya = sb + Y_IN + u * 512 + lane * 16;
        uint32_t qv[2][4], yv[2][4];
#pragma unroll
        for (int h = 0; h < 2; h++) { lds128(qv[h], qa + h * 1024); lds128(yv[h], ya + h * 512); }
#pragma unroll
        for (int h = 0; h < 2; h++) sts128(qa + h * 1024, bmul2(qv[h][0], yv[h][0]), bmul2(qv[h][1], yv[h][1]), bmul2(qv[h][2], yv[h][2]), bmul2(qv[h][3], yv[h][3]));
        fence_async_smem();
        __syncwarp();
        if (elect()) tma5d_store(&P.outb, sb + RA + u * 1024, 1024 + 16 * cl, 2 * rho, (u >> 4) * 4 + (u & 3), (u >> 2) & 3);
        if (m < PSW) pace(t0, POSTGAP);
      }
      bulk_wait_read();
      TSTAMP(at == 0, 27);
    }
  }
  TSTAMP(tid == 128, 61); GSTAMP(tid == 128, 63);
}

typedef CUresult (*EncodeFn)(CUtensorMap*, CUtensorMapDataType, cuuint32_t, void*, const cuuint64_t*, const cuuint64_t*,
                             const cuuint32_t*, const cuuint32_t*, CUtensorMapInterleave, CUtensorMapSwizzle,
                             CUtensorMapL2promotion, CUtensorMapFloatOOBfill);

void encode(EncodeFn fn, CUtensorMap* m, const void* p, int rank, const cuuint64_t* dims, const cuuint64_t* strides,
            const cuuint32_t* box, CUtensorMapSwizzle sw) {
  const cuuint32_t es[5] = {1, 1, 1, 1, 1};
  fn(m, CU_TENSOR_MAP_DATA_TYPE_BFLOAT16, rank, const_cast<void*>(p), dims, strides, box, es, CU_TENSOR_MAP_INTERLEAVE_NONE, sw,
     CU_TENSOR_MAP_L2_PROMOTION_NONE, CU_TENSOR_MAP_FLOAT_OOB_FILL_NONE);
}
void encode2d(EncodeFn fn, CUtensorMap* m, const void* p, uint64_t cols, uint64_t rows, uint32_t bc, uint32_t br, CUtensorMapSwizzle sw) {
  const cuuint64_t dims[2] = {cols, rows}, strides[1] = {cols * 2};
  const cuuint32_t box[2] = {bc, br};
  encode(fn, m, p, 2, dims, strides, box, sw);
}
void encode3d(EncodeFn fn, CUtensorMap* m, const void* p) {
  const cuuint64_t dims[3] = {1024, 64, 32}, strides[2] = {2048 * 32, 2048};
  const cuuint32_t box[3] = {16, 32, 4};
  encode(fn, m, p, 3, dims, strides, box, CU_TENSOR_MAP_SWIZZLE_32B);
}
void encode4d(EncodeFn fn, CUtensorMap* m, const void* p, uint64_t cols, uint32_t rows, uint32_t nmat) {
  const cuuint64_t dims[4] = {64, 1024, 16, cols / 1024}, strides[3] = {cols * 2, 128, 2048};
  const cuuint32_t box[4] = {64, rows, 2, nmat};
  encode(fn, m, p, 4, dims, strides, box, CU_TENSOR_MAP_SWIZZLE_128B);
}
void encode5d(EncodeFn fn, CUtensorMap* m, const void* p, uint64_t cols, uint32_t n, uint32_t nw) {
  const cuuint64_t dims[5] = {cols, 4, 16, 8, 4}, strides[4] = {cols * 2 * 512, cols * 2 * 8, cols * 2, cols * 2 * 128};
  const cuuint32_t box[5] = {16, 2, 16, n, nw};
  encode(fn, m, p, 5, dims, strides, box, CU_TENSOR_MAP_SWIZZLE_32B);
}

}

extern "C" void kernel_launch(void* const* d_in, const int* in_sizes, int n_in, void* d_out, int out_size) {
  static EncodeFn fn = nullptr;
  static void *o_ptr = nullptr, *g_ptr = nullptr, *tab_ptr = nullptr;
  if (!fn) {
    cudaDriverEntryPointQueryResult qr;
    cudaGetDriverEntryPoint("cuTensorMapEncodeTiled", (void**)&fn, cudaEnableDefault, &qr);
    cudaGetSymbolAddress(&o_ptr, g_o);
    cudaGetSymbolAddress(&g_ptr, g_scratch);
    cudaGetSymbolAddress(&tab_ptr, d_tab);
    cudaFuncSetAttribute(fused_kernel, cudaFuncAttributeMaxDynamicSharedMemorySize, SM_TOTAL);
  }
  Params P;
  encode4d(fn, &P.w1, d_in[1], 3072, 32, 2);
  encode2d(fn, &P.x, d_in[0], 1024, 2048, 64, 64, CU_TENSOR_MAP_SWIZZLE_128B);
  encode4d(fn, &P.w2, d_in[1], 3072, 64, 1);
  encode4d(fn, &P.wo, d_in[2], 1024, 64, 1);
  encode2d(fn, &P.o, o_ptr, 1024, 2048, 64, 64, CU_TENSOR_MAP_SWIZZLE_128B);
  encode2d(fn, &P.outa, d_out, 2048, 2048, 64, 16, CU_TENSOR_MAP_SWIZZLE_128B);
  encode3d(fn, &P.k, d_in[4]);
  encode3d(fn, &P.v, d_in[5]);
  encode5d(fn, &P.q, d_in[3], 1024, 4, 2);
  encode5d(fn, &P.outb, d_out, 2048, 2, 1);
  P.shift_k = (const __nv_bfloat16*)d_in[6];
  P.ssm_k = (const __nv_bfloat16*)d_in[7];
  P.ssm_d = (const __nv_bfloat16*)d_in[8];
  P.q_ptr = (const __nv_bfloat16*)d_in[3];
  P.w_ptr = (const __nv_bfloat16*)d_in[1];
  P.wo_ptr = (const __nv_bfloat16*)d_in[2];
  P.zero = 0;
  P.g = (Scratch*)g_ptr;
  P.tab = (const uint32_t*)tab_ptr;
  fused_kernel<<<kCtas, kThreads, SM_TOTAL>>>(P);
}
```

```cpp
#include <cuda.h>
#include <cuda_runtime.h>
#include <cuda_bf16.h>
#include <stdint.h>

#define DEVI __device__ __forceinline__
#define INL __attribute__((always_inline))

namespace {

DEVI void mma_kt_init(float* d, uint64_t da, uint64_t db) {
  asm volatile("{\nwgmma.mma_async.sync.aligned.m64n128k16.f32.bf16.bf16 {%0, %1, %2, %3, %4, %5, %6, %7, %8, %9, %10, %11, %12, %13, %14, %15, %16, %17, %18, %19, %20, %21, %22, %23, %24, %25, %26, %27, %28, %29, %30, %31, %32, %33, %34, %35, %36, %37, %38, %39, %40, %41, %42, %43, %44, %45, %46, %47, %48, %49, %50, %51, %52, %53, %54, %55, %56, %57, %58, %59, %60, %61, %62, %63}, %64, %65, 0, 1, 1, 1, 0;\n}\n"
    : "=f"(d[0]), "=f"(d[1]), "=f"(d[2]), "=f"(d[3]), "=f"(d[4]), "=f"(d[5]), "=f"(d[6]), "=f"(d[7]), "=f"(d[8]), "=f"(d[9]), "=f"(d[10]), "=f"(d[11]), "=f"(d[12]), "=f"(d[13]), "=f"(d[14]), "=f"(d[15]), "=f"(d[16]), "=f"(d[17]), "=f"(d[18]), "=f"(d[19]), "=f"(d[20]), "=f"(d[21]), "=f"(d[22]), "=f"(d[23]), "=f"(d[24]), "=f"(d[25]), "=f"(d[26]), "=f"(d[27]), "=f"(d[28]), "=f"(d[29]), "=f"(d[30]), "=f"(d[31]), "=f"(d[32]), "=f"(d[33]), "=f"(d[34]), "=f"(d[35]), "=f"(d[36]), "=f"(d[37]), "=f"(d[38]), "=f"(d[39]), "=f"(d[40]), "=f"(d[41]), "=f"(d[42]), "=f"(d[43]), "=f"(d[44]), "=f"(d[45]), "=f"(d[46]), "=f"(d[47]), "=f"(d[48]), "=f"(d[49]), "=f"(d[50]), "=f"(d[51]), "=f"(d[52]), "=f"(d[53]), "=f"(d[54]), "=f"(d[55]), "=f"(d[56]), "=f"(d[57]), "=f"(d[58]), "=f"(d[59]), "=f"(d[60]), "=f"(d[61]), "=f"(d[62]), "=f"(d[63])
    : "l"(da), "l"(db));
}
DEVI void mma_kt(float* d, uint64_t da, uint64_t db) {
  asm volatile("{\nwgmma.mma_async.sync.aligned.m64n128k16.f32.bf16.bf16 {%0, %1, %2, %3, %4, %5, %6, %7, %8, %9, %10, %11, %12, %13, %14, %15, %16, %17, %18, %19, %20, %21, %22, %23, %24, %25, %26, %27, %28, %29, %30, %31, %32, %33, %34, %35, %36, %37, %38, %39, %40, %41, %42, %43, %44, %45, %46, %47, %48, %49, %50, %51, %52, %53, %54, %55, %56, %57, %58, %59, %60, %61, %62, %63}, %64, %65, 1, 1, 1, 1, 0;\n}\n"
    : "+f"(d[0]), "+f"(d[1]), "+f"(d[2]), "+f"(d[3]), "+f"(d[4]), "+f"(d[5]), "+f"(d[6]), "+f"(d[7]), "+f"(d[8]), "+f"(d[9]), "+f"(d[10]), "+f"(d[11]), "+f"(d[12]), "+f"(d[13]), "+f"(d[14]), "+f"(d[15]), "+f"(d[16]), "+f"(d[17]), "+f"(d[18]), "+f"(d[19]), "+f"(d[20]), "+f"(d[21]), "+f"(d[22]), "+f"(d[23]), "+f"(d[24]), "+f"(d[25]), "+f"(d[26]), "+f"(d[27]), "+f"(d[28]), "+f"(d[29]), "+f"(d[30]), "+f"(d[31]), "+f"(d[32]), "+f"(d[33]), "+f"(d[34]), "+f"(d[35]), "+f"(d[36]), "+f"(d[37]), "+f"(d[38]), "+f"(d[39]), "+f"(d[40]), "+f"(d[41]), "+f"(d[42]), "+f"(d[43]), "+f"(d[44]), "+f"(d[45]), "+f"(d[46]), "+f"(d[47]), "+f"(d[48]), "+f"(d[49]), "+f"(d[50]), "+f"(d[51]), "+f"(d[52]), "+f"(d[53]), "+f"(d[54]), "+f"(d[55]), "+f"(d[56]), "+f"(d[57]), "+f"(d[58]), "+f"(d[59]), "+f"(d[60]), "+f"(d[61]), "+f"(d[62]), "+f"(d[63])
    : "l"(da), "l"(db));
}
DEVI void mma_n128_init(float* d, uint64_t da, uint64_t db) {
  asm volatile("{\nwgmma.mma_async.sync.aligned.m64n128k16.f32.bf16.bf16 {%0, %1, %2, %3, %4, %5, %6, %7, %8, %9, %10, %11, %12, %13, %14, %15, %16, %17, %18, %19, %20, %21, %22, %23, %24, %25, %26, %27, %28, %29, %30, %31, %32, %33, %34, %35, %36, %37, %38, %39, %40, %41, %42, %43, %44, %45, %46, %47, %48, %49, %50, %51, %52, %53, %54, %55, %56, %57, %58, %59, %60, %61, %62, %63}, %64, %65, 0, 1, 1, 0, 1;\n}\n"
    : "=f"(d[0]), "=f"(d[1]), "=f"(d[2]), "=f"(d[3]), "=f"(d[4]), "=f"(d[5]), "=f"(d[6]), "=f"(d[7]), "=f"(d[8]), "=f"(d[9]), "=f"(d[10]), "=f"(d[11]), "=f"(d[12]), "=f"(d[13]), "=f"(d[14]), "=f"(d[15]), "=f"(d[16]), "=f"(d[17]), "=f"(d[18]), "=f"(d[19]), "=f"(d[20]), "=f"(d[21]), "=f"(d[22]), "=f"(d[23]), "=f"(d[24]), "=f"(d[25]), "=f"(d[26]), "=f"(d[27]), "=f"(d[28]), "=f"(d[29]), "=f"(d[30]), "=f"(d[31]), "=f"(d[32]), "=f"(d[33]), "=f"(d[34]), "=f"(d[35]), "=f"(d[36]), "=f"(d[37]), "=f"(d[38]), "=f"(d[39]), "=f"(d[40]), "=f"(d[41]), "=f"(d[42]), "=f"(d[43]), "=f"(d[44]), "=f"(d[45]), "=f"(d[46]), "=f"(d[47]), "=f"(d[48]), "=f"(d[49]), "=f"(d[50]), "=f"(d[51]), "=f"(d[52]), "=f"(d[53]), "=f"(d[54]), "=f"(d[55]), "=f"(d[56]), "=f"(d[57]), "=f"(d[58]), "=f"(d[59]), "=f"(d[60]), "=f"(d[61]), "=f"(d[62]), "=f"(d[63])
    : "l"(da), "l"(db));
}
DEVI void mma_n128(float* d, uint64_t da, uint64_t db) {
  asm volatile("{\nwgmma.mma_async.sync.aligned.m64n128k16.f32.bf16.bf16 {%0, %1, %2, %3, %4, %5, %6, %7, %8, %9, %10, %11, %12, %13, %14, %15, %16, %17, %18, %19, %20, %21, %22, %23, %24, %25, %26, %27, %28, %29, %30, %31, %32, %33, %34, %35, %36, %37, %38, %39, %40, %41, %42, %43, %44, %45, %46, %47, %48, %49, %50, %51, %52, %53, %54, %55, %56, %57, %58, %59, %60, %61, %62, %63}, %64, %65, 1, 1, 1, 0, 1;\n}\n"
    : "+f"(d[0]), "+f"(d[1]), "+f"(d[2]), "+f"(d[3]), "+f"(d[4]), "+f"(d[5]), "+f"(d[6]), "+f"(d[7]), "+f"(d[8]), "+f"(d[9]), "+f"(d[10]), "+f"(d[11]), "+f"(d[12]), "+f"(d[13]), "+f"(d[14]), "+f"(d[15]), "+f"(d[16]), "+f"(d[17]), "+f"(d[18]), "+f"(d[19]), "+f"(d[20]), "+f"(d[21]), "+f"(d[22]), "+f"(d[23]), "+f"(d[24]), "+f"(d[25]), "+f"(d[26]), "+f"(d[27]), "+f"(d[28]), "+f"(d[29]), "+f"(d[30]), "+f"(d[31]), "+f"(d[32]), "+f"(d[33]), "+f"(d[34]), "+f"(d[35]), "+f"(d[36]), "+f"(d[37]), "+f"(d[38]), "+f"(d[39]), "+f"(d[40]), "+f"(d[41]), "+f"(d[42]), "+f"(d[43]), "+f"(d[44]), "+f"(d[45]), "+f"(d[46]), "+f"(d[47]), "+f"(d[48]), "+f"(d[49]), "+f"(d[50]), "+f"(d[51]), "+f"(d[52]), "+f"(d[53]), "+f"(d[54]), "+f"(d[55]), "+f"(d[56]), "+f"(d[57]), "+f"(d[58]), "+f"(d[59]), "+f"(d[60]), "+f"(d[61]), "+f"(d[62]), "+f"(d[63])
    : "l"(da), "l"(db));
}
DEVI void mma_kv_init(float* d, const uint32_t* a, uint64_t db, uint32_t meta) {
  asm volatile("{\nwgmma.mma_async.sp.sync.aligned.m64n40k32.f32.bf16.bf16 {%0, %1, %2, %3, %4, %5, %6, %7, %8, %9, %10, %11, %12, %13, %14, %15, %16, %17, %18, %19}, {%20,%21,%22,%23}, %24, %25, 0, 0, 1, 1, 1;\n}\n"
    : "=f"(d[0]), "=f"(d[1]), "=f"(d[2]), "=f"(d[3]), "=f"(d[4]), "=f"(d[5]), "=f"(d[6]), "=f"(d[7]), "=f"(d[8]), "=f"(d[9]), "=f"(d[10]), "=f"(d[11]), "=f"(d[12]), "=f"(d[13]), "=f"(d[14]), "=f"(d[15]), "=f"(d[16]), "=f"(d[17]), "=f"(d[18]), "=f"(d[19])
    : "r"(a[0]), "r"(a[1]), "r"(a[2]), "r"(a[3]), "l"(db), "r"(meta));
}
DEVI void mma_kv(float* d, const uint32_t* a, uint64_t db, uint32_t meta) {
  asm volatile("{\nwgmma.mma_async.sp.sync.aligned.m64n40k32.f32.bf16.bf16 {%0, %1, %2, %3, %4, %5, %6, %7, %8, %9, %10, %11, %12, %13, %14, %15, %16, %17, %18, %19}, {%20,%21,%22,%23}, %24, %25, 0, 1, 1, 1, 1;\n}\n"
    : "+f"(d[0]), "+f"(d[1]), "+f"(d[2]), "+f"(d[3]), "+f"(d[4]), "+f"(d[5]), "+f"(d[6]), "+f"(d[7]), "+f"(d[8]), "+f"(d[9]), "+f"(d[10]), "+f"(d[11]), "+f"(d[12]), "+f"(d[13]), "+f"(d[14]), "+f"(d[15]), "+f"(d[16]), "+f"(d[17]), "+f"(d[18]), "+f"(d[19])
    : "r"(a[0]), "r"(a[1]), "r"(a[2]), "r"(a[3]), "l"(db), "r"(meta));
}
DEVI void mma_o_init(float* d, const uint32_t* a, uint64_t db) {
  asm volatile("{\nwgmma.mma_async.sync.aligned.m64n40k16.f32.bf16.bf16 {%0, %1, %2, %3, %4, %5, %6, %7, %8, %9, %10, %11, %12, %13, %14, %15, %16, %17, %18, %19}, {%20,%21,%22,%23}, %24, 0, 1, 1, 1;\n}\n"
    : "=f"(d[0]), "=f"(d[1]), "=f"(d[2]), "=f"(d[3]), "=f"(d[4]), "=f"(d[5]), "=f"(d[6]), "=f"(d[7]), "=f"(d[8]), "=f"(d[9]), "=f"(d[10]), "=f"(d[11]), "=f"(d[12]), "=f"(d[13]), "=f"(d[14]), "=f"(d[15]), "=f"(d[16]), "=f"(d[17]), "=f"(d[18]), "=f"(d[19])
    : "r"(a[0]), "r"(a[1]), "r"(a[2]), "r"(a[3]), "l"(db));
}
DEVI void mma_o(float* d, const uint32_t* a, uint64_t db) {
  asm volatile("{\nwgmma.mma_async.sync.aligned.m64n40k16.f32.bf16.bf16 {%0, %1, %2, %3, %4, %5, %6, %7, %8, %9, %10, %11, %12, %13, %14, %15, %16, %17, %18, %19}, {%20,%21,%22,%23}, %24, 1, 1, 1, 1;\n}\n"
    : "+f"(d[0]), "+f"(d[1]), "+f"(d[2]), "+f"(d[3]), "+f"(d[4]), "+f"(d[5]), "+f"(d[6]), "+f"(d[7]), "+f"(d[8]), "+f"(d[9]), "+f"(d[10]), "+f"(d[11]), "+f"(d[12]), "+f"(d[13]), "+f"(d[14]), "+f"(d[15]), "+f"(d[16]), "+f"(d[17]), "+f"(d[18]), "+f"(d[19])
    : "r"(a[0]), "r"(a[1]), "r"(a[2]), "r"(a[3]), "l"(db));
}
DEVI void mma_s1_init(uint32_t* d, const uint32_t* a, uint64_t db) {
  asm volatile("{\nwgmma.mma_async.sync.aligned.m64n128k16.f16.f16.f16 {%0, %1, %2, %3, %4, %5, %6, %7, %8, %9, %10, %11, %12, %13, %14, %15, %16, %17, %18, %19, %20, %21, %22, %23, %24, %25, %26, %27, %28, %29, %30, %31}, {%32,%33,%34,%35}, %36, 0, 1, 1, 1;\n}\n"
    : "=r"(d[0]), "=r"(d[1]), "=r"(d[2]), "=r"(d[3]), "=r"(d[4]), "=r"(d[5]), "=r"(d[6]), "=r"(d[7]), "=r"(d[8]), "=r"(d[9]), "=r"(d[10]), "=r"(d[11]), "=r"(d[12]), "=r"(d[13]), "=r"(d[14]), "=r"(d[15]), "=r"(d[16]), "=r"(d[17]), "=r"(d[18]), "=r"(d[19]), "=r"(d[20]), "=r"(d[21]), "=r"(d[22]), "=r"(d[23]), "=r"(d[24]), "=r"(d[25]), "=r"(d[26]), "=r"(d[27]), "=r"(d[28]), "=r"(d[29]), "=r"(d[30]), "=r"(d[31])
    : "r"(a[0]), "r"(a[1]), "r"(a[2]), "r"(a[3]), "l"(db));
}
DEVI void mma_s1(uint32_t* d, const uint32_t* a, uint64_t db) {
  asm volatile("{\nwgmma.mma_async.sync.aligned.m64n128k16.f16.f16.f16 {%0, %1, %2, %3, %4, %5, %6, %7, %8, %9, %10, %11, %12, %13, %14, %15, %16, %17, %18, %19, %20, %21, %22, %23, %24, %25, %26, %27, %28, %29, %30, %31}, {%32,%33,%34,%35}, %36, 1, 1, 1, 1;\n}\n"
    : "+r"(d[0]), "+r"(d[1]), "+r"(d[2]), "+r"(d[3]), "+r"(d[4]), "+r"(d[5]), "+r"(d[6]), "+r"(d[7]), "+r"(d[8]), "+r"(d[9]), "+r"(d[10]), "+r"(d[11]), "+r"(d[12]), "+r"(d[13]), "+r"(d[14]), "+r"(d[15]), "+r"(d[16]), "+r"(d[17]), "+r"(d[18]), "+r"(d[19]), "+r"(d[20]), "+r"(d[21]), "+r"(d[22]), "+r"(d[23]), "+r"(d[24]), "+r"(d[25]), "+r"(d[26]), "+r"(d[27]), "+r"(d[28]), "+r"(d[29]), "+r"(d[30]), "+r"(d[31])
    : "r"(a[0]), "r"(a[1]), "r"(a[2]), "r"(a[3]), "l"(db));
}
DEVI void mma_s2_init(uint32_t* d, const uint32_t* a, uint64_t db) {
  asm volatile("{\nwgmma.mma_async.sync.aligned.m64n32k16.f16.f16.f16 {%0, %1, %2, %3, %4, %5, %6, %7}, {%8,%9,%10,%11}, %12, 0, 1, 1, 0;\n}\n"
    : "=r"(d[0]), "=r"(d[1]), "=r"(d[2]), "=r"(d[3]), "=r"(d[4]), "=r"(d[5]), "=r"(d[6]), "=r"(d[7])
    : "r"(a[0]), "r"(a[1]), "r"(a[2]), "r"(a[3]), "l"(db));
}
DEVI void mma_s2(uint32_t* d, const uint32_t* a, uint64_t db) {
  asm volatile("{\nwgmma.mma_async.sync.aligned.m64n32k16.f16.f16.f16 {%0, %1, %2, %3, %4, %5, %6, %7}, {%8,%9,%10,%11}, %12, 1, 1, 1, 0;\n}\n"
    : "+r"(d[0]), "+r"(d[1]), "+r"(d[2]), "+r"(d[3]), "+r"(d[4]), "+r"(d[5]), "+r"(d[6]), "+r"(d[7])
    : "r"(a[0]), "r"(a[1]), "r"(a[2]), "r"(a[3]), "l"(db));
}
DEVI void mma_s2_neg(uint32_t* d, const uint32_t* a, uint64_t db) {
  asm volatile("{\nwgmma.mma_async.sync.aligned.m64n32k16.f16.f16.f16 {%0, %1, %2, %3, %4, %5, %6, %7}, {%8,%9,%10,%11}, %12, 1, -1, 1, 0;\n}\n"
    : "+r"(d[0]), "+r"(d[1]), "+r"(d[2]), "+r"(d[3]), "+r"(d[4]), "+r"(d[5]), "+r"(d[6]), "+r"(d[7])
    : "r"(a[0]), "r"(a[1]), "r"(a[2]), "r"(a[3]), "l"(db));
}
DEVI void mma_i2_init(float* d, const uint32_t* a, uint64_t db, uint32_t meta) {
  asm volatile("{\nwgmma.mma_async.sp.sync.aligned.m64n128k32.f32.f16.f16 {%0, %1, %2, %3, %4, %5, %6, %7, %8, %9, %10, %11, %12, %13, %14, %15, %16, %17, %18, %19, %20, %21, %22, %23, %24, %25, %26, %27, %28, %29, %30, %31, %32, %33, %34, %35, %36, %37, %38, %39, %40, %41, %42, %43, %44, %45, %46, %47, %48, %49, %50, %51, %52, %53, %54, %55, %56, %57, %58, %59, %60, %61, %62, %63}, {%64,%65,%66,%67}, %68, %69, 0, 0, 1, 1, 1;\n}\n"
    : "=f"(d[0]), "=f"(d[1]), "=f"(d[2]), "=f"(d[3]), "=f"(d[4]), "=f"(d[5]), "=f"(d[6]), "=f"(d[7]), "=f"(d[8]), "=f"(d[9]), "=f"(d[10]), "=f"(d[11]), "=f"(d[12]), "=f"(d[13]), "=f"(d[14]), "=f"(d[15]), "=f"(d[16]), "=f"(d[17]), "=f"(d[18]), "=f"(d[19]), "=f"(d[20]), "=f"(d[21]), "=f"(d[22]), "=f"(d[23]), "=f"(d[24]), "=f"(d[25]), "=f"(d[26]), "=f"(d[27]), "=f"(d[28]), "=f"(d[29]), "=f"(d[30]), "=f"(d[31]), "=f"(d[32]), "=f"(d[33]), "=f"(d[34]), "=f"(d[35]), "=f"(d[36]), "=f"(d[37]), "=f"(d[38]), "=f"(d[39]), "=f"(d[40]), "=f"(d[41]), "=f"(d[42]), "=f"(d[43]), "=f"(d[44]), "=f"(d[45]), "=f"(d[46]), "=f"(d[47]), "=f"(d[48]), "=f"(d[49]), "=f"(d[50]), "=f"(d[51]), "=f"(d[52]), "=f"(d[53]), "=f"(d[54]), "=f"(d[55]), "=f"(d[56]), "=f"(d[57]), "=f"(d[58]), "=f"(d[59]), "=f"(d[60]), "=f"(d[61]), "=f"(d[62]), "=f"(d[63])
    : "r"(a[0]), "r"(a[1]), "r"(a[2]), "r"(a[3]), "l"(db), "r"(meta));
}
DEVI void mma_i2(float* d, const uint32_t* a, uint64_t db, uint32_t meta) {
  asm volatile("{\nwgmma.mma_async.sp.sync.aligned.m64n128k32.f32.f16.f16 {%0, %1, %2, %3, %4, %5, %6, %7, %8, %9, %10, %11, %12, %13, %14, %15, %16, %17, %18, %19, %20, %21, %22, %23, %24, %25, %26, %27, %28, %29, %30, %31, %32, %33, %34, %35, %36, %37, %38, %39, %40, %41, %42, %43, %44, %45, %46, %47, %48, %49, %50, %51, %52, %53, %54, %55, %56, %57, %58, %59, %60, %61, %62, %63}, {%64,%65,%66,%67}, %68, %69, 0, 1, 1, 1, 1;\n}\n"
    : "+f"(d[0]), "+f"(d[1]), "+f"(d[2]), "+f"(d[3]), "+f"(d[4]), "+f"(d[5]), "+f"(d[6]), "+f"(d[7]), "+f"(d[8]), "+f"(d[9]), "+f"(d[10]), "+f"(d[11]), "+f"(d[12]), "+f"(d[13]), "+f"(d[14]), "+f"(d[15]), "+f"(d[16]), "+f"(d[17]), "+f"(d[18]), "+f"(d[19]), "+f"(d[20]), "+f"(d[21]), "+f"(d[22]), "+f"(d[23]), "+f"(d[24]), "+f"(d[25]), "+f"(d[26]), "+f"(d[27]), "+f"(d[28]), "+f"(d[29]), "+f"(d[30]), "+f"(d[31]), "+f"(d[32]), "+f"(d[33]), "+f"(d[34]), "+f"(d[35]), "+f"(d[36]), "+f"(d[37]), "+f"(d[38]), "+f"(d[39]), "+f"(d[40]), "+f"(d[41]), "+f"(d[42]), "+f"(d[43]), "+f"(d[44]), "+f"(d[45]), "+f"(d[46]), "+f"(d[47]), "+f"(d[48]), "+f"(d[49]), "+f"(d[50]), "+f"(d[51]), "+f"(d[52]), "+f"(d[53]), "+f"(d[54]), "+f"(d[55]), "+f"(d[56]), "+f"(d[57]), "+f"(d[58]), "+f"(d[59]), "+f"(d[60]), "+f"(d[61]), "+f"(d[62]), "+f"(d[63])
    : "r"(a[0]), "r"(a[1]), "r"(a[2]), "r"(a[3]), "l"(db), "r"(meta));
}
__device__ const __align__(128) uint32_t d_tab[2944] = {
  0x3bf13bff,0x2fbd25e4,0x38ee3986,0x3a4d39c9,0x3b9a3bcf,0x34ff32f7,0x3737384a,0x3b243ac1,0x3af73b52,0x37dd3676,0x344b35c8,0x3bb53b76,
  0x3a113a8c,0x39373899,0x2cce3185,0x3bfa3be1,0x3a933bf2,0x388e2f59,0xb1b6b8f8,0xbbdfba45,0xa452374e,0x3c003b1e,0x39c034e7,0xb990bb9e,
  0xbabab7c8,0x38553afe,0x3bd23bb2,0x32c6b463,0xbb57bbf9,0xb65f2d33,0x35df3a19,0x3b71392e,0x37643bd4,0x3b183294,0xb4cf385f,0x3ba13ab3,
  0xbbaeb648,0x347b3b5c,0xbb04bb6c,0xb7b235f7,0xad97ba9b,0xbbf8b884,0x3924b1e8,0xba21bbdd,0x3bf439b8,0x2ef5b999,0x39023c00,0x3a3d217f,
  0x9cb63ba5,0x3c0034b7,0x39afb77a,0xb9a1bb13,0xb86abbab,0xbaac3493,0xb2633b0a,0x3bd7379b,0x3b60391b,0x3631ba29,0xb60ebbf7,0xbb682dfb,
  0xbbdaae91,0x32193bf5,0x3aa23a35,0x387ab90c,0xb7853b65,0x3b10361a,0xbba73625,0x34ab3b63,0x3911baa9,0xba31b86f,0x3bf6b24b,0xae5fbbd8,
  0xba2d39aa,0x391639a6,0xbbf61648,0xae2d3c00,0x3b0db874,0xb790baa5,0x3ba93232,0x349fbbd9,0xba9e3b16,0x387f376f,0x3bdcb4c3,0x3201bba3,
  0x3b6aaec3,0x3602bbf5,0xb63cb907,0xbb5e3a39,0xb27cba25,0xbbd6391f,0xb8653bf8,0x3ab02dc9,0xb99d3bac,0x39b33487,0x3c00b7a6,0x9fdbbb07,
  0xbbf33ab6,0x2f27385a,0xba4132ad,0xb8fd3bd3,0xad653994,0x3bf9b9bc,0xba1d3c00,0x3929a311,0x3bb0b889,0x346fba97,0x37bd31cf,0x3b01bbde,
  0x3759bb59,0xbb1b3654,0x3b9fbb6f,0xb4dbb5eb,0xbb733a49,0xb5d438f3,0x366baf8b,0x3b54bbf2,0xbbd03bfa,0x32de2d00,0x3abdb933,0x3850ba15,
  0xb98b3afb,0x39c5b7d2,0x3c00bbb3,0xa51bb457,0xb19e3742,0x3be0bb21,0x3a90bb9c,0xb89434f3,0xb93c39cd,0xba0d3982,0x2c9c26ad,0xbbfb3bff,
  0xb7e8389e,0xbaf43a89,0x343eb16c,0xbbb73be2,0xb50b3682,0xbb983b4f,0x372cb5bc,0xbb273b78,0xafef330f,0xbbf03bce,0x38eab845,0xba503ac4,
  0xb3403946,0xbbcb3a04,0xb83a2c38,0x3acbbbfc,0x3979b426,0xb9d63bba,0xbbff3aee,0x281fb7fe,0x3be4bb94,0x313b3523,0xb8a83b2c,0xba813715,
  0x3699ba58,0x3b4ab8e0,0x35a53029,0xbb7c3bef,0x340e38b2,0xbbbd3a7a,0x3ae8b109,0xb80a3be6,0x3b32bb45,0x36ff36af,0x353abb81,0x3b90b58d,
  0xb8d6b371,0x3a60bbc8,0xbbed3830,0x305bbad1,0xb94f3bfe,0xb9fca8e8,0x2ba739df,0xbbfc3970,0x39663815,0xb9e73ae1,0xbbfe33eb,0x29b1bbc0,
  0xb0d7bb37,0x3be8b6e8,0x3a733552,0xb8bc3b8b,0xb6c63beb,0xbb3fb08d,0xb576ba67,0x3b85b8cc,0x3ad8b9f4,0x38253958,0xb3a23bfd,0xbbc52ade,
  0x3b8736dd,0xb56a3b3a,0x3b3db55e,0x36d23b89,0xbbe9b3d3,0x30bebbc2,0xba6f381a,0xb8c1bade,0x3bfe2a7a,0x2a163bfd,0x3962b95d,0x39eb39f0,
  0xbbc330a6,0xb3babbea,0xb8203a6b,0xbadbb8c7,0x3bec3581,0x30743b83,0xb8d136bb,0xba64bb42,0xb6f438b7,0xbb35ba76,0xb546bbe7,0x3b8e30f0,
  0xb80fbbfe,0x3ae5a94d,0x3bbf396b,0xb40239e3,0x3bfd382a,0xab433ad5,0xb9f83389,0xb954bbc6,0x3a7e341a,0x38ad3bbc,0x3122b805,0x3be53aeb,
  0x39da3bfc,0xb974ac06,0x3bff3a00,0x2884394a,0xb8353042,0xbacebbee,0x33593a5c,0xbbc9b8db,0xbb7fbb92,0x3599b52f,0xbb47b70a,0xb6a4bb2f,
  0x37213153,0x3b2a3be3,0x351738a3,0xbb96ba85,0x3af1397d,0x37f339d2,0xb4322776,0xbbb8bbff,0x3bfb3bcc,0xac6a3328,0xba09b840,0xb941bac7,
  0x3a543b7a,0xb8e5b5b1,0xbbefbb4c,0xb010b68d,0x32f72fbd,0xbbcfbbf1,0x3ac13a4d,0xb84ab8ee,0x367634ff,0xbb52bb9a,0x3b763b24,0xb5c8b737,
  0x389937dd,0xba8cbaf7,0x3be13bb5,0xb185b44b,0x39c93937,0xb986ba11,0x3bff3bfa,0x25e4acce,0x392e32c6,0xba19bbd2,0xbbf9baba,0x2d333855,
  0x3bf23b71,0x2f59b5df,0xb8f8bb57,0xba45b65f,0x374e3a93,0x3b1e388e,0x34e7b1b6,0xbb9ebbdf,0xb7c8a452,0x3afe3c00,0x3bb239c0,0xb463b990,
  0x3b6c34cf,0xb5f7bba1,0x3b5c3b18,0x3648b764,0x31e83b04,0x3bdd37b2,0xb884347b,0x3a9b3bae,0xbc00b924,0xa17f3a21,0xb999bbf8,0xb9b82d97,
  0x3294b902,0xbbd4ba3d,0x3ab32ef5,0xb85fbbf4,0x3bf53631,0x2e91bb60,0xb90cbb68,0xba35360e,0xbb133219,0x377a3bda,0x3ba5387a,0x34b7baa2,
  0x379bb9a1,0xbb0ab9af,0xbbab9cb6,0x34933c00,0x2dfb3bd7,0x3bf73263,0x391bb86a,0xba29baac,0x3aa93785,0x386fbb10,0x324b3ba7,0x3bd8b4ab,
  0xb9aab911,0xb9a63a31,0x9648bbf6,0xbc002e5f,0x38743a2d,0x3aa5b916,0xb2323bf6,0x3bd92e2d,0xb625bb0d,0xbb633790,0x361abba9,0xbb65b49f,
  0x37a63865,0x3b07bab0,0x3487bbd6,0xbbac327c,0x376fbc00,0xbb161fdb,0xbba339b3,0x34c3399d,0xbbf5387f,0x2ec33a9e,0x3a393201,0x3907bbdc,
  0x391f3602,0x3a25bb6a,0x2dc9bb5e,0xbbf8363c,0x231138fd,0x3c00ba41,0xb9943bf3,0x39bcaf27,0x3bdeb929,0x31cfba1d,0x38892d65,0x3a97bbf9,
  0x35ebbb01,0xbb6f37bd,0x3b59bbb0,0xb654b46f,0xbab634db,0xb85a3b9f,0xb2adb759,0xbbd33b1b,0xb742398b,0x3b21b9c5,0x3b9cbc00,0xb4f3251b,
  0x2f8b319e,0x3bf2bbe0,0x38f3ba90,0xba493894,0x3933b66b,0x3a15bb54,0x2d00b5d4,0xbbfa3b73,0x3bb3babd,0x3457b850,0xb7d232de,0xbafb3bd0,
  0xba893a0d,0x389eb93c,0xbbe23bfb,0xb16c2c9c,0xbb4f3af4,0x3682b7e8,0xbb783bb7,0xb5bc343e,0xbbce3b98,0x330fb50b,0xbac43b27,0xb845372c,
  0xbbff3bf0,0x26adafef,0xb9cd3a50,0xb98238ea,0xbbef3a81,0x3029b8a8,0x3a58bbe4,0x38e0b13b,0xb9463b7c,0xba0435a5,0xac38b699,0x3bfcbb4a,
  0x34263340,0xbbba3bcb,0xbaee383a,0x37febacb,0x3b94b979,0xb52339d6,0xbb2c3bff,0xb715a81f,0xbb813ae8,0xb58db80a,0xb6af3bbd,0xbb45340e,
  0x3830353a,0xbad13b90,0x3bc8b6ff,0xb3713b32,0x39dfbbed,0x3970305b,0x28e8ba60,0x3bfeb8d6,0xba7a2ba7,0x38b2bbfc,0xbbe639fc,0xb109b94f,
  0xb9583b3f,0xb9f4b6c6,0xaadebb85,0x3bfdb576,0x3bc0b825,0x33eb3ad8,0xb8153bc5,0xbae1b3a2,0xbb8ba9b1,0x3552bbfe,0x3b37b966,0x36e839e7,
  0x38cc38bc,0xba673a73,0xbbeb30d7,0x308dbbe8,0xb3d33b87,0xbbc2b56a,0x381a3b3d,0xbade36d2,0x2a7abbe9,0x3bfd30be,0xb95dba6f,0x39f0b8c1,
  0x30a63bfe,0xbbea2a16,0x3a6b3962,0xb8c739eb,0xb55ebbc3,0x3b89b3ba,0xbb3ab820,0x36ddbadb,0x33893bbf,0xbbc6b402,0xbad5bae5,0x382ab80f,
  0xbb83b9f8,0x3581b954,0x3b422b43,0x36bb3bfd,0x3a76b074,0x38b73bec,0xb0f03a64,0xbbe7b8d1,0x294d3b35,0xbbfeb6f4,0xb9e3bb8e,0x396bb546,
  0x394a3be5,0xba00b122,0x3bfc3a7e,0xac0638ad,0xb8db2884,0xba5cbbff,0x304239da,0xbbeeb974,0xbb2fbbc9,0x370ab359,0xbb92b835,0xb52fbace,
  0x341ab6a4,0x3bbc3b47,0xb805bb7f,0x3aeb3599,0x3b7a3bfb,0xb5b1ac6a,0xbb4cba09,0xb68db941,0x38a33a54,0xba85b8e5,0xbbe3bbef,0x3153b010,
  0x27763517,0xbbffbb96,0xb9d2bb2a,0x397d3721,0xb840b432,0xbac7bbb8,0xb328b7f3,0x3bcc3af1,0x3be23bfb,0x316c2c9c,0x389e393c,0x3a893a0d,
  0x3b783bb7,0x35bc343e,0x368237e8,0x3b4f3af4,0x3ac43b27,0x3845372c,0x330f350b,0x3bce3b98,0x39cd3a50,0x398238ea,0x26ad2fef,0x3bff3bf0,
  0x39463b7c,0x3a0435a5,0x2c38b699,0xbbfcbb4a,0xb4263340,0x3bba3bcb,0x3aee383a,0xb7febacb,0xbb94b979,0x352339d6,0x3b2c3bff,0x3715a81f,
  0xba58bbe4,0xb8e0b13b,0x302938a8,0x3bef3a81,0x28e83a60,0x3bfe38d6,0xb970305b,0x39df3bed,0xbbe6b9fc,0xb109394f,0xb8b2bbfc,0xba7aaba7,
  0x358db80a,0xbb81bae8,0x3b45340e,0xb6afbbbd,0x3ad13b90,0x3830b53a,0x33713b32,0x3bc836ff,0xb8cc38bc,0x3a673a73,0x3beb30d7,0xb08dbbe8,
  0x2adebb85,0xbbfdb576,0xb9f436c6,0x39583b3f,0x38153bc5,0x3ae1b3a2,0x33ebbad8,0xbbc0b825,0xbb37b966,0xb6e839e7,0x35523bfe,0x3b8ba9b1,
  0xbbc2356a,0x33d33b87,0xbadeb6d2,0xb81a3b3d,0x3bfdb0be,0xaa7abbe9,0x39f038c1,0x395dba6f,0xbbeaaa16,0xb0a63bfe,0xb8c7b9eb,0xba6b3962,
  0x3b8933ba,0x355ebbc3,0x36dd3adb,0x3b3ab820,0xbb422b43,0xb6bb3bfd,0x35813954,0x3b83b9f8,0x30f03a64,0x3be7b8d1,0x38b7bbec,0xba76b074,
  0x39e3bb8e,0xb96bb546,0xbbfe36f4,0xa94d3b35,0xbbc63402,0xb3893bbf,0x382a380f,0x3ad5bae5,0xb70ab359,0xbb2f3bc9,0x352fbace,0xbb923835,
  0xbbbc3b47,0x341a36a4,0xbaeb3599,0xb8053b7f,0x2c0638ad,0x3bfcba7e,0xb94a3be5,0x3a00b122,0x3beeb974,0x3042b9da,0x38db2884,0x3a5cbbff,
  0x3328b7f3,0xbbcc3af1,0xbac73bb8,0x3840b432,0xb5b12c6a,0xbb7a3bfb,0xb68d3941,0x3b4cba09,0xba8538e5,0xb8a33a54,0x31533010,0x3be3bbef,
  0xbbff3b96,0xa7763517,0x397db721,0x39d2bb2a,0x3a4db9c9,0xb8ee3986,0x3bf1bbff,0x2fbda5e4,0x3b24bac1,0xb737384a,0x3b9abbcf,0x34ffb2f7,
  0x3bb5bb76,0xb44b35c8,0x3af7bb52,0x37ddb676,0x3bfabbe1,0xacce3185,0x3a11ba8c,0x3937b899,0x3c00bb1e,0x2452374e,0xb9903b9e,0xb9c034e7,
  0x3855bafe,0x3abab7c8,0x32c63463,0xbbd23bb2,0xb65fad33,0x3b57bbf9,0x3b71b92e,0xb5df3a19,0xbbdf3a45,0x31b6b8f8,0x3a93bbf2,0x388eaf59,
  0x3a21bbdd,0x392431e8,0x2d97ba9b,0x3bf8b884,0xba3d217f,0x3902bc00,0xbbf439b8,0xaef5b999,0xb7643bd4,0xbb183294,0x34cf385f,0xbba13ab3,
  0x3baeb648,0xb47b3b5c,0x3b04bb6c,0x37b235f7,0x3219bbf5,0x3bdaae91,0x387a390c,0xbaa23a35,0xb9a13b13,0xb9afb77a,0x9cb6bba5,0x3c00b4b7,
  0x3bd7b79b,0x32633b0a,0xb86a3bab,0xbaacb493,0xbb68adfb,0x360ebbf7,0x3b60b91b,0x36313a29,0xb785bb65,0x3b10b61a,0xbba7b625,0x34abbb63,
  0x39113aa9,0xba31386f,0x3bf6324b,0xae5f3bd8,0xba2db9aa,0x3916b9a6,0xbbf69648,0xae2dbc00,0x3b0d3874,0xb7903aa5,0x3ba9b232,0x349f3bd9,
  0xbb5eba39,0x363cb907,0x3b6a2ec3,0x36023bf5,0x3ab0adc9,0x38653bf8,0xb27c3a25,0xbbd6b91f,0x9fdb3b07,0xbc00b7a6,0xb99dbbac,0x39b3b487,
  0xba9ebb16,0x387fb76f,0x3bdc34c3,0x32013ba3,0xbbb0b889,0xb46fba97,0xb7bd31cf,0xbb01bbde,0xb759bb59,0x3b1b3654,0xbb9fbb6f,0x34dbb5eb,
  0x3a4132ad,0x38fd3bd3,0x2f27b85a,0x3bf33ab6,0x3a1d3c00,0xb929a311,0x3bf939bc,0x2d653994,0xb894b4f3,0xba90bb9c,0xb19eb742,0x3be03b21,
  0xbb73ba49,0xb5d4b8f3,0x366b2f8b,0x3b543bf2,0xbbd0bbfa,0x32dead00,0x3abd3933,0x38503a15,0xb98bbafb,0x39c537d2,0x3c003bb3,0xa51b3457,
  0xb43eb16c,0x3bb73be2,0xbaf4ba89,0x37e8389e,0xb72cb5bc,0x3b273b78,0xbb98bb4f,0x350b3682,0xb8eab845,0x3a503ac4,0xbbf0bbce,0x2fef330f,
  0xba0db982,0x393c39cd,0xbbfbbbff,0xac9c26ad,0xba81b715,0x38a83b2c,0x3be43b94,0x313bb523,0xbb7cbbef,0xb5a53029,0x36993a58,0x3b4a38e0,
  0xb340b946,0xbbcbba04,0xb83aac38,0x3acb3bfc,0x39793426,0xb9d6bbba,0xbbffbaee,0x281f37fe,0xbbfcb970,0xaba739df,0xb94fbbfe,0xb9fc28e8,
  0x340eb8b2,0xbbbdba7a,0x3ae83109,0xb80abbe6,0x3b323b45,0x36ffb6af,0x353a3b81,0x3b90358d,0xb8d63371,0x3a603bc8,0xbbedb830,0x305b3ad1,
  0xb9e7bae1,0xb9663815,0x29b13bc0,0x3bfe33eb,0x3be836e8,0x30d7bb37,0xb8bcbb8b,0xba733552,0xbb3f308d,0x36c63beb,0x3b8538cc,0x3576ba67,
  0x3825b958,0xbad8b9f4,0xbbc5aade,0x33a23bfd,0xb0bebbc2,0xbbe933d3,0x38c1bade,0xba6fb81a,0xaa163bfd,0x3bfeaa7a,0xb9eb39f0,0x3962395d,
  0x33babbea,0xbbc3b0a6,0x3adbb8c7,0xb820ba6b,0xb6d23b89,0x3b3d355e,0xbb8736dd,0x356a3b3a,0x380fbbfe,0xbae5a94d,0xbbbf396b,0x340239e3,
  0xbbfd382a,0x2b433ad5,0x39f83389,0x3954bbc6,0x38d136bb,0x3a64bb42,0x3074bb83,0xbbec3581,0x3546bbe7,0xbb8e30f0,0xbb353a76,0x36f438b7,
  0x3b7fbb92,0xb599b52f,0x3b47b70a,0x36a4bb2f,0xb122b805,0xbbe53aeb,0x38adbbbc,0xba7e341a,0xbbff3a00,0xa884394a,0xb9742c06,0xb9da3bfc,
  0xb3593a5c,0x3bc9b8db,0xbace3bee,0x38353042,0x3b96ba85,0x3517b8a3,0xb7213153,0xbb2a3be3,0x3bb8bbff,0xb432a776,0xbaf1397d,0xb7f339d2,
  0x3941bac7,0xba093840,0xbbfb3bcc,0x2c6a3328,0x3010b68d,0xbbef3b4c,0xba543b7a,0x38e5b5b1,0x384ab8ee,0x3ac1ba4d,0xb2f72fbd,0x3bcfbbf1,
  0x35c8b737,0x3b76bb24,0xb67634ff,0x3b52bb9a,0x3185b44b,0x3be1bbb5,0xb89937dd,0x3a8cbaf7,0xa5e4acce,0x3bffbbfa,0xb9c93937,0x3986ba11,
  0xaf59b5df,0x3bf2bb71,0x3a45b65f,0xb8f83b57,0xbb1e388e,0x374eba93,0x3b9ebbdf,0x34e731b6,0xbafe3c00,0xb7c82452,0x3463b990,0x3bb2b9c0,
  0xad333855,0xbbf93aba,0xb92e32c6,0x3a19bbd2,0xb9b8ad97,0x3999bbf8,0xbc003924,0xa17fba21,0xb85f3bf4,0xbab32ef5,0x32943902,0xbbd43a3d,
  0x3b6cb4cf,0xb5f73ba1,0x3b5cbb18,0x36483764,0x31e8bb04,0x3bddb7b2,0xb884b47b,0x3a9bbbae,0xbbf73263,0x2dfbbbd7,0x3a29baac,0x391b386a,
  0x3a35360e,0xb90c3b68,0xbbf53631,0xae91bb60,0xb4b7baa2,0x3ba5b87a,0x3b133219,0xb77a3bda,0xb4933c00,0xbbab1cb6,0xb79bb9a1,0x3b0ab9af,
  0xbaa93785,0xb86fbb10,0xb24b3ba7,0xbbd8b4ab,0x39aab911,0x39a63a31,0x1648bbf6,0x3c002e5f,0xb8743a2d,0xbaa5b916,0x32323bf6,0xbbd92e2d,
  0x3625bb0d,0x3b633790,0xb61abba9,0x3b65b49f,0xb4c3399d,0xbba3b9b3,0xb76fbc00,0x3b161fdb,0xb907bbdc,0x3a39b201,0x3bf5387f,0xaec33a9e,
  0x3bf8363c,0x2dc93b5e,0xb91f3602,0xba25bb6a,0xb7a63865,0xbb07bab0,0xb487bbd6,0x3bac327c,0x35eb3b01,0xbb6fb7bd,0x3b593bb0,0xb654346f,
  0xbab6b4db,0xb85abb9f,0xb2ad3759,0xbbd3bb1b,0xb994bbf3,0x39bc2f27,0xbc00ba41,0x2311b8fd,0x3889ad65,0x3a973bf9,0xb1cfba1d,0x3bde3929,
  0x3afb3bd0,0xb7d2b2de,0xbbb3babd,0xb457b850,0x3742398b,0xbb21b9c5,0xbb9cbc00,0x34f3251b,0xaf8b319e,0xbbf2bbe0,0xb8f3ba90,0x3a493894,
  0xb933b66b,0xba15bb54,0xad00b5d4,0x3bfa3b73,0x211b21e4,0xa51ba5e4,0x98b69248,0x1cb61648,0x1f122052,0xa311a452,0x9d7f9bdb,0x217f1fdb,
  0x1bdb1d7f,0x9fdba17f,0xa0529f12,0x24522311,0x124818b6,0x96489cb6,0xa1e4a11b,0x25e4251b,0x2a632b5f,0xae5faf59,0xa1e49bdb,0x25e41fdb,
  0x286b2967,0xac6aad65,0xa6e0a4e9,0x2ade28e8,0x24e926e0,0xa8e8aade,0xa967a86b,0x2d652c6a,0x1bdb21e4,0x9fdba5e4,0xab5faa63,0x2f592e5f,
  0x2dc22ea7,0xb1b6b294,0xa54d9f12,0x294d2311,0x2bf62cde,0xafefb0d7,0xaa31a86b,0x2e2d2c6a,0x286b2a31,0xac6aae2d,0xacdeabf6,0x30d72fef,
  0x1f12254d,0xa311a94d,0xaea7adc2,0x329431b6,0x302c30d2,0xb41ab4b7,0xa7a9a11b,0x2ba7251b,0x2dc22f0c,0xb1b6b2f7,0xac79aa63,0x30742e5f,
  0x2a632c79,0xae5fb074,0xaf0cadc2,0x32f731b6,0x211b27a9,0xa51baba7,0xb0d2b02c,0x34b7341a,0x317a3257,0xb552b61a,0xa902a2ad,0x2d0026ad,
  0x2f8c309f,0xb371b487,0xaddcac2e,0x31cf3029,0x2c2e2ddc,0xb029b1cf,0xb09faf8c,0x34873371,0x22ad2902,0xa6adad00,0xb257b17a,0x361a3552,
  0x32cd33e3,0xb682b76f,0xaa31a420,0x2e2d281f,0x30ac31bb,0xb493b58d,0xaf3fad2a,0x33283122,0x2d2a2f3f,0xb122b328,0xb1bbb0ac,0x358d3493,
  0x24202a31,0xa81fae2d,0xb3e3b2cd,0x376f3682,0x341334bc,0xb7a6b85a,0xab5fa4e9,0x2f5928e8,0x319432da,0xb56ab68d,0xb052ae28,0x343e3219,
  0x2e283052,0xb219b43e,0xb2dab194,0x368d356a,0x24e92b5f,0xa8e8af59,0xb4bcb413,0x385a37a6,0x34c3358c,0xb85fb8f3,0xac47a5b2,0x304229b1,
  0x327e33fd,0xb63cb785,0xb106af26,0x34e7330f,0x2f263106,0xb30fb4e7,0xb3fdb27e,0x3785363c,0x25b22c47,0xa9b1b042,0xb58cb4c3,0x38f3385f,
  0x35773662,0xb8e5b982,0xacdea67b,0x30d72a7a,0x336b3493,0xb70ab83a,0xb1bbb012,0x358d3402,0x301231bb,0xb402b58d,0xb493b36b,0x383a370a,
  0x267b2cde,0xaa7ab0d7,0xb662b577,0x398238e5,0x36303741,0xb962ba04,0xad76a744,0x316c2b43,0x342e352a,0xb7d2b8ad,0xb271b092,0x3631347b,
  0x30923271,0xb47bb631,0xb52ab42e,0x38ad37d2,0x27442d76,0xab43b16c,0xb741b630,0x3a043962,0x36ee3815,0xb9d6ba7a,0xae0ea807,0x32012c06,
  0x34a735c4,0xb84ab91b,0xb329b113,0x36d234f3,0x31133329,0xb4f3b6d2,0xb5c4b4a7,0x391b384a,0x28072e0e,0xac06b201,0xb815b6ee,0x3a7a39d6,
  0x37b4388e,0xba41bae1,0xaea7a86b,0x32942c6a,0x35233662,0xb8a8b982,0xb3e3b194,0x376f356a,0x319433e3,0xb56ab76f,0xb662b523,0x398238a8,
  0x286b2ea7,0xac6ab294,0xb88eb7b4,0x3ae13a41,0x3841390f,0xbaa2bb3a,0xaf3fa8d0,0x33282cce,0x35a13705,0xb902b9e3,0xb44fb216,0x380535df,
  0x3216344f,0xb5dfb805,0xb705b5a1,0x39e33902,0x28d02f3f,0xacceb328,0xb90fb841,0x3b3a3aa2,0x38ac3997,0xbaf7bb83,0xafd8a935,0x33ba2d33,
  0x362137ac,0xb958ba3d,0xb4aeb298,0x38503654,0x329834ae,0xb654b850,0xb7acb621,0x3a3d3958,0x29352fd8,0xad33b3ba,0xb997b8ac,0x3b833af7,
  0x391c3a28,0xbb42bbbc,0xb039a999,0x34262d97,0x36a4382d,0xb9aaba90,0xb50eb31c,0x389936c6,0x331c350e,0xb6c6b899,0xb82db6a4,0x3a9039aa,
  0x29993039,0xad97b426,0xba28b91c,0x3bbc3b42,0x39923ac3,0xbb81bbe3,0xb085a9fe,0x346f2dfb,0x372a3886,0xb9f8badb,0xb570b3a0,0x38e03737,
  0x33a03570,0xb737b8e0,0xb886b72a,0x3adb39f8,0x29fe3085,0xadfbb46f,0xbac3b992,0x3be33b81,0xb9cfbb16,0x3b9c3bf1,0x30ac2a31,0xb493ae2d,
  0xb76fb8b4,0x3a1d3afe,0x35a133e3,0xb902b76f,0xb3e3b5a1,0x376f3902,0x38b4376f,0xbafeba1d,0xaa31b0ac,0x2e2d3493,0x3b1639cf,0xbbf1bb9c,
  0xb956ba74,0x3b633bd2,0x305f29cc,0xb44badc9,0xb6e7b859,0x39d23ab6,0x353f335e,0xb8bcb6ff,0xb35eb53f,0x36ff38bc,0x385936e7,0xbab6b9d2,
  0xa9ccb05f,0x2dc9344b,0x3a743956,0xbbd2bb63,0xb8e3b9de,0x3b1e3ba1,0x30122967,0xb402ad65,0xb662b801,0x39823a67,0x34de32da,0xb874b68d,
  0xb2dab4de,0x368d3874,0x38013662,0xba67b982,0xa967b012,0x2d653402,0x39de38e3,0xbba1bb1e,0xb876b952,0x3ace3b60,0x2f8c2902,0xb371ad00,
  0xb5e1b758,0x392e3a11,0x347e3257,0xb82ab61a,0xb257b47e,0x361a382a,0x375835e1,0xba11b92e,0xa902af8c,0x2d003371,0x39523876,0xbb60bace,
  0xb80db8ce,0x3a733b10,0x2ef3289e,0xb2deac9c,0xb562b6b3,0x38d639b3,0x342031d5,0xb7bdb5a5,0xb1d5b420,0x35a537bd,0x36b33562,0xb9b3b8d6,
  0xa89eaef3,0x2c9c32de,0x38ce380d,0xbb10ba73,0xb750b851,0x3a0d3ab0,0x2e5a2839,0xb24bac38,0xb4e5b613,0x387a394f,0x33863153,0xb721b52f,
  0xb153b386,0x352f3721,0x361334e5,0xb94fb87a,0xa839ae5a,0x2c38324b,0x38513750,0xbab0ba0d,0xb68eb7b4,0x399d3a41,0x2dc227a9,0xb1b6aba7,
  0xb46ab577,0x381a38e5,0x32cd30d2,0xb682b4b7,0xb0d2b2cd,0x34b73682,0x3577346a,0xb8e5b81a,0xa7a9adc2,0x2ba731b6,0x37b4368e,0xba41b99d,
  0xb5d2b6d1,0x392439c5,0x2d2a26e0,0xb122aade,0xb3e3b4de,0x376f3874,0x32163052,0xb5dfb43e,0xb052b216,0x343e35df,0x34de33e3,0xb874b76f,
  0xa6e0ad2a,0x2ade3122,0x36d135d2,0xb9c5b924,0xb51cb5f6,0x38a3393c,0x2c932617,0xb08daa16,0xb2f4b448,0x36a437fe,0x31602fa5,0xb53ab389,
  0xafa5b160,0x3389353a,0x344832f4,0xb7feb6a4,0xa617ac93,0x2a16308d,0x35f6351c,0xb93cb8a3,0xb46ab523,0x381a38a8,0x2bf6254d,0xafefa94d,
  0xb209b36b,0x35d4370a,0x30ac2ea7,0xb493b294,0xaea7b0ac,0x32943493,0x336b3209,0xb70ab5d4,0xa54dabf6,0x294d2fef,0x3523346a,0xb8a8b81a,
  0xb378b456,0x3715380a,0x2ac82484,0xaec3a884,0xb120b24a,0x34ff360e,0x2ff22da9,0xb3d3b19e,0xada9aff2,0x319e33d3,0x324a3120,0xb60eb4ff,
  0xa484aac8,0x28842ec3,0x34563378,0xb80ab715,0xb223b31c,0x35eb36c6,0x29992376,0xad97a776,0xb039b12d,0x3426350b,0x2e8d2cac,0xb27cb0a6,
  0xacacae8d,0x30a6327c,0x312d3039,0xb50bb426,0xa376a999,0x27762d97,0x331c3223,0xb6c6b5eb,0xb0d2b194,0x34b7356a,0x286b21e4,0xac6aa5e4,
  0xaea7b012,0x32943402,0x2d2a2b5f,0xb122af59,0xab5fad2a,0x2f593122,0x30122ea7,0xb402b294,0xa1e4a86b,0x25e42c6a,0x319430d2,0xb56ab4b7,
  0xaf0cb012,0x32f73402,0x267b2052,0xaa7aa452,0xacdeadf5,0x30d731e8,0x2b912967,0xaf8bad65,0xa967ab91,0x2d652f8b,0x2df52cde,0xb1e8b0d7,
  0xa052a67b,0x24522a7a,0x30122f0c,0xb402b2f7,0xac79ad2a,0x30743122,0x24201d7f,0xa81fa17f,0xaa31ab91,0x2e2d2f8b,0x28d026e0,0xacceaade,
  0xa6e0a8d0,0x2ade2cce,0x2b912a31,0xaf8bae2d,0x9d7fa420,0x217f281f,0x2d2a2c79,0xb122b074,0xa7a9a86b,0x2ba72c6a,0x1f1218b6,0xa3119cb6,
  0xa54da67b,0x294d2a7a,0x242021e4,0xa81fa5e4,0xa1e4a420,0x25e4281f,0x267b254d,0xaa7aa94d,0x98b69f12,0x1cb62311,0x286b27a9,0xac6aaba7,
  0xa5e43bff,0xb61a3b65,0xb98239cd,0xbb3a36dd,0xaf593bf2,0xb76f3b16,0xba043946,0xbb833581,0xb2943bd4,0xb85a3ab6,0xba7a38b2,0xbbbc341a,
  0xb4b73ba5,0xb8f33a49,0xbae13815,0xbbe33153,0xac9c3bfb,0xbb87356a,0xb986b9c9,0x361abb65,0xb5a53b7c,0xbbfd2b43,0xb74ebb1e,0x3907ba39,
  0xb8d63a60,0xbbc9b359,0xb1e8bbdd,0x3a97b889,0xba7338bc,0xbaf1b7f3,0x2e91bbf5,0x3b9cb4f3,0xafbd3bf1,0xbb10b785,0x3a0db93c,0x356a3b87,
  0xb88e3a93,0xb87fba9e,0x3bcbb340,0xb0743bec,0xbb183764,0xaf27bbf3,0x3bbd340e,0xb8ad3a7e,0xbc009cb6,0x35d4bb73,0x39e73966,0xbb2a3721,
  0xb16c3be2,0xb3d3bbc2,0x38ee3a4d,0xbb10b785,0xba043946,0x36bbbb42,0xa4523c00,0xb63cbb5e,0xbbfe28e8,0x3b2fb70a,0xb9243a21,0x346fbbb0,
  0xba67b8cc,0x3bcc3328,0xbbda3219,0x3a90b894,0xb2f73bcf,0x386fbaa9,0xba89389e,0x3bc2b3d3,0xbb1e374e,0x3bf5aec3,0xbbbab426,0x3a7638b7,
  0xbb5cb648,0x39bc3994,0xb6afbb45,0x2c063bfc,0xb493bbab,0xad003bfa,0x36e8bb37,0xb9d2397d,0xb43e3bb7,0x3be9b0be,0xb84abac1,0xb86f3aa9,
  0xbbcb3340,0x38d13a64,0x37c8bafe,0xbbf8adc9,0xb94fb9fc,0xb6a43b47,0x3c00217f,0xb654bb59,0x3576bb85,0xbbfb2c6a,0x377a3b13,0x38f3ba49,
  0xb4ff3b9a,0x3a313911,0x3af4b7e8,0xb0bebbe9,0xbc00a452,0xb6023b6a,0x39d63979,0x3b35b6f4,0xb47bbbae,0xbbf9ad65,0xb6ff3b32,0x397439da,
  0x3aacb86a,0xb2debbd0,0xbbe8b0d7,0xb7f33af1,0xb5bc3b78,0x2a7a3bfd,0x37373b24,0x3a313911,0xbbbab426,0xbbe730f0,0xbaba3855,0xb8653ab0,
  0x3109bbe6,0xb41abbbc,0xb902ba3d,0xbb1bb759,0x3bfd2ade,0x3b7ab5b1,0x39afb9a1,0x35d4bb73,0xb6763b52,0xb9a639aa,0xbb4f3682,0xbbfd2a7a,
  0xbafeb7c8,0xb91fba25,0xb523bb94,0x294dbbfe,0x3884ba9b,0x3a97b889,0x3bc8b371,0x3bee3042,0x3a29391b,0x37d23afb,0x308d3beb,0xb3283bcc,
  0xb72c3b27,0xbbfeaa16,0xb5c8bb76,0x39a6b9aa,0xb9d6b979,0x3546bb8e,0x3bf9ad33,0x37a63b07,0x3ae8b80a,0x3a7e38ad,0xb2943bd4,0xbbd332ad,
  0x33a23bc5,0xba5438e5,0xbb0ab79b,0x2d00bbfa,0xb7dd3af7,0xb916ba2d,0x3b98b50b,0xaa163bfe,0xb855baba,0x3bd6b27c,0xb13b3be4,0xbae5b80f,
  0x3bf8ad97,0xb46f3bb0,0xba60b8d6,0x3aceb835,0xb6313b60,0xb9c5b98b,0x3b3fb6c6,0x2c6a3bfb,0xb8453ac4,0x30a6bbea,0x344b3bb5,0xb916ba2d,
  0xb523bb94,0x396b39e3,0xbb57b65f,0x3c009fdb,0x3b81358d,0xbbfc2c06,0x3b18b764,0xb8fd3a41,0xbae13815,0x38a3ba85,0xb2633bd7,0xb2debbd0,
  0xb8993a8c,0x3aa5b874,0xbbce330f,0x3bea30a6,0xad33bbf9,0xb4873bac,0x38e0ba58,0xbad5382a,0x399939b8,0xb654bb59,0x28e83bfe,0x352fbb92,
  0xbbf5ae91,0x3b213742,0xb958b9f4,0x35b13b7a,0xb8ea3a50,0x3bc333ba,0xb185bbe1,0xbaa53874,0x313bbbe4,0xbbbf3402,0x38f83a45,0x376fbb16,
  0x353a3b90,0x39dab974,0xbb5cb648,0x23113c00,0xb9e7b966,0xb5173b96,0x3bf7adfb,0xb7d2bafb,0xb9373a11,0x37903b0d,0x3bf0afef,0x33babbc3,
  0x365fbb57,0xb9b3b99d,0xbb4a3699,0x2b433bfd,0xaef53bf4,0x3b1b3759,0x39fcb94f,0xb599bb7f,0xb219bbda,0xbbe0b19e,0xb8253ad8,0x38e53a54,
  0xb98239cd,0xb55e3b89,0x2cce3bfa,0x37903b0d,0x38e0ba58,0x3389bbc6,0xb1b6bbdf,0xb87fba9e,0xb8303ad1,0xb0423bee,0x347b3bae,0x39293a1d,
  0x36e8bb37,0x2776bbff,0xb60ebb68,0xb9c5b98b,0xb9c93986,0xbb633625,0xbbff26ad,0xbb89b55e,0x3a45b8f8,0x3ba3b4c3,0x3bfc2c38,0x3b4236bb,
  0xbab3385f,0xbbd332ad,0xbbe6b109,0xbaebb805,0x3b13b77a,0x3bf2af8b,0x3bc033eb,0x3a8538a3,0xba0d393c,0xbb3db6d2,0x25e4bbff,0x3b63b625,
  0x3b4ab699,0x39f83954,0xb4e73b9e,0xbbf52ec3,0xbbed305b,0xb835bace,0x3884ba9b,0x3bde31cf,0x3be830d7,0x34323bb8,0xba35390c,0xbb21b742,
  0xba4d38ee,0xb4abbba7,0x3bfb2c9c,0xb6d23b3d,0x3bdfb1b6,0xb2013bdc,0xbacbb83a,0x3a64b8d1,0xbba1b4cf,0x38fdba41,0x380a3ae8,0xbbe53122,
  0x39a139af,0xbb54366b,0xa9b1bbfe,0x3b963517,0xba89389e,0x381abade,0xafbd3bf1,0xb4abbba7,0x3bfc2c38,0xbb833581,0x39c0b990,0xb6023b6a,
  0xb9dfb970,0x3b92352f,0xbbf82d97,0x3b01b7bd,0x308d3beb,0xb840bac7,0x3aa2387a,0xbbe0b19e,0xbac1384a,0x3bd8b24b,0xbbe2b16c,0x3ade381a,
  0x3b9e34e7,0xba39b907,0x37fe3aee,0xb0f0bbe7,0xb5f7bb6c,0x23113c00,0x358dbb81,0xb94a3a00,0xb79b3b0a,0x3a15b933,0xbb8b3552,0x3bff2776,
  0xbaf437e8,0x3a6f38c1,0x32f7bbcf,0xbbd8324b,0x3acb383a,0x3074bbec,0xbbb23463,0x391f3a25,0x2ba7bbfc,0xbb7f3599,0x399939b8,0x35ebbb6f,
  0xbb3f36c6,0x3a093941,0x34b7bba5,0xbbf22f8b,0xbb243737,0x2e5f3bf6,0x3bb7343e,0x38c1ba6f,0x399039c0,0x3b5eb63c,0xa81fbbff,0xbb8eb546,
  0x37b2bb04,0xb929ba1d,0xbb90353a,0xa8843bff,0xbbd7b263,0xb8503abd,0x38bc3a73,0x3bb8b432,0xbb4f3682,0xb95d39f0,0xb4ff3b9a,0x2e5f3bf6,
  0x37fe3aee,0x3a7638b7,0x3bd232c6,0x3bd6b27c,0x3a7ab8b2,0x3805baeb,0x2ef5bbf4,0xb4dbbb9f,0xb958b9f4,0xbb4cb68d,0xbc009cb6,0xbb54366b,
  0xbb7635c8,0xbc001648,0xbb78b5bc,0xb9f0b95d,0x34633bb2,0xadc93bf8,0xb7153b2c,0xb9e3396b,0x3bddb1e8,0x3bde31cf,0x3ad13830,0x38db3a5c,
  0xadfbbbf7,0x3457bbb3,0x38ccba67,0x3ac7b840,0xbb98350b,0xb962b9eb,0x3676bb52,0x3c009648,0x281f3bff,0xbb3536f4,0xba19b92e,0x3487bbac,
  0x3bbd340e,0x31223be5,0xbab3385f,0xbab6b85a,0x3825bad8,0x3bef3010,0x34933bab,0xba153933,0xbbb5344b,0x2e2dbbf6,0x3b27372c,0xb9eb3962,
  0xb2c63bd2,0xbab0b865,0x3a81b8a8,0x34023bbf,0x3a213924,0xbb0137bd,0xb05bbbed,0x3bc93359,0x3b68b60e,0x251b3c00,0xbb85b576,0x3941ba09,
  0xbbce330f,0x3a6bb8c7,0xb7dd3af7,0x2e2dbbf6,0xb7153b2c,0x294dbbfe,0x35df3b71,0xb9b3b99d,0x36af3b45,0xba00b94a,0x3ba134cf,0xbbf32f27,
  0x3bc033eb,0xbbe33153,0x3aacb86a,0xb8503abd,0xbbe13185,0x3bd93232,0xbac4b845,0x38c73a6b,0xb92e3a19,0x3b07b7a6,0xbbef3029,0x3bc63389,
  0xa17f3c00,0x35ebbb6f,0xb97039df,0x3b2fb70a,0x390c3a35,0xb4f3bb9c,0xaade3bfd,0x368dbb4c,0xbbf02fef,0x38203adb,0x3899ba8c,0xbbd9b232,
  0xba8138a8,0x3ae5380f,0x2f59bbf2,0xbba334c3,0xb6ff3b32,0x3bff2884,0xb5f7bb6c,0xb99439bc,0x29b13bfe,0x3b2ab721,0xba29b91b,0xb4573bb3,
  0xbbfa2cce,0xb49f3ba9,0x3a5038ea,0x3adbb820,0xbb7135df,0x1fdb3c00,0x3b7c35a5,0x3954b9f8,0xba3d3902,0x34db3b9f,0x3bfc2ba7,0x36a4bb47,
  0xb87a3aa2,0x38943a90,0x3bc5b3a2,0x3010bbef,0xbbff26ad,0xbb3a36dd,0xb9373a11,0xb49f3ba9,0xbbef3029,0xbad5382a,0xb88e3a93,0xb2013bdc,
  0xbbc83371,0xba5c38db,0xb7b23b04,0xad653bf9,0xbb8b3552,0xb9d2397d,0xb6313b60,0x251b3c00,0x3bf12fbd,0x3b103785,0x393c3a0d,0x356a3b87,
  0x3bd232c6,0x3ab03865,0x38a83a81,0x34023bbf,0x3ba134cf,0x3a4138fd,0x380a3ae8,0x31223be5,0x3b603631,0x39c5398b,0x36c63b3f,0x2c6a3bfb,
  0xbbe2b16c,0xb3d3bbc2,0x3a4db8ee,0x3b103785,0xbb2cb715,0x294dbbfe,0x3b71b5df,0x39b3399d,0xb9dfb970,0x352fbb92,0x3bf8ad97,0x37bd3b01,
  0xb815bae1,0x38a3ba85,0x3bd73263,0x32de3bd0,0x3bcf32f7,0xb86f3aa9,0xb89eba89,0x3bc2b3d3,0x3a19392e,0xbb0737a6,0xb029bbef,0x3bc63389,
  0x35f73b6c,0xbc002311,0x358dbb81,0x3a00394a,0xae913bf5,0xbb21b742,0x39f4b958,0x35b13b7a,0xbbb7b43e,0x3be9b0be,0xbac1384a,0x386fbaa9,
  0xb8a8ba81,0x3ae5380f,0xbbf2af59,0x3ba3b4c3,0x2ba7bbfc,0x35993b7f,0xb999b9b8,0x3b6f35eb,0x3966b9e7,0xb5173b96,0xadfbbbf7,0x37d23afb,
  0x3b9a34ff,0xba31b911,0x37e83af4,0xb0bebbe9,0x35df3b71,0x9fdbbc00,0xb5a53b7c,0x3954b9f8,0xb7b23b04,0x3a1db929,0xbb90353a,0x3bff2884,
  0xbbda3219,0x3be0319e,0xbad8b825,0x38e53a54,0xbb78b5bc,0x2a7a3bfd,0x3b24b737,0xba31b911,0xb029bbef,0xbad5382a,0x3a93388e,0x3201bbdc,
  0x3a7ab8b2,0xbaebb805,0xaef53bf4,0x3b9fb4db,0x3b3736e8,0x2776bbff,0xbb68360e,0x39c5398b,0x3b523676,0x39a6b9aa,0xb682bb4f,0xbbfd2a7a,
  0xaf593bf2,0x3b16376f,0x3a04b946,0xb581bb83,0xbbdd31e8,0xb1cf3bde,0x3ad13830,0x3a5cb8db,0xb77abb13,0xbbf22f8b,0xb3eb3bc0,0x3a8538a3,
  0xbb27b72c,0xbbfeaa16,0xbb7635c8,0xb9a639aa,0x35a5bb7c,0xab43bbfd,0xb74ebb1e,0xba39b907,0x3bbd340e,0x3be5b122,0x3ab3b85f,0x385abab6,
  0xb0d73be8,0x34323bb8,0x390c3a35,0x3b213742,0x3af737dd,0x39163a2d,0x350b3b98,0xaa163bfe,0xb88e3a93,0xba9e387f,0xbbcb3340,0xbbecb074,
  0xba21b924,0xb7bdbb01,0xb05bbbed,0x3359bbc9,0x39afb9a1,0x3b54b66b,0x3bfea9b1,0x3b963517,0xbac4b845,0x30a6bbea,0x3bb5b44b,0x39163a2d,
  0x3a04b946,0x3b4236bb,0xa4523c00,0xbb5e363c,0x36af3b45,0xb94a3a00,0xbba1b4cf,0xaf27bbf3,0xbbeb308d,0xb840bac7,0x387abaa2,0x3be0319e,
  0x3a8c3899,0xbaa53874,0xb30fbbce,0x3bea30a6,0xbb1e374e,0xaec3bbf5,0x3bba3426,0xb8b73a76,0x217fbc00,0x3b6f35eb,0xb97039df,0xb70abb2f,
  0x3b0a379b,0xba153933,0xb552bb8b,0x3bff2776,0xba50b8ea,0x3bc333ba,0xbbe13185,0x3aa5b874,0x3bcbb340,0xba6438d1,0x37c8bafe,0xadc93bf8,
  0xb6ff3b32,0x2884bbff,0x35f73b6c,0xb9bcb994,0xb6c6bb3f,0x3a093941,0xbba5b4b7,0x3bf2af8b,0x3a113937,0xb790bb0d,0x2fef3bf0,0x33babbc3,
  0xbc00a452,0x3b6a3602,0xb9d6b979,0x36f43b35,0x3a3db902,0xbb9f34db,0x3bfc2ba7,0xbb47b6a4,0xb2633bd7,0x3850babd,0xba7338bc,0x3bb8b432,
  0xb9cdb982,0xb55e3b89,0x3bfaacce,0xb790bb0d,0x3bba3426,0xb0f0bbe7,0xbaba3855,0x3ab03865,0xbbc83371,0x38db3a5c,0x37b2bb04,0xbbf9ad65,
  0x39f4b958,0xbb4cb68d,0x9cb63c00,0x3b54b66b,0x398639c9,0x3b63b625,0xa6adbbff,0xbb89b55e,0xbafeb7c8,0xba25391f,0x35233b94,0x3bfe294d,
  0x3bd43294,0x385abab6,0xb8b2ba7a,0xbbbc341a,0xbbf72dfb,0xb4573bb3,0x3a6738cc,0x3ac7b840,0xb93cba0d,0xbb3db6d2,0xbbffa5e4,0xbb633625,
  0x39d63979,0x3b8e3546,0x3bf9ad33,0x3b07b7a6,0xba60b8d6,0xbbc9b359,0xbbdd31e8,0xba973889,0x3ad83825,0x3bef3010,0x3babb493,0x3a15b933,
  0x38ee3a4d,0x34ab3ba7,0xac9c3bfb,0xb6d23b3d,0xb855baba,0xb27cbbd6,0x313bbbe4,0x380fbae5,0x37643b18,0x2f273bf3,0xb40e3bbd,0xb8ad3a7e,
  0xb60ebb68,0xa51bbc00,0x3576bb85,0x3941ba09,0xb89eba89,0x381abade,0x3bf12fbd,0x34ab3ba7,0x35233b94,0xb9e3396b,0xbb57b65f,0x9fdbbc00,
  0xa8e8bbfe,0x3b2fb70a,0x3a213924,0xb46f3bb0,0xb3eb3bc0,0xbbe33153,0xb86abaac,0x3850babd,0x384a3ac1,0xbbd8324b,0x316cbbe2,0x3ade381a,
  0xad33bbf9,0x3bac3487,0xb8e03a58,0xb82abad5,0xb6483b5c,0xb9bcb994,0x3b45b6af,0x2c063bfc,0x3a35b90c,0x34f33b9c,0xbbfdaade,0x368dbb4c,
  0xb7e8baf4,0x3a6f38c1,0xbbcfb2f7,0x3bd8b24b,0xb13b3be4,0xb402bbbf,0x38f83a45,0xbb16b76f,0x39fcb94f,0xb6a43b47,0x217fbc00,0x36543b59,
  0xbbfe29b1,0x3b2ab721,0xb91b3a29,0x3457bbb3,0x37373b24,0xae5fbbf6,0xb43e3bb7,0x38c1ba6f,0x365fbb57,0xb99d39b3,0x3b4ab699,0xbbfd2b43,
  0xbbae347b,0x3bf92d65,0xbb32b6ff,0x397439da,0x3aa2387a,0xb894ba90,0x33a23bc5,0x3010bbef,0xb682bb4f,0xb95d39f0,0x3b9a34ff,0xae5fbbf6,
  0xb8e03a58,0x3bc63389,0xb1b6bbdf,0xba9e387f,0x3be63109,0xb41abbbc,0xba3d3902,0x3b1b3759,0xb552bb8b,0xb9d2397d,0x3b603631,0xa51bbc00,
  0x35c83b76,0x3c009648,0x35bcbb78,0xb9f0b95d,0x3a45b8f8,0xb4c3bba3,0xbbfcac38,0xb6bb3b42,0xba9bb884,0xba973889,0x33713bc8,0x3bee3042,
  0xb4b73ba5,0x3a4938f3,0x3ae1b815,0xb153bbe3,0xb50bbb98,0xb962b9eb,0xbb52b676,0xbc001648,0xbb4a3699,0xb95439f8,0xb4e73b9e,0x2ec33bf5,
  0x380a3ae8,0x3a7e38ad,0x3bd43294,0x3bd3b2ad,0x3a73b8bc,0x37f3baf1,0x2e91bbf5,0xb4f3bb9c,0x344b3bb5,0xae2d3bf6,0xb72c3b27,0xb9eb3962,
  0x3bdfb1b6,0x3bdc3201,0x3acb383a,0x38d13a64,0xad97bbf8,0x346fbbb0,0x38d6ba60,0x3aceb835,0xbc009cb6,0xbb73b5d4,0xb9e7b966,0xb721bb2a,
  0xb30fbbce,0x3a6bb8c7,0x3af737dd,0xae2d3bf6,0xbbfcac38,0xb581bb83,0x39c0b990,0x3b6a3602,0xb58d3b81,0xbbfc2c06,0xb764bb18,0x38fdba41,
  0x3a6738cc,0xb3283bcc,0xbbda3219,0xb894ba90,0x31853be1,0xbbd9b232,0x3845bac4,0x38c73a6b,0x3b9e34e7,0xb9073a39,0xb7febaee,0x3be7b0f0,
  0x39b8b999,0x36543b59,0xbbfe28e8,0x352fbb92,0xb493bbab,0x3bfa2d00,0xb6e83b37,0xb97db9d2,0xafefbbf0,0x38203adb,0xba8cb899,0x3bd93232,
  0xbacbb83a,0x3bec3074,0xbbb23463,0x3a25b91f,0xbb90353a,0x39dab974,0xb6483b5c,0xa311bc00,0xb5763b85,0xac6abbfb,0x377a3b13,0xba49b8f3,
  0x2cce3bfa,0x349fbba9,0xb8ea3a50,0x3adbb820,0x399039c0,0xb63cbb5e,0x281f3bff,0x3546bb8e,0x3bf42ef5,0xbb1bb759,0x394f39fc,0xb599bb7f,
  0x3aacb86a,0xbbd032de,0x3be830d7,0xbaf1b7f3,0xa6adbbff,0xbb3a36dd,0x3a113937,0x349fbba9,0xb7febaee,0xb8b73a76,0x3bd232c6,0xb27cbbd6,
  0xbad1b830,0xb0423bee,0x3baeb47b,0xb929ba1d,0xbbfdaade,0x35b13b7a,0x39afb9a1,0xbb73b5d4,0xa5e43bff,0x3b65361a,0x3982b9cd,0xb6ddbb3a,
  0x34633bb2,0x3bf82dc9,0x3715bb2c,0xb96bb9e3,0x385f3ab3,0x3bd3b2ad,0x3109bbe6,0xbaebb805,0x3a29391b,0x3afbb7d2,0xb08dbbeb,0xbbccb328,
  0x2c9cbbfb,0xb56abb87,0xb986b9c9,0xbb65b61a,0xa81fbbff,0xb6f4bb35,0xba19b92e,0xbbacb487,0xb05bbbed,0xb835bace,0xba9bb884,0xbbdeb1cf,
  0xb3a2bbc5,0xb8e5ba54,0xbb0ab79b,0xbbfaad00,0x00000000,0x00000000,0x00000000,0x00000000,0xaa1f0000,0xaf64ada8,0xaf64b000,0xaa1fada8,
  0xada80000,0xada8b000,0x2da88000,0x2da83000,0xaf640000,0x2a1fada8,0x2a1f3000,0xaf64ada8,0xb0000000,0x30008000,0xb0000000,0x30008000,
  0xaf640000,0x2a1f2da8,0x2a1fb000,0xaf642da8,0xada80000,0xada83000,0x2da88000,0x2da8b000,0xaa1f0000,0xaf642da8,0xaf643000,0xaa1f2da8,
  0x00000000,0x00000000,0x00000000,0x00000000,0x2a1f8000,0x2f642da8,0x2f643000,0x2a1f2da8,0xada80000,0xada8b000,0x2da88000,0x2da83000,
  0x2f648000,0xaa1f2da8,0xaa1fb000,0x2f642da8,0xb0000000,0x30008000,0xb0000000,0x30008000,0x2f648000,0xaa1fada8,0xaa1f3000,0x2f64ada8,
  0xada80000,0xada83000,0x2da88000,0x2da8b000,0x2a1f8000,0x2f64ada8,0x2f64b000,0x2a1fada8,0x80000000,0x80000000,0x80000000,0x80000000,
  0x2a1f0000,0x2f64ada8,0x2f64b000,0x2a1fada8,0x2da80000,0x2da8b000,0xada88000,0xada83000,0x2f640000,0xaa1fada8,0xaa1f3000,0x2f64ada8,
  0x30000000,0xb0008000,0x30000000,0xb0008000,0x2f640000,0xaa1f2da8,0xaa1fb000,0x2f642da8,0x2da80000,0x2da83000,0xada88000,0xada8b000,
  0x2a1f0000,0x2f642da8,0x2f643000,0x2a1f2da8,0x80000000,0x80000000,0x80000000,0x80000000,0xaa1f8000,0xaf642da8,0xaf643000,0xaa1f2da8,
  0x2da80000,0x2da8b000,0xada88000,0xada83000,0xaf648000,0x2a1f2da8,0x2a1fb000,0xaf642da8,0x30000000,0xb0008000,0x30000000,0xb0008000,
  0xaf648000,0x2a1fada8,0x2a1f3000,0xaf64ada8,0x2da80000,0x2da83000,0xada88000,0xada8b000,0xaa1f8000,0xaf64ada8,0xaf64b000,0xaa1fada8,
  0x30003000,0x30003000,0x30003000,0x30003000,0x2f643000,0x2a1f2da8,0xaa1f0000,0xaf64ada8,0x2da83000,0xada80000,0xada8b000,0x2da88000,
  0x2a1f3000,0xaf64ada8,0x2f648000,0xaa1f2da8,0x00003000,0x8000b000,0x00003000,0x8000b000,0xaa1f3000,0x2f64ada8,0xaf640000,0x2a1f2da8,
  0xada83000,0x2da88000,0x2da8b000,0xada80000,0xaf643000,0xaa1f2da8,0x2a1f8000,0x2f64ada8,0x30003000,0x30003000,0x30003000,0x30003000,
  0xaf64b000,0xaa1fada8,0x2a1f8000,0x2f642da8,0x2da83000,0xada80000,0xada8b000,0x2da88000,0xaa1fb000,0x2f642da8,0xaf640000,0x2a1fada8,
  0x00003000,0x8000b000,0x00003000,0x8000b000,0x2a1fb000,0xaf642da8,0x2f648000,0xaa1fada8,0xada83000,0x2da88000,0x2da8b000,0xada80000,
  0x2f64b000,0x2a1fada8,0xaa1f0000,0xaf642da8,0xb0003000,0xb0003000,0xb0003000,0xb0003000,0xaf643000,0xaa1f2da8,0x2a1f0000,0x2f64ada8,
  0xada83000,0x2da80000,0x2da8b000,0xada88000,0xaa1f3000,0x2f64ada8,0xaf648000,0x2a1f2da8,0x80003000,0x0000b000,0x80003000,0x0000b000,
  0x2a1f3000,0xaf64ada8,0x2f640000,0xaa1f2da8,0x2da83000,0xada88000,0xada8b000,0x2da80000,0x2f643000,0x2a1f2da8,0xaa1f8000,0xaf64ada8,
  0xb0003000,0xb0003000,0xb0003000,0xb0003000,0x2f64b000,0x2a1fada8,0xaa1f8000,0xaf642da8,0xada83000,0x2da80000,0x2da8b000,0xada88000,
  0x2a1fb000,0xaf642da8,0x2f640000,0xaa1fada8,0x80003000,0x0000b000,0x80003000,0x0000b000,0xaa1fb000,0x2f642da8,0xaf648000,0x2a1fada8,
  0x2da83000,0xada88000,0xada8b000,0x2da80000,0xaf64b000,0xaa1fada8,0x2a1f0000,0x2f642da8,0x80008000,0x80008000,0x80008000,0x80008000,
  0x2a1f8000,0x2f642da8,0x2f643000,0x2a1f2da8,0x2da88000,0x2da83000,0xada80000,0xada8b000,0x2f648000,0xaa1f2da8,0xaa1fb000,0x2f642da8,
  0x30008000,0xb0000000,0x30008000,0xb0000000,0x2f648000,0xaa1fada8,0xaa1f3000,0x2f64ada8,0x2da88000,0x2da8b000,0xada80000,0xada83000,
  0x2a1f8000,0x2f64ada8,0x2f64b000,0x2a1fada8,0x80008000,0x80008000,0x80008000,0x80008000,0xaa1f0000,0xaf64ada8,0xaf64b000,0xaa1fada8,
  0x2da88000,0x2da83000,0xada80000,0xada8b000,0xaf640000,0x2a1fada8,0x2a1f3000,0xaf64ada8,0x30008000,0xb0000000,0x30008000,0xb0000000,
  0xaf640000,0x2a1f2da8,0x2a1fb000,0xaf642da8,0x2da88000,0x2da8b000,0xada80000,0xada83000,0xaa1f0000,0xaf642da8,0xaf643000,0xaa1f2da8,
  0x00008000,0x00008000,0x00008000,0x00008000,0xaa1f8000,0xaf642da8,0xaf643000,0xaa1f2da8,0xada88000,0xada83000,0x2da80000,0x2da8b000,
  0xaf648000,0x2a1f2da8,0x2a1fb000,0xaf642da8,0xb0008000,0x30000000,0xb0008000,0x30000000,0xaf648000,0x2a1fada8,0x2a1f3000,0xaf64ada8,
  0xada88000,0xada8b000,0x2da80000,0x2da83000,0xaa1f8000,0xaf64ada8,0xaf64b000,0xaa1fada8,0x00008000,0x00008000,0x00008000,0x00008000,
  0x2a1f0000,0x2f64ada8,0x2f64b000,0x2a1fada8,0xada88000,0xada83000,0x2da80000,0x2da8b000,0x2f640000,0xaa1fada8,0xaa1f3000,0x2f64ada8,
  0xb0008000,0x30000000,0xb0008000,0x30000000,0x2f640000,0xaa1f2da8,0xaa1fb000,0x2f642da8,0xada88000,0xada8b000,0x2da80000,0x2da83000,
  0x2a1f0000,0x2f642da8,0x2f643000,0x2a1f2da8,
};

constexpr int kThreads = 384;
constexpr int kCtas = 128;

#define PREP0 1600
#define PREPGAP 650
#define HT0 13800
#define HGAP 500
#define WQT 11800
#define QT 17800
#define QGAP 400
#define POSTGAP 1000
#define TAIL 3
#define PSW 6
constexpr int EARLY = 2, L0 = 2;

constexpr int NS1 = 6;
__host__ __device__ constexpr int slot1(int it) { return (it + 4) % NS1; }
__host__ __device__ constexpr uint32_t w1_off(int s) { return (s < 4 ? 2 * s + 1 : s + 4) * 16384; }
__host__ __device__ constexpr uint32_t x1_off(int it) { return ((it >> 1) & 3) * 32768; }
constexpr uint32_t ST2 = 32768;
constexpr uint32_t RA = 131072;
constexpr uint32_t RB = 163840;
constexpr uint32_t RU = 196608;
constexpr uint32_t Y_IN = RU;
constexpr uint32_t SM_ONES = 229376;
constexpr uint32_t SM_F2 = SM_ONES + 128;
constexpr uint32_t SM_BAR = 231424;
constexpr uint32_t SM_SCALE = SM_ONES + 1792;
constexpr uint32_t SM_MAX = SM_BAR + 512;
constexpr uint32_t SM_TOTAL = 232448;
constexpr uint32_t SM_BASE = 1024;
__host__ __device__ constexpr uint32_t kv_off(int h) { return RB + (h >> 1) * 16384 + (h & 1) * 2560; }

enum Bar { B_F1 = 0, B_F2 = 6, B_H = B_F2 + 4, B_KVL = 12, B_RDY = 20, B_Q = 34, B_MAX, B_ZERO, B_U, B_KV,
           B_E1 = 39, B_E2 = 45, B_I2 = B_E2 + 4,
           B_KVE = 51, B_VST, B_KVM, B_KVP, B_KVI, B_OW, B_ZST = 58,
           B_OFREE = 59, B_F2M, B_STG, B_Y, B_COUNT = 64, B_U2 = B_KVL };
__host__ __device__ constexpr int slot2(int n) { return n < 22 ? n & 3 : (0x1032510325ull >> (4 * (n - 22))) & 7; }
__host__ __device__ constexpr int par2(int n) { return n < 22 ? (n >> 2) & 1 : (0x326 >> (n - 22)) & 1; }

constexpr int KV_WORDS = 4096 + 128;
struct Scratch {
  float kv[8][KV_WORDS];
  unsigned kvflag[8 * 32], zflag[8 * 32], oflag[16 * 32], epoch[kCtas];
};
struct Params {
  CUtensorMap w1, x, k, v, w2, wo, o, outa, q, outb;
  const __nv_bfloat16* shift_k;
  const __nv_bfloat16* ssm_k;
  const __nv_bfloat16* ssm_d;
  const __nv_bfloat16* q_ptr;
  const __nv_bfloat16* w_ptr;
  const __nv_bfloat16* wo_ptr;
  uint64_t zero;
  Scratch* g;
  const uint32_t* tab;
};

__device__ __align__(128) Scratch g_scratch;
__device__ __align__(128) __nv_bfloat16 g_o[2048 * 1024];

#define TSTAMP(cond, i) do { } while (0)
#define GSTAMP(cond, i) do { } while (0)
#define KSTAMP(n) do { } while (0)
#define QSTAMP(n) do { } while (0)

#define JIT() do { } while (0)
constexpr int kSpinLimit = 1 << 16;

DEVI void mbar_init(uint32_t a, uint32_t c) { asm volatile("mbarrier.init.shared::cta.b64 [%0], %1;" :: "r"(a), "r"(c) : "memory"); }
DEVI void mbar_expect(uint32_t a, uint32_t b) { asm volatile("mbarrier.arrive.expect_tx.shared::cta.b64 _, [%0], %1;" :: "r"(a), "r"(b) : "memory"); }
DEVI void mbar_arrive(uint32_t a) { asm volatile("mbarrier.arrive.shared::cta.b64 _, [%0];" :: "r"(a) : "memory"); }
DEVI void mbar_arrive_if(uint32_t a, bool pred) {
  asm volatile("{\n.reg .pred p;\nsetp.ne.b32 p, %1, 0;\n@p mbarrier.arrive.shared::cta.b64 _, [%0];\n}" :: "r"(a), "r"((int)pred) : "memory");
}
DEVI void mbar_wait(uint32_t a, uint32_t parity) {
  asm volatile("{\n.reg .pred p;\n.reg .u32 n;\nmov.u32 n, 0;\nW_LOOP:\n"
               "mbarrier.try_wait.parity.shared::cta.b64 p, [%0], %1;\n@p bra W_DONE;\n"
               "add.u32 n, n, 1;\nsetp.lt.u32 p, n, %2;\n@p bra W_LOOP;\nW_DONE:\n}"
               :: "r"(a), "r"(parity), "n"(kSpinLimit) : "memory");
  JIT();
}
DEVI void mbar_wait4(uint32_t a, uint32_t b, uint32_t c, uint32_t d) {
  asm volatile("{\n.reg .pred p, q, r, s;\n.reg .u32 n;\nmov.u32 n, 0;\nW_LOOP:\n"
               "mbarrier.try_wait.parity.shared::cta.b64 p, [%0], 0;\nmbarrier.try_wait.parity.shared::cta.b64 q, [%1], 0;\n"
               "mbarrier.try_wait.parity.shared::cta.b64 r, [%2], 0;\nmbarrier.try_wait.parity.shared::cta.b64 s, [%3], 0;\n"
               "and.pred p, p, q;\nand.pred r, r, s;\nand.pred p, p, r;\n@p bra W_DONE;\n"
               "add.u32 n, n, 1;\nsetp.lt.u32 p, n, %4;\n@p bra W_LOOP;\nW_DONE:\n}"
               :: "r"(a), "r"(b), "r"(c), "r"(d), "n"(kSpinLimit) : "memory");
  JIT();
}
DEVI uint32_t mbar_test(uint32_t a, uint32_t parity) {
  uint32_t ok; asm volatile("{\n.reg .pred p;\nmbarrier.test_wait.parity.shared::cta.b64 p, [%1], %2;\nselp.u32 %0, 1, 0, p;\n}" : "=r"(ok) : "r"(a), "r"(parity) : "memory"); return ok;
}
DEVI void mbar_wait_unless(uint32_t ok, uint32_t a, uint32_t parity) {
  asm volatile("{\n.reg .pred p;\n.reg .u32 n;\nsetp.ne.u32 p, %3, 0;\n@p bra W_DONE;\nmov.u32 n, 0;\nW_LOOP:\n"
               "mbarrier.try_wait.parity.shared::cta.b64 p, [%0], %1;\n@p bra W_DONE;\n"
               "add.u32 n, n, 1;\nsetp.lt.u32 p, n, %2;\n@p bra W_LOOP;\nW_DONE:\n}"
               :: "r"(a), "r"(parity), "n"(kSpinLimit), "r"(ok) : "memory");
  JIT();
}
DEVI void mbar_wait_long(uint32_t a, uint32_t parity) {
  asm volatile("{\n.reg .pred p;\n.reg .u32 n;\nmov.u32 n, 0;\nW_LOOP:\n"
               "mbarrier.try_wait.parity.shared::cta.b64 p, [%0], %1, %3;\n@p bra W_DONE;\n"
               "add.u32 n, n, 1;\nsetp.lt.u32 p, n, %2;\n@p bra W_LOOP;\nW_DONE:\n}"
               :: "r"(a), "r"(parity), "n"(kSpinLimit), "r"(4000) : "memory");
  JIT();
}
DEVI void flag_wait(const unsigned* p, unsigned target) {
  int n = 0; unsigned v;
  do {
    asm volatile("ld.relaxed.gpu.global.u32 %0, [%1];" : "=r"(v) : "l"(p) : "memory");
  } while ((int)(v - target) < 0 && ++n < kSpinLimit);
  asm volatile("fence.acquire.gpu;" ::: "memory");
}
DEVI unsigned ld_relaxed(const unsigned* p) { unsigned v; asm volatile("ld.relaxed.gpu.global.u32 %0, [%1];" : "=r"(v) : "l"(p) : "memory"); return v; }
DEVI uint32_t clock32() { uint32_t t; asm volatile("mov.u32 %0, %%clock;" : "=r"(t)); return t; }
DEVI void pace(uint32_t t0, uint32_t n) { while (clock32() - t0 < n) __nanosleep(20); }
DEVI bool elect() { uint32_t p; asm volatile("{\n.reg .pred p;\nelect.sync _|p, 0xffffffff;\nselp.u32 %0, 1, 0, p;\n}" : "=r"(p)); return p; }
DEVI void fence_async_smem() { asm volatile("fence.proxy.async.shared::cta;" ::: "memory"); }
DEVI void bar_sync(int id, int n) { asm volatile("bar.sync %0, %1;" :: "r"(id), "r"(n) : "memory"); }
DEVI void cluster_sync() { asm volatile("barrier.cluster.arrive.relaxed.aligned;\nbarrier.cluster.wait.aligned;" ::: "memory"); }
DEVI void wg_fence() { asm volatile("wgmma.fence.sync.aligned;" ::: "memory"); }
DEVI void wg_commit() { asm volatile("wgmma.commit_group.sync.aligned;" ::: "memory"); }
template <int N> DEVI void wg_wait() { asm volatile("wgmma.wait_group.sync.aligned %0;" :: "n"(N) : "memory"); }
template <int N> DEVI void pin(uint32_t* r) {
#pragma unroll
  for (int i = 0; i < N; i++) asm volatile("" : "+r"(r[i]));
}
template <int N> DEVI void pin(float* r) {
#pragma unroll
  for (int i = 0; i < N; i++) asm volatile("" : "+f"(r[i]));
}

DEVI void tma2d(uint32_t dst, const CUtensorMap* m, int c0, int c1, uint32_t bar) {
  asm volatile("cp.async.bulk.tensor.2d.shared::cluster.global.mbarrier::complete_tx::bytes [%0], [%1, {%3, %4}], [%2];"
               :: "r"(dst), "l"(m), "r"(bar), "r"(c0), "r"(c1) : "memory");
}
DEVI void tma2d_mc(uint32_t dst, const CUtensorMap* m, int c0, int c1, uint32_t bar) {
  asm volatile("cp.async.bulk.tensor.2d.shared::cluster.global.mbarrier::complete_tx::bytes.multicast::cluster [%0], [%1, {%3, %4}], [%2], %5;"
               :: "r"(dst), "l"(m), "r"(bar), "r"(c0), "r"(c1), "h"((uint16_t)3) : "memory");
}
DEVI void tma3d(uint32_t dst, const CUtensorMap* m, int c0, int c1, int c2, uint32_t bar) {
  asm volatile("cp.async.bulk.tensor.3d.shared::cluster.global.mbarrier::complete_tx::bytes [%0], [%1, {%3, %4, %5}], [%2];"
               :: "r"(dst), "l"(m), "r"(bar), "r"(c0), "r"(c1), "r"(c2) : "memory");
}
DEVI void tma4d(uint32_t dst, const CUtensorMap* m, int c1, int c2, int c3, uint32_t bar) {
  asm volatile("cp.async.bulk.tensor.4d.shared::cluster.global.mbarrier::complete_tx::bytes [%0], [%1, {%3, %4, %5, %6}], [%2];"
               :: "r"(dst), "l"(m), "r"(bar), "r"(0), "r"(c1), "r"(c2), "r"(c3) : "memory");
}
DEVI void tma5d(uint32_t dst, const CUtensorMap* m, int c0, int c1, int c3, int c4, uint32_t bar) {
  asm volatile("cp.async.bulk.tensor.5d.shared::cluster.global.mbarrier::complete_tx::bytes [%0], [%1, {%3, %4, %5, %6, %7}], [%2];"
               :: "r"(dst), "l"(m), "r"(bar), "r"(c0), "r"(c1), "r"(0), "r"(c3), "r"(c4) : "memory");
}
DEVI void tma2d_store(const CUtensorMap* m, uint32_t src, int c0, int c1) {
  asm volatile("cp.async.bulk.tensor.2d.global.shared::cta.bulk_group [%0, {%2, %3}], [%1];" :: "l"(m), "r"(src), "r"(c0), "r"(c1) : "memory");
}
DEVI void tma2d_store_e(const CUtensorMap* m, uint32_t src, int c0, int c1) {
  asm volatile("{\n.reg .pred e;\nelect.sync _|e, 0xffffffff;\n@e cp.async.bulk.tensor.2d.global.shared::cta.bulk_group [%0, {%2, %3}], [%1];\n"
               "@e cp.async.bulk.commit_group;\n}" :: "l"(m), "r"(src), "r"(c0), "r"(c1) : "memory");
}
DEVI void tma5d_store(const CUtensorMap* m, uint32_t src, int c0, int c1, int c3, int c4) {
  asm volatile("cp.async.bulk.tensor.5d.global.shared::cta.bulk_group [%0, {%2, %3, %4, %5, %6}], [%1];\ncp.async.bulk.commit_group;"
               :: "l"(m), "r"(src), "r"(c0), "r"(c1), "r"(0), "r"(c3), "r"(c4) : "memory");
}
DEVI void bulk_load(uint32_t dst, const void* src, uint32_t bytes, uint32_t bar) {
  asm volatile("cp.async.bulk.shared::cluster.global.mbarrier::complete_tx::bytes [%0], [%1], %2, [%3];" :: "r"(dst), "l"(src), "r"(bytes), "r"(bar) : "memory");
}
DEVI uint32_t mapa(uint32_t a, int rank) { uint32_t r; asm("mapa.shared::cluster.u32 %0, %1, %2;" : "=r"(r) : "r"(a), "r"(rank)); return r; }
DEVI void st_async4(uint32_t dst, uint32_t a, uint32_t b, uint32_t c, uint32_t d, uint32_t bar) {
  asm volatile("st.async.weak.shared::cluster.mbarrier::complete_tx::bytes.v4.b32 [%0], {%1,%2,%3,%4}, [%5];"
               :: "r"(dst), "r"(a), "r"(b), "r"(c), "r"(d), "r"(bar) : "memory");
}
DEVI void st_either8(bool local, uint32_t dst, uint32_t bar, uint32_t a, uint32_t b, uint32_t c, uint32_t d, uint32_t e, uint32_t f, uint32_t g, uint32_t h) {
  asm volatile("{\n.reg .pred p;\nsetp.ne.b32 p, %10, 0;\n@p st.shared.v4.b32 [%0], {%2,%3,%4,%5};\n@p st.shared.v4.b32 [%0 + 4096], {%6,%7,%8,%9};\n@p bra.uni E_DONE;\n"
               "st.async.weak.shared::cluster.mbarrier::complete_tx::bytes.v4.b32 [%0], {%2,%3,%4,%5}, [%1];\n"
               "st.async.weak.shared::cluster.mbarrier::complete_tx::bytes.v4.b32 [%0 + 4096], {%6,%7,%8,%9}, [%1];\nE_DONE:\n}"
               :: "r"(dst), "r"(bar), "r"(a), "r"(b), "r"(c), "r"(d), "r"(e), "r"(f), "r"(g), "r"(h), "r"((int)local) : "memory");
}
DEVI void red_async_max(uint32_t dst, uint32_t a, uint32_t bar) {
  asm volatile("red.async.relaxed.cluster.shared::cluster.mbarrier::complete_tx::bytes.max.u32 [%0], %1, [%2];" :: "r"(dst), "r"(a), "r"(bar) : "memory");
}
DEVI void pf_line(const void* p) { asm volatile("prefetch.global.L2 [%0];" :: "l"(p) : "memory"); }
DEVI void bulk_commit() { asm volatile("cp.async.bulk.commit_group;" ::: "memory"); }
DEVI void bulk_wait_all() { asm volatile("cp.async.bulk.wait_group 0;" ::: "memory"); }
DEVI void bulk_wait_read() { asm volatile("cp.async.bulk.wait_group.read 0;" ::: "memory"); }
DEVI void prefetch_map(const CUtensorMap* m) { asm volatile("prefetch.tensormap [%0];" :: "l"(m) : "memory"); }

__host__ __device__ constexpr uint32_t dlo(uint32_t off, uint32_t lbo) { return (off >> 4) + ((lbo >> 4) << 16); }
struct Desc {
  uint64_t v;
  DEVI Desc(uint64_t z, uint32_t base, uint32_t sbo, uint32_t mode) : v(z + (base | (uint64_t)((sbo >> 4) | (mode << 30)) << 32)) { asm volatile("" : "+l"(v)); }
  DEVI void renew(uint64_t z) { asm volatile("add.s64 %0, %0, %1;" : "+l"(v) : "l"(z)); }
  DEVI uint64_t at(uint32_t lo) const { uint64_t r; asm volatile("add.s64 %0, %1, %2;" : "=l"(r) : "l"(v), "l"((int64_t)(int32_t)lo)); return r; }
};
DEVI uint32_t pack_bf16(float lo, float hi) { uint32_t r; asm("cvt.rn.bf16x2.f32 %0, %1, %2;" : "=r"(r) : "f"(hi), "f"(lo)); return r; }
DEVI uint32_t pack_f16(float lo, float hi) { uint32_t r; asm("cvt.rn.f16x2.f32 %0, %1, %2;" : "=r"(r) : "f"(hi), "f"(lo)); return r; }
DEVI void stsm4(uint32_t addr, uint32_t r0, uint32_t r1, uint32_t r2, uint32_t r3) {
  asm volatile("stmatrix.sync.aligned.m8n8.x4.shared.b16 [%0], {%1,%2,%3,%4};" :: "r"(addr), "r"(r0), "r"(r1), "r"(r2), "r"(r3) : "memory");
}
DEVI void stsm4_t(uint32_t addr, uint32_t r0, uint32_t r1, uint32_t r2, uint32_t r3) {
  asm volatile("stmatrix.sync.aligned.m8n8.x4.trans.shared.b16 [%0], {%1,%2,%3,%4};" :: "r"(addr), "r"(r0), "r"(r1), "r"(r2), "r"(r3) : "memory");
}
DEVI void sts128(uint32_t addr, uint32_t a, uint32_t b, uint32_t c, uint32_t d) {
  asm volatile("st.shared.v4.b32 [%0], {%1,%2,%3,%4};" :: "r"(addr), "r"(a), "r"(b), "r"(c), "r"(d) : "memory");
}
DEVI void sts32(uint32_t addr, uint32_t v) { asm volatile("st.shared.b32 [%0], %1;" :: "r"(addr), "r"(v) : "memory"); }
DEVI uint32_t lds32(uint32_t a) { uint32_t v; asm volatile("ld.shared.b32 %0, [%1];" : "=r"(v) : "r"(a)); return v; }
DEVI void lds128(uint32_t* v, uint32_t a) {
  asm volatile("ld.shared.v4.b32 {%0,%1,%2,%3}, [%4];" : "=r"(v[0]), "=r"(v[1]), "=r"(v[2]), "=r"(v[3]) : "r"(a));
}
DEVI void ldg128(uint32_t* v, const void* p) {
  asm volatile("ld.global.nc.L1::no_allocate.v4.b32 {%0,%1,%2,%3}, [%4];" : "=r"(v[0]), "=r"(v[1]), "=r"(v[2]), "=r"(v[3]) : "l"(p));
}
DEVI float rcp(float x) { float r; asm("rcp.approx.ftz.f32 %0, %1;" : "=f"(r) : "f"(x)); return r; }
DEVI float exp_sat(float t) {
  float e, s;
  asm("ex2.approx.ftz.f32 %0, %1;" : "=f"(e) : "f"(t * 1.4426950408889634f));
  asm("add.sat.f32 %0, %1, 0f358637BD;" : "=f"(s) : "f"(e));
  return s;
}
DEVI uint32_t phi2(float a, float b) {
  uint32_t r, o;
  asm("cvt.rn.relu.bf16x2.f32 %0, %1, %2;" : "=r"(r) : "f"(b), "f"(a));
  asm("add.rn.bf16x2 %0, %1, %2;" : "=r"(o) : "r"(r), "r"(pack_bf16(exp_sat(a), exp_sat(b))));
  return o;
}
DEVI void arrive_both(uint32_t bar, int lane, bool pred = true) {
  asm volatile("{\n.reg .pred p;\n.reg .b32 r;\nsetp.ne.b32 p, %2, 0;\nmapa.shared::cluster.u32 r, %0, %1;\n@p mbarrier.arrive.shared::cluster.b64 _, [r];\n}"
               :: "r"(bar), "r"(lane & 1), "r"((int)(pred && lane < 2)) : "memory");
}
DEVI uint32_t bmul2(uint32_t a, uint32_t b) { uint32_t r; asm("mul.rn.bf16x2 %0, %1, %2;" : "=r"(r) : "r"(a), "r"(b)); return r; }
DEVI uint32_t badd2(uint32_t a, uint32_t b) { uint32_t r; asm("add.rn.bf16x2 %0, %1, %2;" : "=r"(r) : "r"(a), "r"(b)); return r; }
DEVI uint32_t bamax2(uint32_t a, uint32_t b) { uint32_t r; asm("max.NaN.xorsign.abs.bf16x2 %0, %1, %2;" : "=r"(r) : "r"(a), "r"(b)); return r; }
DEVI uint32_t hmul2(uint32_t a, uint32_t b) { uint32_t r; asm("mul.rn.f16x2 %0, %1, %2;" : "=r"(r) : "r"(a), "r"(b)); return r; }
DEVI uint32_t hadd2(uint32_t a, uint32_t b) { uint32_t r; asm("add.rn.f16x2 %0, %1, %2;" : "=r"(r) : "r"(a), "r"(b)); return r; }
DEVI uint32_t hsub2(uint32_t a, uint32_t b) { uint32_t r; asm("sub.rn.f16x2 %0, %1, %2;" : "=r"(r) : "r"(a), "r"(b)); return r; }
DEVI uint32_t hfma2(uint32_t a, uint32_t b, uint32_t c) { uint32_t r; asm("fma.rn.f16x2 %0, %1, %2, %3;" : "=r"(r) : "r"(a), "r"(b), "r"(c)); return r; }
DEVI uint32_t hfnma2(uint32_t a, uint32_t b, uint32_t c) {
  uint32_t r; asm("{\n.reg .b32 n;\nneg.f16x2 n, %1;\nfma.rn.f16x2 %0, n, %2, %3;\n}" : "=r"(r) : "r"(a), "r"(b), "r"(c)); return r;
}
DEVI float bf_lo(uint32_t w) { return __uint_as_float(w << 16); }
DEVI float bf_hi(uint32_t w) { return __uint_as_float(w & 0xffff0000u); }

DEVI uint32_t chan_exponent(const uint32_t* w) {
  uint32_t m[4];
#pragma unroll
  for (int i = 0; i < 4; i++) m[i] = bamax2(w[i], w[i + 4]);
#pragma unroll
  for (int i = 8; i < 32; i++) m[i & 3] = bamax2(m[i & 3], w[i]);
  uint32_t x = bamax2(bamax2(m[0], m[1]), bamax2(m[2], m[3])) & 0x7fff7fffu;
  x = max(x >> 16, x & 0xffffu);
  x = __reduce_max_sync(0xffffffffu, x);
  return min(x >> 7, 251u);
}
DEVI uint32_t to_f16(uint32_t w, uint32_t mul) { const uint32_t y = bmul2(w, mul); return pack_f16(bf_lo(y), bf_hi(y)); }

struct Tile { int j, r; };
DEVI Tile tile_of() {
  int cta; asm volatile("mov.u32 %0, %%ctaid.x;" : "=r"(cta));
  const int cl = cta >> 1, lo = (cl - 4) >> 31, hi = (35 - cl) >> 31;
  const int p = cl - 4 + (lo & (36 + 7 * cl)) + (hi & ((((cl - 36) * 37) >> 8) + 1)), g = p & 7, rr = p >> 3;
  return Tile{(g & 6) | (cta & 1), 2 * rr + (g & 1)};
}

static_assert(TAIL <= 4, "the releases up to stage 26 feed the ring");
__host__ __device__ constexpr bool prew(int it) { return it >= 28 && it < 31; }

DEVI void twiddle(uint32_t& ore, uint32_t& oim, uint32_t re, uint32_t im, uint32_t t, uint32_t s) {
  re = hfma2(t, im, re);
  oim = hfma2(s, re, im);
  ore = hfma2(t, oim, re);
}

__global__ void __cluster_dims__(2, 1, 1) __launch_bounds__(kThreads, 1)
fused_kernel(const __grid_constant__ Params P) {
  extern __shared__ __align__(1024) uint8_t smem[];
  const int tid = threadIdx.x, lane = tid & 31;
  const int warp = tid >> 5, warpu = __shfl_sync(0xffffffffu, tid >> 5, 0);
  const int cta = blockIdx.x, rho = cta & 1, cl = cta >> 1;
  const uint32_t sb = SM_BASE + (rho << 24);
  const uint32_t tstart = clock32();
  auto bar = [&](int i) INL { return sb + SM_BAR + 8u * i; };
  auto load1 = [&](int it, int s, int j, int r, bool mc) INL {
    const uint32_t fb = bar(B_F1 + s), xs = sb + x1_off(it);
    mbar_expect(fb, (it & 1) ? 16384 : 32768);
    tma4d(sb + w1_off(s), &P.w1, 32 * it, 2 * j, 1, fb);
    if (!(it & 1)) {
      if (mc) tma2d_mc(xs + rho * 8192, &P.x, 32 * it, 128 * r + 64 * rho, fb);
      else { tma2d(xs, &P.x, 32 * it, 128 * r, fb); tma2d(xs + 8192, &P.x, 32 * it, 128 * r + 64, fb); }
    }
  };
  TSTAMP(tid == 0, 0); GSTAMP(tid == 0, 62);

  if (warpu == 8 && elect()) {
    prefetch_map(&P.w1); prefetch_map(&P.x);
    for (int i = 0; i < EARLY; i++) mbar_init(bar(B_F1 + slot1(i)), 1);
    const Tile T = tile_of();
    for (int i = 0; i < EARLY; i++) load1(i, slot1(i), T.j, T.r, false);
    TSTAMP(true, 18);
    for (int i = EARLY; i < NS1; i++) mbar_init(bar(B_F1 + slot1(i)), 1);
    asm volatile("fence.mbarrier_init.release.cluster;" ::: "memory");
  }
  if (warpu == 9 && elect()) {
    if (sb != (uint32_t)__cvta_generic_to_shared(smem)) __trap();
#pragma unroll
    for (int i = B_F2; i < B_Q; i++) mbar_init(bar(i), 1);
    mbar_expect(bar(B_H), 32768);
    asm volatile("fence.mbarrier_init.release.cluster;" ::: "memory");
  }
  if (warpu == 10 && elect()) {
#pragma unroll
    for (int i = B_Q; i < B_KVE; i++) mbar_init(bar(i), i < B_E1 ? 1 : 16);
    mbar_expect(bar(B_Q), 32768); mbar_expect(bar(B_U), 16384); mbar_expect(bar(B_MAX), 1024);
    asm volatile("fence.mbarrier_init.release.cluster;" ::: "memory");
  }
  if (warpu == 11 && elect()) {
#pragma unroll
    for (int i = B_KVE; i < B_COUNT; i++) mbar_init(bar(i), i < B_OFREE ? 8 : i == B_F2M ? 3 : i < B_Y ? 4 : 9);
    mbar_expect(bar(B_Y), 8192); mbar_expect(bar(B_Y + 1), 8192);
    asm volatile("fence.mbarrier_init.release.cluster;" ::: "memory");
  }
  __syncwarp();
  cluster_sync();

  if (warpu < 8) {
    asm volatile("setmaxnreg.inc.sync.aligned.u32 %0;" :: "n"(232));
    const int wg = warp >> 2, wq = warp & 3, g = lane >> 2, q = lane & 3;
    constexpr uint32_t sbq = SM_BASE >> 4;
    const uint32_t wgu = warpu >> 2;
    const uint64_t z64 = P.zero;
    Desc dA(z64, sbq + wgu * 512, 1024, 1), dB(z64, sbq, 1024, 1);
    const int srow = wg * 64 + wq * 16 + (lane & 15);
    const uint32_t stm = srow * 128 + (((lane >> 4) ^ (srow & 7)) << 4);
    auto stage2 = [&](float* acc, int n, bool first, bool wait = true) INL {
      const int s = slot2(n);
      if (wait) mbar_wait(bar(B_F2 + s), par2(n));
      const uint32_t da = s * (ST2 >> 4) + dlo(0, 16), db = s * (ST2 >> 4) + dlo(16384, 8192);
      wg_fence();
      const uint64_t a0 = dA.at(da), b0 = dB.at(db);
      if (first) mma_n128_init(acc, a0, b0); else mma_n128(acc, a0, b0);
#pragma unroll
      for (int kk = 1; kk < 4; kk++) mma_n128(acc, a0 + 2 * kk, b0 + kk * (2048 >> 4));
      wg_commit();
    };
    auto release2 = [&](int n) INL { arrive_both(bar(B_E2 + slot2(n)), lane); };
    auto publish = [&](int b) INL { fence_async_smem(); __syncwarp(); mbar_arrive_if(bar(b), lane == 0); };

    float aq[64];
    uint32_t f1[8], tw[4];
    uint32_t su[2][32], sh[2][32];
    uint32_t x0[4][8], x1[4][8], p0[2][8], p1[2][8], z0[2][8], z1[2][8];
    auto s1 = [&](uint32_t* d, uint32_t base) INL {
      Desc db(z64, sbq + wgu * 1024 + dlo(base, 128), 512, 0);
      wg_fence();
      mma_s1_init(d, f1, db.v);
      mma_s1(d, f1 + 4, db.at(256 >> 4));
      wg_commit();
    };
    const uint64_t dre = Desc(z64, sbq + dlo(SM_F2 + 512, 128), 256, 0).v, dim = Desc(z64, sbq + dlo(SM_F2, 128), 256, 0).v;
    auto fwd2 = [&](uint32_t (*x)[8], int c) INL {
      uint32_t a[4][8];
#pragma unroll
      for (int t = 0; t < 4; t++) {
        uint32_t* s = (t < 2 ? sh[c >> 1] : su[c >> 1]) + 16 * (c & 1) + 8 * (t & 1);
        pin<8>(s);
#pragma unroll
        for (int i = 0; i < 4; i++) twiddle(a[t][i], a[t][4 + i], s[4 * (i & 1) + (i & 2)], s[4 * (i & 1) + (i & 2) + 1], tw[i & 2], tw[(i & 2) + 1]);
      }
      wg_fence();
#pragma unroll
      for (int t = 0; t < 4; t++) { mma_s2_init(x[t], a[t], dre); mma_s2(x[t], a[t] + 4, dim); }
      wg_commit();
    };
    auto half2 = [&](uint32_t (*x)[8], uint32_t* s) INL {
      uint32_t a[2][8];
      pin<16>(s);
#pragma unroll
      for (int t = 0; t < 2; t++)
#pragma unroll
        for (int i = 0; i < 4; i++) twiddle(a[t][i], a[t][4 + i], s[8 * t + 4 * (i & 1) + (i & 2)], s[8 * t + 4 * (i & 1) + (i & 2) + 1], tw[i & 2], tw[(i & 2) + 1]);
      wg_fence();
#pragma unroll
      for (int t = 0; t < 2; t++) { mma_s2_init(x[t], a[t], dre); mma_s2(x[t], a[t] + 4, dim); }
      wg_commit();
    };
    auto product = [&](uint32_t (*a)[8], uint32_t (*x)[8], int i) INL {
#pragma unroll
      for (int t = 0; t < 4; t++) { pin<2>(x[t] + i); pin<2>(x[t] + 4 + i); }
      auto hr = [&](int l) INL { return x[l >> 1][i + (l & 1)]; };
      auto hi = [&](int l) INL { return x[l >> 1][4 + i + (l & 1)]; };
      auto ur = [&](int l) INL { return x[2 + (l >> 1)][i + (l & 1)]; };
      auto ui = [&](int l) INL { return x[2 + (l >> 1)][4 + i + (l & 1)]; };
      uint32_t gr[4], gi[4];
      gr[0] = hr(0); gi[0] = hi(0);
#pragma unroll
      for (int l = 1; l < 4; l++) { gr[l] = hadd2(hr(l), hi(l - 1)); gi[l] = hsub2(hi(l), hr(l - 1)); }
#pragma unroll
      for (int p = 0; p < 4; p++) {
        uint32_t re = hfnma2(gi[0], ui(p), hmul2(gr[0], ur(p))), im = hfma2(gi[0], ur(p), hmul2(gr[0], ui(p)));
#pragma unroll
        for (int l = 1; l <= p; l++) {
          re = hfnma2(gi[l], ui(p - l), hfma2(gr[l], ur(p - l), re));
          im = hfma2(gi[l], ur(p - l), hfma2(gr[l], ui(p - l), im));
        }
        a[p >> 1][i + (p & 1)] = re; a[p >> 1][4 + i + (p & 1)] = im;
      }
#pragma unroll
      for (int t = 0; t < 2; t++) { pin<2>(a[t] + i); pin<2>(a[t] + 4 + i); }
    };
    auto inv1 = [&](uint32_t (*z)[8], uint32_t (*a)[8]) INL {
      wg_fence();
#pragma unroll
      for (int t = 0; t < 2; t++) { mma_s2_init(z[t], a[t], dre); mma_s2_neg(z[t], a[t] + 4, dim); }
      wg_commit();
    };
    auto zstore = [&](uint32_t (*z)[8], int c) INL {
      const uint32_t zoff = sb + RB + (q >> 1) * (RU + 16 - RB) + (8 * rho + 4 * wg) * 2048 + (4 * (8 * wq + g) + 2 * (q & 1)) * 16;
#pragma unroll
      for (int t = 0; t < 2; t++) {
        uint32_t a[8];
        pin<8>(z[t]);
#pragma unroll
        for (int i = 0; i < 4; i++) twiddle(a[i], a[4 + i], z[t][i], z[t][4 + i], tw[i & 2], tw[(i & 2) + 1]);
        const uint32_t dst = zoff + t * (16384 - rho * 32768) + c * 2048;
        sts128(dst, a[0], a[1], a[2], a[3]);
        sts128(dst + 16, a[4], a[5], a[6], a[7]);
      }
    };
    float kvr[18];
    auto kvstore = [&]() INL {
      const uint32_t dst = sb + kv_off(warp >> 1) + (warp & 1) * 256 + lane * 4;
      pin<18>(kvr);
#pragma unroll
      for (int b = 0; b < 4; b++) { sts32(dst + b * 512, pack_bf16(kvr[4 * b], kvr[4 * b + 1])); sts32(dst + b * 512 + 128, pack_bf16(kvr[4 * b + 2], kvr[4 * b + 3])); }
      sts32(dst + 2048, pack_bf16(kvr[16], kvr[16])); sts32(dst + 2176, pack_bf16(kvr[17], kvr[17]));
      publish(B_KVI);
    };
    {
      float ak[64], av[64];
      Desc dK(z64, sbq + wgu * 256, 1024, 1);
      auto kstep = [&](int c, int i) INL {
        const int s = slot1(c);
        if (!prew(c - 1)) mbar_wait(bar(B_F1 + s), (c / NS1 + i) & 1);
        TSTAMP(tid == 0 && c == 0, 1);
        const uint32_t dx = dlo(x1_off(c + 6 * i), 16), dk = dlo(w1_off(s), 16);
        const uint64_t xb = dB.at(dx) + (c & 1) * 4;
        wg_fence();
        if (c == 0) { mma_kt_init(ak, dK.at(dk), xb); mma_kt_init(av, dK.at(dk + 512), xb); }
        else { mma_kt(ak, dK.at(dk), xb); mma_kt(av, dK.at(dk + 512), xb); }
        mma_kt(ak, dK.at(dk + 128), xb + 2);
        mma_kt(av, dK.at(dk + 640), xb + 2);
        wg_commit();
        wg_wait<1>();
        if (c > 0) arrive_both(bar(B_E1 + (s + NS1 - 1) % NS1), lane);
        if (prew(c)) mbar_wait(bar(B_F1 + slot1(c + 1)), ((c + 1) / NS1) & 1);
        KSTAMP(c + 6 * i);
      };
      auto renew = [&]() INL { dK.renew(z64); dB.renew(z64); };
      uint32_t kk[7], u[36], sw[4], mx[2], um = 0, eu;
      unsigned short dskip;
      const int cp = 4 * (warp & 1) + (lane >> 3), run = 8 * (warp >> 1) + (lane & 7);
      const uint32_t ua = sb + RB + run * 32 + ((warp ^ (lane >> 2)) & 1) * 16 + (lane >> 3) * 4;
      sts32(sb + SM_MAX + (lane & 15) * 4, 0);
      ldg128(sw, P.shift_k + (cl * 16 + 2 * cp) * 4);
      asm volatile("ld.global.nc.b16 %0, [%1];" : "=h"(dskip) : "l"(P.ssm_d + 8 * cta + warp));
#pragma unroll
      for (int c = 0; c < L0; c++) kstep(c, 0);
      {
        pin<4>(sw);
        const uint32_t t0 = __byte_perm(sw[0], sw[2], 0x5410), t1 = __byte_perm(sw[0], sw[2], 0x7632), t2 = __byte_perm(sw[1], sw[3], 0x5410);
        sw[3] = __byte_perm(sw[1], sw[3], 0x7632); sw[0] = t0; sw[1] = t1; sw[2] = t2;
        pin<4>(sw);
      }
      float tap0 = lane == 0 ? bf_lo(dskip) : 0.f;
      pin<1>(&tap0);
#pragma unroll
      for (int e = 0; e < 36; e++) u[e] = 0;
#pragma unroll
      for (int e = 0; e < 7; e++) kk[e] = 0;
      renew();
#pragma unroll
      for (int c = L0; c < L0 + 6; c++) kstep(c, 0);
      renew();
#pragma unroll 1
      for (int i = 1; i < 4; i++) {
#pragma unroll
        for (int h = 0; h < 3; h++) {
          kstep(L0 + 2 * h, i);
          {
            const int slot = (3 * i + h + 4) & 7;
#pragma unroll
            for (int e = 4 * h; e < 4 * h + 4; e++) { u[e] = u[e + 12]; u[e + 12] = u[e + 24]; }
            pin<4>(u + 4 * h); pin<4>(u + 4 * h + 12);
            mbar_wait(bar(B_KVL + slot), h == 2 && i == 3);
#pragma unroll
            for (int e = 0; e < 4; e++) { kk[3 + e] = lds32(ua + slot * 8192 + e * 1024); u[24 + 4 * h + e] = lds32(ua + slot * 8192 + 4096 + e * 1024); }
          }
          kstep(L0 + 2 * h + 1, i);
          pin<7>(kk); pin<4>(u + 24 + 4 * h);
#pragma unroll
          for (int e = 0; e < 4; e++) {
            uint32_t& y = u[24 + 4 * h + e];
            y = bmul2(badd2(badd2(badd2(bmul2(kk[e], sw[3]), bmul2(kk[1 + e], sw[2])), bmul2(kk[2 + e], sw[1])), bmul2(kk[3 + e], sw[0])), y);
            um = bamax2(um, y);
          }
          if (h == 0) um = i == 1 ? 0 : um;
          kk[0] = kk[4]; kk[1] = kk[5]; kk[2] = kk[6];
          pin<4>(u + 24 + 4 * h); pin<1>(&um);
          if (h == 1) mbar_arrive_if(bar(B_KVE), lane == 0 && i == 2);
        }
      }
      um = bamax2(um, __shfl_xor_sync(0xffffffffu, um, 1));
      um = bamax2(um, __shfl_xor_sync(0xffffffffu, um, 2));
      red_async_max(mapa(sb + SM_MAX + cp * 8 + (q & 1) * 4, q >> 1), min((um >> (7 + 16 * (q & 1))) & 0xffu, 251u), mapa(bar(B_MAX), q >> 1));
      renew();
#pragma unroll
      for (int c = L0 + 24; c < 28; c++) {
        kstep(c, 0);
        if (c == L0 + 24) { ldg128(f1, P.tab + (tid & 127) * 4); ldg128(f1 + 4, P.tab + 512 + (tid & 127) * 4); ldg128(tw, P.tab + 1024 + (tid & 127) * 4); }
      }
      mbar_wait(bar(B_MAX), 0);
      TSTAMP(tid == 0, 5);
      asm volatile("ld.shared.v2.b32 {%0,%1}, [%2];" : "=r"(mx[0]), "=r"(mx[1]) : "r"(sb + SM_MAX + cp * 8));
      eu = lds32(sb + SM_MAX + (8 * rho + warp) * 4);
      const uint32_t ud = mapa(sb + RU + (lane >> 3) * 8192 + (2 * rho + wg) * 1024 + (run & 15) * 16, warp & 1), ub = mapa(bar(B_U), rho ^ 1);
#pragma unroll
      for (int i = 0; i < 4; i++) {
        kstep(28 + i, 0);
        if (i == 0) { pin<2>(mx); mx[0] = (0x00fd00fdu - (mx[0] | mx[1] << 16)) << 7; }
        uint32_t* y = u + 4 + 8 * i;
        pin<8>(y);
#pragma unroll
        for (int e = 0; e < 8; e++) y[e] = bmul2(y[e], mx[0]);
        st_either8((warpu & 1) == rho, ud + (i & 1) * 512 + (i >> 1) * 256, ub,
                   pack_f16(bf_lo(y[0]), bf_lo(y[1])), pack_f16(bf_lo(y[2]), bf_lo(y[3])), pack_f16(bf_lo(y[4]), bf_lo(y[5])), pack_f16(bf_lo(y[6]), bf_lo(y[7])),
                   pack_f16(bf_hi(y[0]), bf_hi(y[1])), pack_f16(bf_hi(y[2]), bf_hi(y[3])), pack_f16(bf_hi(y[4]), bf_hi(y[5])), pack_f16(bf_hi(y[6]), bf_hi(y[7])));
      }
      auto qstep = [&](int n) INL {
        if ((n & 3) == 0) { dA.renew(z64); dB.renew(z64); }
        stage2(aq, n, n == 0);
        wg_wait<1>();
        if (n == 0) arrive_both(bar(B_E1 + NS1 - 1), lane); else release2(n - 1);
        QSTAMP(n);
      };
      uint32_t pk[32];
      auto phik = [&](int i0, int i1) INL {
#pragma unroll
        for (int i = i0; i < i1; i++) { pin<2>(ak + 2 * i); pk[i] = phi2(ak[2 * i], ak[2 * i + 1]); pin<1>(pk + i); }
      };
      const uint32_t rot = tile_of().r & 3;
      const uint32_t kr = 16 * (lane >> 4) + 2 * (lane & 6) + 2 * (((wq >> 1) ^ (lane >> 2)) & 1) + (lane & 1);
      const uint32_t stt = sb + RA + wg * 16384 + kr * 64 + ((((2 * wq + ((lane >> 3) & 1)) ^ rot ^ (kr >> 1)) & 3) << 4);
      auto vst = [&](int k0, int k1) INL {
#pragma unroll
        for (int kt = k0; kt < k1; kt++) {
          float* a = av + 8 * kt;
          pin<8>(a);
          stsm4_t(stt + kt * 2048, pack_bf16(a[0], a[1]), pack_bf16(a[2], a[3]), pack_bf16(a[4], a[5]), pack_bf16(a[6], a[7]));
        }
      };
      float dkv[20];
      uint32_t kvmeta;
      Desc dV(z64, sbq + wgu * (1024u - (1024u << 16)) + dlo(RA, SM_ONES - RA), 512, 2);
      auto kvmma = [&](int k0, int k1) INL {
        if (k0 == 0) asm volatile("shf.l.wrap.b32 %0, %1, %1, %2;" : "=r"(kvmeta) : "r"(0xEE44EE44u), "r"((tid >> 3) & 8));
        wg_fence();
#pragma unroll
        for (int ks = k0; ks < k1; ks++) {
          const uint64_t db = dV.at(ks * (128u - (128u << 16)));
          if (ks == 0) mma_kv_init(dkv, pk, db, kvmeta); else mma_kv(dkv, pk + 4 * ks, db, kvmeta);
        }
        wg_commit();
      };
      float* gacc;
      auto kvred = [&](int b) INL {
        asm volatile("red.relaxed.gpu.global.add.v4.f32 [%0], {%1,%2,%3,%4};" :: "l"(gacc + (b ^ rot) * 128), "f"(dkv[4 * b]), "f"(dkv[4 * b + 1]), "f"(dkv[4 * b + 2]), "f"(dkv[4 * b + 3]) : "memory");
        if (b == 3) {
          asm volatile("{\n.reg .pred p;\nsetp.eq.s32 p, %3, 0;\n@p red.relaxed.gpu.global.add.v2.f32 [%0], {%1,%2};\n}"
                       :: "l"(gacc + 4096 - warp * 496 - g * 14), "f"(dkv[16]), "f"(dkv[18]), "r"(q) : "memory");
          __syncwarp();
          mbar_arrive_if(bar(B_KVP), lane == 0);
          TSTAMP(tid == 0, 4);
        }
      };
      uint32_t w[32], hmul;
      auto hload = [&](int i0, int i1) INL {
        const uint32_t a = sb + RB + warp * 4096 + (((lane >> 2) & 1) + (lane & 2) + 4 * (lane & 1) + (((lane << 2) ^ lane) & 24)) * 16;
#pragma unroll
        for (int i = i0; i < i1; i++) lds128(w + 4 * i, a + i * 512);
      };
      auto hmax = [&]() INL {
        pin<32>(w);
        tap0 += bf_lo(w[0]);
        w[0] = pack_bf16(tap0, bf_hi(w[0]));
        hmul = (252u - chan_exponent(w)) * 0x00800080u;
        const int e = min(max((int)(eu + 128 - (hmul >> 23)), 0), 254);
        asm volatile("st.shared.b16 [%0], %1;" :: "r"(sb + SM_SCALE + 2 * warp), "h"((unsigned short)(e << 7)) : "memory");
      };
      auto hstore = [&](int i0, int i1) INL {
        const uint32_t dst = sb + RB + warp * 4096 + (lane & 6) * 128 + ((lane ^ ((lane >> 2) & 6)) & 7) * 16;
#pragma unroll
        for (int i = i0; i < i1; i++) {
          pin<4>(w + 4 * i);
          const uint32_t w0 = i == 0 ? pack_f16(tap0 * bf_lo(hmul), bf_hi(w[0]) * bf_lo(hmul)) : to_f16(w[4 * i], hmul);
          sts128(dst + (i >> 1) * 1024 + (i & 1) * 128, w0, to_f16(w[4 * i + 1], hmul), to_f16(w[4 * i + 2], hmul), to_f16(w[4 * i + 3], hmul));
        }
      };
      auto kvload = [&]() INL {
        mbar_wait(bar(B_KV), 0);
        TSTAMP(tid == 0, 7);
#pragma unroll
        for (int b = 0; b < 4; b++)
          asm volatile("ld.global.cg.v4.f32 {%0,%1,%2,%3}, [%4];" : "=f"(kvr[4 * b]), "=f"(kvr[4 * b + 1]), "=f"(kvr[4 * b + 2]), "=f"(kvr[4 * b + 3]) : "l"(gacc + b * 128) : "memory");
        asm volatile("ld.global.cg.v2.f32 {%0,%1}, [%2];" : "=f"(kvr[16]), "=f"(kvr[17]) : "l"(gacc + 4096 - warp * 496 - g * 14 - q * 4) : "memory");
      };
      qstep(0);
      TSTAMP(tid == 0, 2);
      phik(0, 5);
      qstep(1);
      mbar_wait(bar(B_E1 + NS1 - 1), 1);
      vst(0, 3); phik(5, 9);
      qstep(2);
      vst(3, 6); phik(9, 13);
      qstep(3);
      vst(6, 8);
      publish(B_VST);
      phik(13, 17);
      qstep(4);
      mbar_wait4(bar(B_ZERO), bar(B_VST), bar(B_H), bar(B_H));
      kvmma(0, 4); hload(0, 3); phik(17, 22);
      gacc = &P.g->kv[tile_of().j][warp * 512 + lane * 4];
      qstep(5);
      hload(3, 5); phik(22, 27);
      qstep(6);
      hload(5, 8); phik(27, 32); kvmma(4, 8);
      qstep(7);
      pin<20>(dkv);
      mbar_arrive_if(bar(B_KVM), lane == 0);
      kvred(0);
      mbar_wait(bar(B_U2), 1);
      s1(su[0], RU);
      hmax(); hstore(0, 2); kvred(1);
      qstep(8);
      hstore(2, 5); kvred(2);
      qstep(9);
      kvred(3); hstore(5, 8);
      publish(B_VST);
      qstep(10);
      mbar_wait(bar(B_VST), 1);
      s1(sh[0], RB);
      mbar_wait(bar(B_F2M), 0);
      half2(x0 + 2, su[0]); half2(x1 + 2, su[0] + 16);
      qstep(11);
      half2(x0, sh[0]); half2(x1, sh[0] + 16);
      qstep(12);
      product(p0, x0, 0);
      qstep(13);
      product(p0, x0, 2);
      kvload();
      qstep(14);
      product(p1, x1, 0);
      qstep(15);
      product(p1, x1, 2);
    }

    float acc[64];
    {
      uint32_t pq[4][8];
      float dn[4][20];
      Desc dO(z64, sbq + dlo(0, 128), 512, 0);
      auto phiq = [&](int h) INL {
        pin<16>(aq + 16 * h);
#pragma unroll
        for (int i = 0; i < 8; i++) pq[h][i] = phi2(aq[16 * h + 2 * i], aq[16 * h + 2 * i + 1]);
        pin<8>(pq[h]);
      };
      auto omma = [&](int h) INL {
        wg_fence();
        mma_o_init(dn[h], pq[h], dO.at(kv_off(h) >> 4));
        mma_o(dn[h], pq[h] + 4, dO.at((kv_off(h) + 256) >> 4));
        wg_commit();
      };
      auto onorm = [&](int h) INL {
        pin<20>(dn[h]);
        const float i0 = rcp(dn[h][16] + 1e-6f), i1 = rcp(dn[h][18] + 1e-6f);
#pragma unroll
        for (int hf = 0; hf < 2; hf++) {
          const float* a = dn[h] + 8 * hf;
          stsm4(sb + (h >> 1) * ST2 + (stm ^ (((h & 1) * 2 + hf) << 5)), pack_bf16(a[0] * i0, a[1] * i0), pack_bf16(a[2] * i1, a[3] * i1),
                pack_bf16(a[4] * i0, a[5] * i0), pack_bf16(a[6] * i1, a[7] * i1));
        }
        if (h & 1) publish(B_OW + (h >> 1));
      };
      s1(su[1], RU + 8192);
      kvstore();
      wg_wait<1>();
      release2(15);
      TSTAMP(tid == 0, 6);
      uint32_t gf[4][4];
      auto gdup = [&]() INL {
#pragma unroll
        for (int i = 0; i < 4; i += 2) {
          pin<4>(gf[i + 1]);
          gf[i][0] = gf[i][1] = gf[i + 1][0]; gf[i][2] = gf[i][3] = gf[i + 1][1];
          gf[i + 1][0] = gf[i + 1][1] = gf[i + 1][2]; gf[i + 1][2] = gf[i + 1][3];
          pin<4>(gf[i]); pin<4>(gf[i + 1]);
        }
      };
      const uint32_t qa = sb + RA + warp * 4096 + lane * 32 + ((rho ^ g) & 1) * 16;
      uint32_t qv[4][4];
      auto qload = [&]() INL {
#pragma unroll
        for (int i = 0; i < 4; i++) lds128(qv[i], qa + i * 1024);
      };
      phiq(0);
      const uint32_t kvok = mbar_test(bar(B_KVI), 0);
      phiq(1);
      mbar_wait_unless(kvok, bar(B_KVI), 0);
      omma(0); omma(1);
      wg_wait<1>(); onorm(0);
      wg_wait<0>(); onorm(1);
      TSTAMP(tid == 0, 8);
      s1(sh[1], RB + 8192);
      phiq(2); omma(2); phiq(3);
      wg_wait<0>(); onorm(2);
      omma(3); inv1(z0, p0);
      wg_wait<1>(); onorm(3);
      TSTAMP(tid == 0, 9);
      inv1(z1, p1); fwd2(x0, 2);
      wg_wait<1>();
      mbar_wait4(bar(B_OW + 1), bar(B_F2), bar(B_F2 + 1), bar(B_Q));
      zstore(z0, 0); zstore(z1, 1);
      wg_wait<0>();
      dA.renew(z64); dB.renew(z64);
      stage2(acc, 16, true, false);
      fwd2(x1, 3);
      product(p0, x0, 0); product(p0, x0, 2);
      inv1(z0, p0);
      stage2(acc, 17, false, false);
      wg_wait<2>();
      release2(16);
      ldg128(gf[1], P.tab + 1536 + (tid & 127) * 4); ldg128(gf[3], P.tab + 2048 + (tid & 127) * 4);
      product(p1, x1, 0); product(p1, x1, 2);
      inv1(z1, p1);
      wg_wait<2>();
      zstore(z0, 2);
      gdup();
      wg_wait<0>();
      release2(17);
      zstore(z1, 3);
      publish(B_ZST);
      TSTAMP(tid == 0, 10);
      qload();
      mbar_wait(bar(B_ZST), 0);
      float y[64];
      {
        Desc db(z64, sbq + wgu * ((RU + 16 - RB) >> 4) + dlo(RB, 128), 2048, 0);
        wg_fence();
        mma_i2_init(y, gf[0], db.v, 0xEEEE4444u);
#pragma unroll
        for (int i = 1; i < 4; i++) mma_i2(y, gf[i], db.at(i * (512 >> 4)), 0xEEEE4444u);
        wg_commit();
      }
      uint32_t sc[4];
      lds128(sc, sb + SM_SCALE);
      TSTAMP(tid == 0, 11);
      stage2(acc, 18, false);
      TSTAMP(tid == 0, 13);
      wg_wait<1>();
      QSTAMP(18);
      arrive_both(bar(B_I2), lane);
      pin<64>(y);
      uint32_t yv[8][4];
#pragma unroll
      for (int i = 0; i < 8; i++)
#pragma unroll
        for (int m = 0; m < 4; m++) yv[i][m] = bmul2(pack_bf16(y[32 * (i >> 2) + (i & 3) + 8 * m], y[32 * (i >> 2) + (i & 3) + 8 * m + 4]), sc[m]);
      pin<32>(&yv[0][0]);
      stage2(acc, 19, false);
      wg_wait<1>();
      QSTAMP(19);
      release2(18);
      mbar_wait(bar(B_I2), 0);
      const uint32_t yr = mapa(sb + Y_IN + tid * 16 + warp * 1536, rho ^ 1), yb = mapa(bar(B_Y), rho ^ 1);
      dA.renew(z64); dB.renew(z64);
#pragma unroll
      for (int i = 0; i < 4; i++) {
        if (i) { stage2(acc, 19 + i, false); wg_wait<1>(); QSTAMP(19 + i); release2(18 + i); }
        pin<4>(qv[i]);
        sts128(qa + i * 1024, bmul2(yv[i][0], qv[i][0]), bmul2(yv[i][1], qv[i][1]), bmul2(yv[i][2], qv[i][2]), bmul2(yv[i][3], qv[i][3]));
        st_async4(yr + i * 512, yv[4 + i][0], yv[4 + i][1], yv[4 + i][2], yv[4 + i][3], yb + 8 * (i >> 1));
        if (i & 1) { __syncwarp(); mbar_arrive_if(bar(B_Y + (i >> 1)), lane == 0); }
      }
      TSTAMP(tid == 0, 12);
    }
#pragma unroll 1
    for (int n = 23; n < 32 - TAIL; n++) {
      stage2(acc, n, false);
      TSTAMP(tid == 0 && n == 26, 14);
      wg_wait<1>();
      release2(n - 1);
      QSTAMP(n);
    }
    {
      const Tile T = tile_of();
      dA.renew(z64); dB.renew(z64);
      mbar_wait(bar(B_STG), wgu ^ 1);
#pragma unroll
      for (int n = 32 - TAIL; n < 32; n++) {
        stage2(acc, n, false);
        if (n == 28) { wg_wait<1>(); release2(27); }
      }
      mbar_wait(bar(wgu ? B_E2 + 5 : B_STG), 1);
      mbar_arrive_if(bar(B_STG), wgu == 0 && lane == 0);
      const uint32_t stg = sb + (wgu ? RB - 8192 : RU + 16384);
      wg_wait<0>();
      TSTAMP(tid == 0, 17); TSTAMP(tid == 128, 15);
      pin<64>(acc);
#pragma unroll
      for (int c = 0; c < 2; c++) {
#pragma unroll
        for (int t = 0; t < 4; t++) {
          const float* a = acc + 32 * c + 8 * t;
          stsm4(stg + c * 8192 + (stm ^ (t << 5)), pack_bf16(a[0], a[1]), pack_bf16(a[2], a[3]), pack_bf16(a[4], a[5]), pack_bf16(a[6], a[7]));
        }
        fence_async_smem();
        __syncwarp();
        tma2d_store_e(&P.outa, stg + c * 8192 + warpu * 2048, 128 * T.j + 64 * c, 128 * T.r + 16 * warpu);
      }
      bulk_wait_read();
      TSTAMP(tid == 128, 16);
    }
  } else {
    asm volatile("setmaxnreg.dec.sync.aligned.u32 %0;" :: "n"(40));
    const Tile T = tile_of();
    const int j = T.j, r = T.r;
    auto kcol = [&](int n) INL {
      return n < 20 ? 128 * (j ^ ((n >> 1) & 1)) + 64 * (n & 1) : 128 * (((j & 6) + n - (n < 26 ? 18 : 24)) & 7) + (n < 26 ? 0 : 64);
    };
    if (warpu == 8) {
      uint32_t ph = 0;
      int s = slot1(EARLY);
#pragma unroll 1
      for (int it = EARLY; it < 32; ++it, s = s + 1 == NS1 ? 0 : s + 1) {
        if (it >= NS1) { mbar_wait(bar(B_E1 + s), (ph >> s) & 1); ph ^= 1u << s; }
        if (elect()) load1(it, s, j, r, true);
      }
      int qn = 0;
      auto loadq = [&](int n) INL {
        if ((0x9c000 >> n) & 1) { if (elect()) tma5d(sb + RA + qn * 8192, &P.q, 16 * cl, 2 * rho, 2 * (qn & 2), 2 * (qn & 1), bar(B_Q)); qn++; }
      };
#pragma unroll 1
      for (int n = 0; n < 16; ++n) {
        const int s = n & 3, kc = 64 * ((n + 12) & 15);
        mbar_wait(bar((n < 4 ? B_E1 : B_E2) + s), n < 4 ? (ph >> s) & 1 : ((n >> 2) - 1) & 1);
        const uint32_t st = sb + s * ST2, fb = bar(B_F2 + s);
        if (elect()) {
          mbar_expect(fb, n < 4 ? 16384 : ST2);
          tma4d(st + 16384, &P.w2, kc, 2 * j, 0, fb);
          if (n >= 4) tma2d_mc(st + rho * 8192, &P.x, kc, 128 * r + 64 * rho, fb);
        }
        loadq(n);
      }
      auto loadw = [&](int n) INL {
        const int s = n & 3;
        mbar_wait(bar(B_E2 + s), ((n >> 2) - 1) & 1);
        if (elect()) { mbar_expect(bar(B_F2 + s), n < 18 ? 16384 : ST2); tma4d(sb + s * ST2 + 16384, &P.wo, kcol(n), 2 * j, 0, bar(B_F2 + s)); }
      };
#pragma unroll 1
      for (int n = 16; n < 20; ++n) {
        loadw(n);
        loadq(n);
      }
#pragma unroll 1
      for (int n = 18; n < 20; ++n) {
        const uint32_t st = sb + (n & 3) * ST2, fb = bar(B_F2 + (n & 3));
        mbar_wait(bar(B_RDY + n - 18), 0);
        asm volatile("fence.proxy.async.global;" ::: "memory");
        if (elect()) { tma2d(st, &P.o, kcol(n), 128 * r, fb); tma2d(st + 8192, &P.o, kcol(n), 128 * r + 64, fb); }
      }
      mbar_wait(bar(B_OFREE), 0);
      uint64_t slots = 0x103251032510ull, frees = 0x103251032410ull;
      uint32_t pars = 0xc9f, kc = 128 * (j & 6) + 256;
#pragma unroll 1
      for (int n = 20; n < 32; ++n, slots >>= 4, frees >>= 4, pars >>= 1, kc += n == 26 ? 448 : 128) {
        const uint32_t s = slots & 7, st = sb + s * ST2, fb = bar(B_F2 + s);
        mbar_wait(bar(B_RDY + n - 18), 0);
        mbar_wait(bar(B_E2 + (frees & 7)), ~pars & 1);
        if (elect()) {
          mbar_expect(fb, ST2);
          tma4d(st + 16384, &P.wo, kc & 1023, 2 * j, 0, fb);
          tma2d_mc(st + rho * 8192, &P.o, kc & 1023, 128 * r + 64 * rho, fb);
        }
      }
    } else {
      const int at = tid - 288, aw = warpu - 9;
      const unsigned epoch = ld_relaxed(&P.g->epoch[cta]);
      if (aw < 2) {
        float4* zp = reinterpret_cast<float4*>(&P.g->kv[j][r * (KV_WORDS / 16)]) + at;
        zp[0] = zp[2] = make_float4(0.f, 0.f, 0.f, 0.f);
        sts128(sb + SM_ONES + lane * 64 + (lane & 6) * 8, 0x3f803f80u, 0x3f803f80u, 0x3f803f80u, 0x3f803f80u);
        fence_async_smem();
        bar_sync(4, 64);
        if (at == 0) {
          asm volatile("fence.release.gpu;\nred.relaxed.gpu.global.add.u32 [%0], 1;" :: "l"(&P.g->zflag[j * 32]) : "memory");
          flag_wait(&P.g->zflag[j * 32], 16u * (epoch + 1));
          mbar_arrive(bar(B_ZERO));
        }
        __syncwarp();
      } else {
#pragma unroll 1
        for (int m = -1; m < 16; m++) {
          const int s = (m >> 1) & 7;
          pace(tstart, PREP0 + (m + 1) * PREPGAP);
          if (m == 14) mbar_wait(bar(B_KVE), 0);
          if (elect()) {
            if (m < 0 || !(m & 1)) mbar_expect(bar(B_KVL + s), m < 0 ? 4096 : 8192);
            tma3d(sb + RB + (m < 0 ? 14 : m) * 4096, m > 0 && (m & 1) ? &P.v : &P.k, 16 * cl, 32 * rho + (m >> 31), 2 * (m & 14), bar(B_KVL + s));
          }
        }
#pragma unroll 1
        for (int m = 0; m < 8; m++) {
          pace(tstart, HT0 + m * HGAP);
          if (elect()) bulk_load(sb + RB + m * 4096, P.ssm_k + (size_t)(8 * cta + m) * 2048, 4096, bar(B_H));
        }
      }
      if (aw == 1) {
        if (cta < 3) pf_line(P.tab + cta * 768 + lane * 32);
#pragma unroll 1
        for (int m = 0; m < 16; m++) {
          pace(tstart, m < 4 ? WQT + m * 500 : QT + (m - 4) * QGAP);
          pf_line(m < 4 ? P.w_ptr + (size_t)(cta + ((2 * m + 6 + (lane >> 4)) & 7) * 128) * 3072 + (lane & 15) * 64
                        : (m < 12 ? P.q_ptr + cta * 16384 - 8192 : P.wo_ptr + cta * 8192 - 24576) + m * 2048 + lane * 64);
        }
      }
      uint32_t f2[4];
      ldg128(f2, P.tab + 2560 + at * 4);
      if (at == 0) { mbar_wait_long(bar(B_U), 0); fence_async_smem(); mbar_arrive(bar(B_U2)); }
      mbar_wait_long(bar(B_KVM), 0);
      sts128(sb + SM_F2 + at * 16, f2[0], f2[1], f2[2], f2[3]);
      fence_async_smem();
      __syncwarp();
      mbar_arrive_if(bar(B_F2M), lane == 0);
      if (aw == 2 && elect()) {
        mbar_wait(bar(B_KVP), 0);
        asm volatile("fence.release.gpu;\nred.relaxed.gpu.global.add.u32 [%0], 1;" :: "l"(&P.g->kvflag[j * 32]) : "memory");
        flag_wait(&P.g->kvflag[j * 32], 16u * (epoch + 1));
        mbar_arrive(bar(B_KV));
        TSTAMP(true, 19);
      }
      __syncwarp();
      if (aw < 2) {
        {
          const int c = aw;
          if (c == 1) {
            mbar_wait_long(bar(B_KVI), 0);
            if (elect()) { prefetch_map(&P.o); prefetch_map(&P.outb); prefetch_map(&P.outa); }
          }
          mbar_wait_long(bar(B_OW + c), 0);
          if (c == 1) mbar_wait(bar(B_ZERO), 1);
          if (elect()) {
            const uint32_t src = sb + c * ST2;
            tma2d_store(&P.o, src, 128 * j + 64 * c, 128 * r);
            tma2d_store(&P.o, src + 8192, 128 * j + 64 * c, 128 * r + 64);
            bulk_commit();
            bulk_wait_all();
            TSTAMP(c == 0, 21); TSTAMP(c == 1, 26);
            if (c == 0) mbar_arrive(bar(B_ZERO));
            asm volatile("mbarrier.arrive.shared::cluster.b64 _, [%0];\nmbarrier.arrive.shared::cluster.b64 _, [%1];"
                         :: "r"(mapa(bar(B_OFREE), 0)), "r"(mapa(bar(B_OFREE), 1)) : "memory");
            asm volatile("fence.release.gpu;\nst.relaxed.gpu.global.u32 [%0], %1;\nmbarrier.arrive.shared::cluster.b64 _, [%2];"
                         :: "l"(&P.g->oflag[r * 32 + 2 * j + c]), "r"(epoch + 1), "r"(mapa(bar(B_RDY + c), rho ^ 1)) : "memory");
            TSTAMP(c == 0, 22); TSTAMP(c == 1, 23);
          }
          __syncwarp();
        }
      } else {
        const unsigned* fp = &P.g->oflag[r * 32 + (kcol(18 + min(lane, 13)) >> 6)];
        bool done = lane > 13 || lane < 2;
        mbar_wait_long(bar(B_OW), 0);
        for (int i = 0; !__all_sync(0xffffffffu, done) && i < kSpinLimit; i++) {
          const bool now = !done && (int)(ld_relaxed(fp) - epoch) > 0;
          if (__any_sync(0xffffffffu, now)) {
            asm volatile("fence.acquire.gpu;\nfence.proxy.async.global;" ::: "memory");
            mbar_arrive_if(bar(B_RDY + lane), now);
            TSTAMP(lane == 2 && now, 24);
          }
          done |= now;
        }
        if (lane == 0) P.g->epoch[cta] = epoch + 1;
        TSTAMP(lane == 0, 25);
      }
#pragma unroll 1
      for (int m = aw; m < 16; m += 3) {
        const int u = 4 * (m & 7) + 2 * (m >> 3);
        mbar_wait_long(bar(B_Y + (m >> 3)), 0);
        TSTAMP(at == 0 && m == 0, 20);
        const uint32_t t0 = clock32();
        const uint32_t qa = sb + RA + u * 1024 + lane * 32 + ((rho ^ 1 ^ (lane >> 2)) & 1) * 16, ya = sb + Y_IN + u * 512 + lane * 16;
        uint32_t qv[2][4], yv[2][4];
#pragma unroll
        for (int h = 0; h < 2; h++) { lds128(qv[h], qa + h * 1024); lds128(yv[h], ya + h * 512); }
#pragma unroll
        for (int h = 0; h < 2; h++) sts128(qa + h * 1024, bmul2(qv[h][0], yv[h][0]), bmul2(qv[h][1], yv[h][1]), bmul2(qv[h][2], yv[h][2]), bmul2(qv[h][3], yv[h][3]));
        fence_async_smem();
        __syncwarp();
        if (elect()) tma5d_store(&P.outb, sb + RA + u * 1024, 1024 + 16 * cl, 2 * rho, (u >> 4) * 4 + (u & 3), (u >> 2) & 3);
        if (m < PSW) pace(t0, POSTGAP);
      }
      bulk_wait_read();
      TSTAMP(at == 0, 27);
    }
  }
  TSTAMP(tid == 128, 61); GSTAMP(tid == 128, 63);
}

typedef CUresult (*EncodeFn)(CUtensorMap*, CUtensorMapDataType, cuuint32_t, void*, const cuuint64_t*, const cuuint64_t*,
                             const cuuint32_t*, const cuuint32_t*, CUtensorMapInterleave, CUtensorMapSwizzle,
                             CUtensorMapL2promotion, CUtensorMapFloatOOBfill);

void encode(EncodeFn fn, CUtensorMap* m, const void* p, int rank, const cuuint64_t* dims, const cuuint64_t* strides,
            const cuuint32_t* box, CUtensorMapSwizzle sw) {
  const cuuint32_t es[5] = {1, 1, 1, 1, 1};
  fn(m, CU_TENSOR_MAP_DATA_TYPE_BFLOAT16, rank, const_cast<void*>(p), dims, strides, box, es, CU_TENSOR_MAP_INTERLEAVE_NONE, sw,
     CU_TENSOR_MAP_L2_PROMOTION_NONE, CU_TENSOR_MAP_FLOAT_OOB_FILL_NONE);
}
void encode2d(EncodeFn fn, CUtensorMap* m, const void* p, uint64_t cols, uint64_t rows, uint32_t bc, uint32_t br, CUtensorMapSwizzle sw) {
  const cuuint64_t dims[2] = {cols, rows}, strides[1] = {cols * 2};
  const cuuint32_t box[2] = {bc, br};
  encode(fn, m, p, 2, dims, strides, box, sw);
}
void encode3d(EncodeFn fn, CUtensorMap* m, const void* p) {
  const cuuint64_t dims[3] = {1024, 64, 32}, strides[2] = {2048 * 32, 2048};
  const cuuint32_t box[3] = {16, 32, 4};
  encode(fn, m, p, 3, dims, strides, box, CU_TENSOR_MAP_SWIZZLE_32B);
}
void encode4d(EncodeFn fn, CUtensorMap* m, const void* p, uint64_t cols, uint32_t rows, uint32_t nmat) {
  const cuuint64_t dims[4] = {64, 1024, 16, cols / 1024}, strides[3] = {cols * 2, 128, 2048};
  const cuuint32_t box[4] = {64, rows, 2, nmat};
  encode(fn, m, p, 4, dims, strides, box, CU_TENSOR_MAP_SWIZZLE_128B);
}
void encode5d(EncodeFn fn, CUtensorMap* m, const void* p, uint64_t cols, uint32_t n, uint32_t nw) {
  const cuuint64_t dims[5] = {cols, 4, 16, 8, 4}, strides[4] = {cols * 2 * 512, cols * 2 * 8, cols * 2, cols * 2 * 128};
  const cuuint32_t box[5] = {16, 2, 16, n, nw};
  encode(fn, m, p, 5, dims, strides, box, CU_TENSOR_MAP_SWIZZLE_32B);
}

}

extern "C" void kernel_launch(void* const* d_in, const int* in_sizes, int n_in, void* d_out, int out_size) {
  static EncodeFn fn = nullptr;
  static void *o_ptr = nullptr, *g_ptr = nullptr, *tab_ptr = nullptr;
  if (!fn) {
    cudaDriverEntryPointQueryResult qr;
    cudaGetDriverEntryPoint("cuTensorMapEncodeTiled", (void**)&fn, cudaEnableDefault, &qr);
    cudaGetSymbolAddress(&o_ptr, g_o);
    cudaGetSymbolAddress(&g_ptr, g_scratch);
    cudaGetSymbolAddress(&tab_ptr, d_tab);
    cudaFuncSetAttribute(fused_kernel, cudaFuncAttributeMaxDynamicSharedMemorySize, SM_TOTAL);
  }
  Params P;
  encode4d(fn, &P.w1, d_in[1], 3072, 32, 2);
  encode2d(fn, &P.x, d_in[0], 1024, 2048, 64, 64, CU_TENSOR_MAP_SWIZZLE_128B);
  encode4d(fn, &P.w2, d_in[1], 3072, 64, 1);
  encode4d(fn, &P.wo, d_in[2], 1024, 64, 1);
  encode2d(fn, &P.o, o_ptr, 1024, 2048, 64, 64, CU_TENSOR_MAP_SWIZZLE_128B);
  encode2d(fn, &P.outa, d_out, 2048, 2048, 64, 16, CU_TENSOR_MAP_SWIZZLE_128B);
  encode3d(fn, &P.k, d_in[4]);
  encode3d(fn, &P.v, d_in[5]);
  encode5d(fn, &P.q, d_in[3], 1024, 4, 2);
  encode5d(fn, &P.outb, d_out, 2048, 2, 1);
  P.shift_k = (const __nv_bfloat16*)d_in[6];
  P.ssm_k = (const __nv_bfloat16*)d_in[7];
  P.ssm_d = (const __nv_bfloat16*)d_in[8];
  P.q_ptr = (const __nv_bfloat16*)d_in[3];
  P.w_ptr = (const __nv_bfloat16*)d_in[1];
  P.wo_ptr = (const __nv_bfloat16*)d_in[2];
  P.zero = 0;
  P.g = (Scratch*)g_ptr;
  P.tab = (const uint32_t*)tab_ptr;
  fused_kernel<<<kCtas, kThreads, SM_TOTAL>>>(P);
}
```
